```python
import torch

def _softmax(x, axis=-1):
    return torch.softmax(x, dim=axis)

def _gelu(x):
    return torch.nn.functional.gelu(x, approximate='tanh')

def _silu(x):
    return torch.nn.functional.silu(x)

def _sigmoid(x):
    return torch.sigmoid(x)

def _layernorm(x, axis=-1, eps=1e-05):
    m = x.mean(dim=axis, keepdim=True)
    v = x.var(dim=axis, keepdim=True, unbiased=False)
    return (x - m) / torch.sqrt(v + eps)

def _scatter_add(tgt, idx, src, axis=0):
    return tgt.clone().index_add_(axis, idx, src)

def _segment_sum(src, seg, n):
    out = torch.zeros((n,) + src.shape[1:], dtype=src.dtype)
    return out.index_add_(0, seg, src)

def _pad(x, pw):
    flat = tuple((v for pair in reversed(pw) for v in pair))
    return torch.nn.functional.pad(x, flat)
kernel_name = 'recurrent_scan__memory_aug_recurrent_mem_tr__mixer_gmlp__prompt'

def setup_inputs():

    _w = lambda a: (lambda t: t.to(torch.bfloat16) if t.is_floating_point() else t)(torch.as_tensor(a))

    def _A_setup():
        B, S, Dm = (1, 2048, 640)
        H, Dh = (32, 128)
        M, seg = (8, 32)
        seg = min(seg, S)
        S = S // seg * seg
        return {'x': _w((lambda *s: torch.randn(*s, dtype=torch.bfloat16) * 0.05)(B, S, Dm)), 'mem0': _w((lambda *s: torch.randn(*s, dtype=torch.bfloat16) * 0.2)(B, M, Dm)), 'Wq': _w((lambda *s: torch.randn(*s, dtype=torch.bfloat16) * 0.8)(Dm, H, Dh) * Dm ** (-0.5)), 'Wk': _w((lambda *s: torch.randn(*s, dtype=torch.bfloat16) * 0.8)(Dm, H, Dh) * Dm ** (-0.5)), 'Wv': _w((lambda *s: torch.randn(*s, dtype=torch.bfloat16) * 0.2)(Dm, H, Dh) * Dm ** (-0.5)), 'Wo': _w((lambda *s: torch.randn(*s, dtype=torch.bfloat16) * 0.2)(H, Dh, Dm) * (H * Dh) ** (-0.5)), 'seg_len': seg}
    _A_in = _A_setup()

    def _B_setup():
        B, S, D, F = (1, 2048, 640, 1728)
        Fh = F // 2
        return {'x': _w((lambda *s: torch.randn(*s, dtype=torch.bfloat16) * 0.05)(B, S, D)), 'w_in': _w((lambda *s: torch.randn(*s, dtype=torch.bfloat16) * 0.4)(D, 2 * Fh)), 'w_sp': _w(0.01 * (lambda *s: torch.randn(*s, dtype=torch.bfloat16) * 0.4)(S, S)), 'b_sp': _w(1.0 + 0.01 * (lambda *s: torch.randn(*s, dtype=torch.bfloat16) * 0.1)(S)), 'w_out': _w((lambda *s: torch.randn(*s, dtype=torch.bfloat16) * 0.1)(Fh, D))}
    _B_in = _B_setup()
    return {'A_x': _A_in['x'], 'A_mem0': _A_in['mem0'], 'A_Wq': _A_in['Wq'], 'A_Wk': _A_in['Wk'], 'A_Wv': _A_in['Wv'], 'A_Wo': _A_in['Wo'], 'A_seg_len': _A_in['seg_len'], 'B_x': _B_in['x'], 'B_w_in': _B_in['w_in'], 'B_w_sp': _B_in['w_sp'], 'B_b_sp': _B_in['b_sp'], 'B_w_out': _B_in['w_out']}

def reference(A_x, A_mem0, A_Wq, A_Wk, A_Wv, A_Wo, A_seg_len, B_x, B_w_in, B_w_sp, B_b_sp, B_w_out):

    def _A_ref(x, mem0, Wq, Wk, Wv, Wo, seg_len):
        B, S, Dm = x.shape
        H, Dh = (Wq.shape[1], Wq.shape[2])
        M = mem0.shape[1]
        scale = Dh ** (-0.5)
        n_seg = S // seg_len
        L = M + seg_len
        idx = torch.arange(L)
        mask = (idx[:, None] < M) | (idx[:, None] >= idx[None, :])
        mem = mem0
        outs = []
        for s in range(n_seg):
            xs = x[:, s * seg_len:(s + 1) * seg_len, :].clone()
            h = torch.concatenate([mem, xs], axis=1)
            q = torch.einsum('btd,dhe->bhte', h, Wq)
            k = torch.einsum('btd,dhe->bhte', h, Wk)
            v = torch.einsum('btd,dhe->bhte', h, Wv)
            scores = torch.einsum('bhqe,bhke->bhqk', q, k) * scale
            scores = torch.where(mask[None, None], scores, -1000000000.0)
            p = _softmax(scores, axis=-1)
            o = torch.einsum('bhqk,bhke->bhqe', p, v)
            o = torch.einsum('bhte,hed->btd', o, Wo)
            mem = o[:, :M, :].clone()
            outs.append(o[:, M:, :])
        return torch.concatenate(outs, axis=1)

    def _B_ref(x, w_in, w_sp, b_sp, w_out):
        B, S, D = x.shape
        F = w_in.shape[-1]
        Fh = F // 2
        z = _gelu(torch.einsum('bsd,df->bsf', x, w_in))
        z1 = z[..., :Fh].clone()
        z2 = _layernorm(z[..., Fh:], axis=-1)
        g = torch.einsum('ts,bsf->btf', w_sp, z2) + b_sp[None, :, None]
        return torch.einsum('bsf,fd->bsd', z1 * g, w_out)
    x = A_x
    xn = _layernorm(x, axis=-1)
    s = _A_ref(xn, A_mem0, A_Wq, A_Wk, A_Wv, A_Wo, A_seg_len)
    g = _silu(_B_ref(xn, B_w_in, B_w_sp, B_b_sp, B_w_out))
    return x + s * g
```

```cpp
#include <cuda_runtime.h>
#include <cuda_bf16.h>
#include <cuda.h>
#include <stdint.h>

typedef __nv_bfloat16 bf16;

constexpr int S_   = 2048;
constexpr int D_   = 640;
constexpr int H_   = 32;
constexpr int DH_  = 128;
constexpr int MEM_ = 8;
constexpr int SEG_ = 32;
constexpr int NSEG_ = S_ / SEG_;
constexpr int HD_  = H_ * DH_;
constexpr int F_   = 1728;
constexpr int FH_  = 864;

__device__ bf16 g_xn[S_ * D_];
__device__ bf16 g_qkv[(size_t)S_ * 3 * HD_];
__device__ bf16 g_z[S_ * F_];
__device__ bf16 g_zg[S_ * FH_];
__device__ bf16 g_gate[S_ * D_];
__device__ bf16 g_kmem[NSEG_ * MEM_ * HD_];
__device__ bf16 g_vmem[NSEG_ * MEM_ * HD_];
__device__ bf16 g_o[(size_t)S_ * HD_];
__device__ uint2 g_h1[H_ * MEM_ * D_];
__device__ uint2 g_h2[MEM_ * D_ / 2];
__device__ uint2 g_hx[H_ * 4 * 3 * MEM_ * 16];

__device__ __forceinline__ uint32_t smem_u32(const void* p) { return (uint32_t)__cvta_generic_to_shared(p); }
__device__ __forceinline__ float bf2f(bf16 v) { return __bfloat162float(v); }
__device__ __forceinline__ float rbf(float v) { return __bfloat162float(__float2bfloat16_rn(v)); }
__device__ __forceinline__ uint32_t pack_bf16(float lo, float hi) {
    __nv_bfloat162 t = __floats2bfloat162_rn(lo, hi);
    return *reinterpret_cast<uint32_t*>(&t);
}
__device__ __forceinline__ float lo_f(uint32_t u) { return __uint_as_float(u << 16); }
__device__ __forceinline__ float hi_f(uint32_t u) { return __uint_as_float(u & 0xffff0000u); }

__device__ __forceinline__ void mbar_init(uint32_t bar, uint32_t cnt) {
    asm volatile("mbarrier.init.shared.b64 [%0], %1;" ::"r"(bar), "r"(cnt));
}
__device__ __forceinline__ void mbar_expect_tx(uint32_t bar, uint32_t bytes) {
    asm volatile("mbarrier.arrive.expect_tx.shared.b64 _, [%0], %1;" ::"r"(bar), "r"(bytes) : "memory");
}
__device__ __forceinline__ void mbar_arrive(uint32_t bar) {
    asm volatile("mbarrier.arrive.shared.b64 _, [%0];" ::"r"(bar) : "memory");
}
__device__ __forceinline__ void mbar_wait(uint32_t bar, uint32_t parity) {
    asm volatile(
        "{\n .reg .pred p;\n"
        "WAIT_%=:\n"
        " mbarrier.try_wait.parity.shared.b64 p, [%0], %1;\n"
        " @p bra DONE_%=;\n"
        " bra WAIT_%=;\n"
        "DONE_%=:\n}\n" ::"r"(bar), "r"(parity) : "memory");
}
__device__ __forceinline__ void tma_load_2d(uint32_t dst, const CUtensorMap* tm, uint32_t bar, int c0, int c1) {
    asm volatile(
        "cp.async.bulk.tensor.2d.shared::cluster.global.mbarrier::complete_tx::bytes [%0], [%1, {%3, %4}], [%2];"
        ::"r"(dst), "l"(tm), "r"(bar), "r"(c0), "r"(c1) : "memory");
}
__device__ __forceinline__ void wgmma_fence() { asm volatile("wgmma.fence.sync.aligned;" ::: "memory"); }
__device__ __forceinline__ void wgmma_commit() { asm volatile("wgmma.commit_group.sync.aligned;" ::: "memory"); }
template <int N> __device__ __forceinline__ void wgmma_wait() { asm volatile("wgmma.wait_group.sync.aligned %0;" ::"n"(N) : "memory"); }

__device__ __forceinline__ uint64_t make_desc(uint32_t addr, uint32_t lbo, uint32_t sbo) {
    return (uint64_t)((addr & 0x3FFFF) >> 4) | ((uint64_t)(lbo >> 4) << 16) | ((uint64_t)(sbo >> 4) << 32) | (1ull << 62);
}

template <int N> struct Wgmma;
template <> struct Wgmma<128> {
    static __device__ __forceinline__ void mma(float* d, uint64_t da, uint64_t db, int sd) {
        asm volatile(
            "{\n.reg .pred p;\nsetp.ne.b32 p, %66, 0;\n"
            "wgmma.mma_async.sync.aligned.m64n128k16.f32.bf16.bf16 "
            "{%0,%1,%2,%3,%4,%5,%6,%7,%8,%9,%10,%11,%12,%13,%14,%15,"
            "%16,%17,%18,%19,%20,%21,%22,%23,%24,%25,%26,%27,%28,%29,%30,%31,"
            "%32,%33,%34,%35,%36,%37,%38,%39,%40,%41,%42,%43,%44,%45,%46,%47,"
            "%48,%49,%50,%51,%52,%53,%54,%55,%56,%57,%58,%59,%60,%61,%62,%63},"
            "%64,%65,p,1,1,0,1;\n}\n"
            : "+f"(d[0]), "+f"(d[1]), "+f"(d[2]), "+f"(d[3]), "+f"(d[4]), "+f"(d[5]), "+f"(d[6]), "+f"(d[7]),
              "+f"(d[8]), "+f"(d[9]), "+f"(d[10]), "+f"(d[11]), "+f"(d[12]), "+f"(d[13]), "+f"(d[14]), "+f"(d[15]),
              "+f"(d[16]), "+f"(d[17]), "+f"(d[18]), "+f"(d[19]), "+f"(d[20]), "+f"(d[21]), "+f"(d[22]), "+f"(d[23]),
              "+f"(d[24]), "+f"(d[25]), "+f"(d[26]), "+f"(d[27]), "+f"(d[28]), "+f"(d[29]), "+f"(d[30]), "+f"(d[31]),
              "+f"(d[32]), "+f"(d[33]), "+f"(d[34]), "+f"(d[35]), "+f"(d[36]), "+f"(d[37]), "+f"(d[38]), "+f"(d[39]),
              "+f"(d[40]), "+f"(d[41]), "+f"(d[42]), "+f"(d[43]), "+f"(d[44]), "+f"(d[45]), "+f"(d[46]), "+f"(d[47]),
              "+f"(d[48]), "+f"(d[49]), "+f"(d[50]), "+f"(d[51]), "+f"(d[52]), "+f"(d[53]), "+f"(d[54]), "+f"(d[55]),
              "+f"(d[56]), "+f"(d[57]), "+f"(d[58]), "+f"(d[59]), "+f"(d[60]), "+f"(d[61]), "+f"(d[62]), "+f"(d[63])
            : "l"(da), "l"(db), "r"(sd));
    }
};
template <> struct Wgmma<192> {
    static __device__ __forceinline__ void mma(float* d, uint64_t da, uint64_t db, int sd) {
        asm volatile(
            "{\n.reg .pred p;\nsetp.ne.b32 p, %98, 0;\n"
            "wgmma.mma_async.sync.aligned.m64n192k16.f32.bf16.bf16 "
            "{%0,%1,%2,%3,%4,%5,%6,%7,%8,%9,%10,%11,%12,%13,%14,%15,"
            "%16,%17,%18,%19,%20,%21,%22,%23,%24,%25,%26,%27,%28,%29,%30,%31,"
            "%32,%33,%34,%35,%36,%37,%38,%39,%40,%41,%42,%43,%44,%45,%46,%47,"
            "%48,%49,%50,%51,%52,%53,%54,%55,%56,%57,%58,%59,%60,%61,%62,%63,"
            "%64,%65,%66,%67,%68,%69,%70,%71,%72,%73,%74,%75,%76,%77,%78,%79,"
            "%80,%81,%82,%83,%84,%85,%86,%87,%88,%89,%90,%91,%92,%93,%94,%95},"
            "%96,%97,p,1,1,0,1;\n}\n"
            : "+f"(d[0]), "+f"(d[1]), "+f"(d[2]), "+f"(d[3]), "+f"(d[4]), "+f"(d[5]), "+f"(d[6]), "+f"(d[7]),
              "+f"(d[8]), "+f"(d[9]), "+f"(d[10]), "+f"(d[11]), "+f"(d[12]), "+f"(d[13]), "+f"(d[14]), "+f"(d[15]),
              "+f"(d[16]), "+f"(d[17]), "+f"(d[18]), "+f"(d[19]), "+f"(d[20]), "+f"(d[21]), "+f"(d[22]), "+f"(d[23]),
              "+f"(d[24]), "+f"(d[25]), "+f"(d[26]), "+f"(d[27]), "+f"(d[28]), "+f"(d[29]), "+f"(d[30]), "+f"(d[31]),
              "+f"(d[32]), "+f"(d[33]), "+f"(d[34]), "+f"(d[35]), "+f"(d[36]), "+f"(d[37]), "+f"(d[38]), "+f"(d[39]),
              "+f"(d[40]), "+f"(d[41]), "+f"(d[42]), "+f"(d[43]), "+f"(d[44]), "+f"(d[45]), "+f"(d[46]), "+f"(d[47]),
              "+f"(d[48]), "+f"(d[49]), "+f"(d[50]), "+f"(d[51]), "+f"(d[52]), "+f"(d[53]), "+f"(d[54]), "+f"(d[55]),
              "+f"(d[56]), "+f"(d[57]), "+f"(d[58]), "+f"(d[59]), "+f"(d[60]), "+f"(d[61]), "+f"(d[62]), "+f"(d[63]),
              "+f"(d[64]), "+f"(d[65]), "+f"(d[66]), "+f"(d[67]), "+f"(d[68]), "+f"(d[69]), "+f"(d[70]), "+f"(d[71]),
              "+f"(d[72]), "+f"(d[73]), "+f"(d[74]), "+f"(d[75]), "+f"(d[76]), "+f"(d[77]), "+f"(d[78]), "+f"(d[79]),
              "+f"(d[80]), "+f"(d[81]), "+f"(d[82]), "+f"(d[83]), "+f"(d[84]), "+f"(d[85]), "+f"(d[86]), "+f"(d[87]),
              "+f"(d[88]), "+f"(d[89]), "+f"(d[90]), "+f"(d[91]), "+f"(d[92]), "+f"(d[93]), "+f"(d[94]), "+f"(d[95])
            : "l"(da), "l"(db), "r"(sd));
    }
};

template <int W>
__device__ __forceinline__ void ln_row(const bf16* __restrict__ src, bf16* __restrict__ dst, int lane) {
    constexpr int NP = W / 64;
    constexpr int REM = (W / 2) % 32;
    uint32_t v[NP + 1];
    const uint32_t* s32 = reinterpret_cast<const uint32_t*>(src);
    float sum = 0.f;
#pragma unroll
    for (int i = 0; i < NP; i++) { v[i] = s32[i * 32 + lane]; sum += lo_f(v[i]) + hi_f(v[i]); }
    if (REM) { v[NP] = (lane < REM) ? s32[NP * 32 + lane] : 0u; if (lane < REM) sum += lo_f(v[NP]) + hi_f(v[NP]); }
#pragma unroll
    for (int o = 16; o; o >>= 1) sum += __shfl_xor_sync(0xffffffffu, sum, o);
    float mean = sum * (1.0f / W);
    float vs = 0.f;
#pragma unroll
    for (int i = 0; i < NP; i++) { float a = lo_f(v[i]) - mean, b = hi_f(v[i]) - mean; vs += a * a + b * b; }
    if (REM && lane < REM) { float a = lo_f(v[NP]) - mean, b = hi_f(v[NP]) - mean; vs += a * a + b * b; }
#pragma unroll
    for (int o = 16; o; o >>= 1) vs += __shfl_xor_sync(0xffffffffu, vs, o);
    float var = rbf(vs * (1.0f / W));
    float mb = rbf(mean);
    float den = rbf(sqrtf(rbf(var + 1e-5f)));
    uint32_t* d32 = reinterpret_cast<uint32_t*>(dst);
#pragma unroll
    for (int i = 0; i < NP; i++) d32[i * 32 + lane] = pack_bf16(rbf(lo_f(v[i]) - mb) / den, rbf(hi_f(v[i]) - mb) / den);
    if (REM && lane < REM) d32[NP * 32 + lane] = pack_bf16(rbf(lo_f(v[NP]) - mb) / den, rbf(hi_f(v[NP]) - mb) / den);
}

__global__ void ln_kernel(const bf16* __restrict__ x) {
    int row = blockIdx.x * 8 + (threadIdx.x >> 5);
    ln_row<D_>(x + (size_t)row * D_, g_xn + (size_t)row * D_, threadIdx.x & 31);
}
__global__ void ln2_kernel() {
    int row = blockIdx.x * 8 + (threadIdx.x >> 5);
    bf16* p = g_z + (size_t)row * F_ + FH_;
    ln_row<FH_>(p, p, threadIdx.x & 31);
}

enum { EPI_STORE = 0, EPI_GELU = 1, EPI_SP = 2, EPI_SILU = 3, EPI_FINAL = 4 };
struct EpiParams {
    bf16* out; int ldo;
    const bf16* aux0;
    const bf16* aux1;
};

__device__ __forceinline__ float gelu_tanh_f(float x) {
    const float k0 = 0.7978845608028654f, k1 = 0.044715f;
    float inner = k0 * (x + k1 * x * x * x);
    return 0.5f * x * (1.0f + tanhf(inner));
}
__device__ __forceinline__ float silu_f(float x) { return x / (1.0f + expf(-x)); }

template <int BN, int EPI>
__global__ void __launch_bounds__(384, 1)
gemm_kernel(const __grid_constant__ CUtensorMap tmA, const __grid_constant__ CUtensorMap tmB,
            int M, int N, int K, EpiParams ep) {
    constexpr int BM = 128, BK = 64;
    constexpr int A_BYTES = BM * BK * 2;
    constexpr int B_BYTES = (BN / 64) * 8192;
    constexpr int STAGE = A_BYTES + B_BYTES;
    constexpr int NST = (200 * 1024) / STAGE;
    extern __shared__ __align__(1024) uint8_t smem_raw[];
    uint8_t* smem = (uint8_t*)(((uintptr_t)smem_raw + 1023) & ~(uintptr_t)1023);
    __shared__ __align__(8) uint64_t full_bar[NST], empty_bar[NST];

    const int tid = threadIdx.x, wg = tid >> 7;
    const int m0 = blockIdx.y * BM, n0 = blockIdx.x * BN;
    const int nk = (K + BK - 1) / BK;

    if (tid == 0) {
        for (int i = 0; i < NST; i++) { mbar_init(smem_u32(&full_bar[i]), 1); mbar_init(smem_u32(&empty_bar[i]), 2); }
        asm volatile("fence.mbarrier_init.release.cluster;" ::: "memory");
    }
    __syncthreads();

    if (wg == 0) {
        if (tid == 0) {
            for (int kt = 0; kt < nk; kt++) {
                int st = kt % NST; uint32_t ph = (kt / NST) & 1;
                mbar_wait(smem_u32(&empty_bar[st]), ph ^ 1);
                uint32_t fb = smem_u32(&full_bar[st]);
                mbar_expect_tx(fb, STAGE);
                uint32_t sa = smem_u32(smem + st * STAGE);
                tma_load_2d(sa, &tmA, fb, kt * BK, m0);
#pragma unroll
                for (int j = 0; j < BN / 64; j++) tma_load_2d(sa + A_BYTES + j * 8192, &tmB, fb, n0 + j * 64, kt * BK);
            }
        }
    } else {
        const int cw = wg - 1;
        float acc[BN / 2];
#pragma unroll
        for (int i = 0; i < BN / 2; i++) acc[i] = 0.f;
        for (int kt = 0; kt < nk; kt++) {
            int st = kt % NST; uint32_t ph = (kt / NST) & 1;
            mbar_wait(smem_u32(&full_bar[st]), ph);
            uint32_t sa = smem_u32(smem + st * STAGE) + cw * 64 * 128;
            uint32_t sb = smem_u32(smem + st * STAGE) + A_BYTES;
            wgmma_fence();
#pragma unroll
            for (int k = 0; k < BK / 16; k++) {
                uint64_t da = make_desc(sa + k * 32, 16, 1024);
                uint64_t db = make_desc(sb + k * 2048, 8192, 1024);
                Wgmma<BN>::mma(acc, da, db, 1);
            }
            wgmma_commit();
            wgmma_wait<0>();
            if ((tid & 127) == 0) mbar_arrive(smem_u32(&empty_bar[st]));
        }
        const int lane = tid & 31, wi = (tid >> 5) & 3, g = lane >> 2, t = lane & 3;
        const int r0 = m0 + cw * 64 + wi * 16 + g;
#pragma unroll
        for (int j = 0; j < BN / 8; j++) {
            int col = n0 + j * 8 + 2 * t;
            if (col >= N) continue;
#pragma unroll
            for (int hh = 0; hh < 2; hh++) {
                int row = r0 + hh * 8;
                float v0 = rbf(acc[4 * j + 2 * hh]), v1 = rbf(acc[4 * j + 2 * hh + 1]);
                uint32_t o;
                if (EPI == EPI_STORE) {
                    o = pack_bf16(v0, v1);
                } else if (EPI == EPI_GELU) {
                    o = pack_bf16(gelu_tanh_f(v0), gelu_tanh_f(v1));
                } else if (EPI == EPI_SP) {
                    float b = bf2f(ep.aux1[row]);
                    float g0 = rbf(v0 + b), g1 = rbf(v1 + b);
                    uint32_t z1 = *reinterpret_cast<const uint32_t*>(ep.aux0 + (size_t)row * F_ + col);
                    o = pack_bf16(lo_f(z1) * g0, hi_f(z1) * g1);
                } else if (EPI == EPI_SILU) {
                    o = pack_bf16(silu_f(v0), silu_f(v1));
                } else {
                    uint32_t xg = *reinterpret_cast<const uint32_t*>(ep.aux0 + (size_t)row * D_ + col);
                    uint32_t gt = *reinterpret_cast<const uint32_t*>(ep.aux1 + (size_t)row * D_ + col);
                    o = pack_bf16(lo_f(xg) + rbf(v0 * lo_f(gt)), hi_f(xg) + rbf(v1 * hi_f(gt)));
                }
                *reinterpret_cast<uint32_t*>(ep.out + (size_t)row * ep.ldo + col) = o;
            }
        }
    }
}

__device__ __forceinline__ void mma16816(float* c, const uint32_t* a, uint32_t b0, uint32_t b1) {
    asm volatile(
        "mma.sync.aligned.m16n8k16.row.col.f32.bf16.bf16.f32 {%0,%1,%2,%3}, {%4,%5,%6,%7}, {%8,%9}, {%0,%1,%2,%3};"
        : "+f"(c[0]), "+f"(c[1]), "+f"(c[2]), "+f"(c[3])
        : "r"(a[0]), "r"(a[1]), "r"(a[2]), "r"(a[3]), "r"(b0), "r"(b1));
}
__device__ __forceinline__ void ldsm_x4(uint32_t* r, uint32_t addr) {
    asm volatile("ldmatrix.sync.aligned.m8n8.x4.shared.b16 {%0,%1,%2,%3}, [%4];"
                 : "=r"(r[0]), "=r"(r[1]), "=r"(r[2]), "=r"(r[3]) : "r"(addr));
}
__device__ __forceinline__ void ldsm_x4_t(uint32_t* r, uint32_t addr) {
    asm volatile("ldmatrix.sync.aligned.m8n8.x4.trans.shared.b16 {%0,%1,%2,%3}, [%4];"
                 : "=r"(r[0]), "=r"(r[1]), "=r"(r[2]), "=r"(r[3]) : "r"(addr));
}
__device__ __forceinline__ uint4 ld_relaxed_v4(const void* p) {
    uint4 v;
    asm volatile("ld.relaxed.gpu.global.v4.u32 {%0,%1,%2,%3}, [%4];" : "=r"(v.x), "=r"(v.y), "=r"(v.z), "=r"(v.w) : "l"(p) : "memory");
    return v;
}
__device__ __forceinline__ void st_relaxed_v4(void* p, uint32_t a, uint32_t b, uint32_t c, uint32_t d) {
    asm volatile("st.relaxed.gpu.global.v4.u32 [%0], {%1,%2,%3,%4};" ::"l"(p), "r"(a), "r"(b), "r"(c), "r"(d) : "memory");
}
__device__ __forceinline__ void st_relaxed_v2(void* p, uint32_t a, uint32_t b) {
    asm volatile("st.relaxed.gpu.global.v2.u32 [%0], {%1,%2};" ::"l"(p), "r"(a), "r"(b) : "memory");
}
__device__ __forceinline__ void cp_async16(uint32_t dst, const void* src) {
    asm volatile("cp.async.cg.shared.global [%0], [%1], 16;" ::"r"(dst), "l"(src) : "memory");
}
__device__ __forceinline__ void cp_async_commit() { asm volatile("cp.async.commit_group;" ::: "memory"); }
template <int N> __device__ __forceinline__ void cp_async_wait() { asm volatile("cp.async.wait_group %0;" ::"n"(N) : "memory"); }

constexpr int SPIN_LIMIT = 4000000;

__device__ __forceinline__ uint4 poll_ll(const void* p, uint32_t flag) {
    uint4 v = ld_relaxed_v4(p);
    int n = 0;
    while ((v.y != flag || v.w != flag) && ++n < SPIN_LIMIT) v = ld_relaxed_v4(p);
    return v;
}

constexpr int RT = 512;
constexpr int MEMS_LD = D_ + 8;
constexpr int HL = DH_ + 8;
struct RecurSmem {
    bf16 mem[MEM_][MEMS_LD];
    bf16 kall[2][48][HL];
    bf16 vall[2][48][HL];
    bf16 qm[MEM_][HL];
    bf16 p[MEM_][48 + 8];
    bf16 om[MEM_][HL];
    float red[12][16 * 8];
    float wred[2][5][16 * 8];
};

__global__ void __launch_bounds__(RT, 1)
recur_kernel(const bf16* __restrict__ mem0, const bf16* __restrict__ Wq, const bf16* __restrict__ Wk,
             const bf16* __restrict__ Wv, const bf16* __restrict__ Wo) {
    extern __shared__ __align__(16) uint8_t smem_raw[];
    RecurSmem& sm = *reinterpret_cast<RecurSmem*>(smem_raw);
    const int tid = threadIdx.x, lane = tid & 31, w = tid >> 5;
    const int g = lane >> 2, t = lane & 3;
    const int h = blockIdx.x >> 2, c = blockIdx.x & 3;

    uint32_t wf[20][4];
    if (w < 12) {
        int mt = w % 6, kh = w / 6;
        const bf16* W = (mt < 2) ? Wq : (mt < 4 ? Wk : Wv);
        int f0 = h * DH_ + c * 32 + (mt & 1) * 16;
#pragma unroll
        for (int i = 0; i < 20; i++) {
            int k0 = (kh * 20 + i) * 16;
            const bf16* p0 = W + (size_t)(k0 + 2 * t) * HD_ + f0 + g;
            uint16_t a, b;
            a = *(const uint16_t*)(p0);            b = *(const uint16_t*)(p0 + HD_);            wf[i][0] = a | ((uint32_t)b << 16);
            a = *(const uint16_t*)(p0 + 8);        b = *(const uint16_t*)(p0 + HD_ + 8);        wf[i][1] = a | ((uint32_t)b << 16);
            a = *(const uint16_t*)(p0 + 8 * HD_);  b = *(const uint16_t*)(p0 + 9 * HD_);        wf[i][2] = a | ((uint32_t)b << 16);
            a = *(const uint16_t*)(p0 + 8 * HD_ + 8); b = *(const uint16_t*)(p0 + 9 * HD_ + 8); wf[i][3] = a | ((uint32_t)b << 16);
        }
    } else {
        int j = w - 12, mg = j >> 1, kh = j & 1;
#pragma unroll
        for (int mi = 0; mi < 5; mi++)
#pragma unroll
            for (int ki = 0; ki < 4; ki++) {
                int col0 = c * 160 + (mg * 5 + mi) * 16;
                int e0 = h * DH_ + (kh * 4 + ki) * 16;
                const bf16* p0 = Wo + (size_t)(e0 + 2 * t) * D_ + col0 + g;
                uint16_t a, b; int i = mi * 4 + ki;
                a = *(const uint16_t*)(p0);           b = *(const uint16_t*)(p0 + D_);           wf[i][0] = a | ((uint32_t)b << 16);
                a = *(const uint16_t*)(p0 + 8);       b = *(const uint16_t*)(p0 + D_ + 8);       wf[i][1] = a | ((uint32_t)b << 16);
                a = *(const uint16_t*)(p0 + 8 * D_);  b = *(const uint16_t*)(p0 + 9 * D_);       wf[i][2] = a | ((uint32_t)b << 16);
                a = *(const uint16_t*)(p0 + 8 * D_ + 8); b = *(const uint16_t*)(p0 + 9 * D_ + 8); wf[i][3] = a | ((uint32_t)b << 16);
            }
    }
    for (int i = tid; i < 2 * 8 * HL; i += RT) {
        int b = i / (8 * HL), r = (i / HL) % 8, cc = i % HL;
        sm.kall[b][40 + r][cc] = __float2bfloat16(0.f);
        sm.vall[b][40 + r][cc] = __float2bfloat16(0.f);
    }
    auto prefetch_kv = [&](int s, int buf) {
        for (int i = tid; i < 1024; i += RT) {
            int which = i >> 9, r = (i >> 4) & 31, ch = i & 15;
            const bf16* src = g_qkv + (size_t)(s * SEG_ + r) * (3 * HD_) + (1 + which) * HD_ + h * DH_ + ch * 8;
            bf16* dst = which ? &sm.vall[buf][MEM_ + r][ch * 8] : &sm.kall[buf][MEM_ + r][ch * 8];
            cp_async16(smem_u32(dst), src);
        }
        cp_async_commit();
    };
    prefetch_kv(0, 0);

    for (int s = 0; s < NSEG_; s++) {
        const int buf = s & 1;
        const uint32_t flag = s + 1;
        if (s == 0) {
            for (int i = tid; i < MEM_ * D_ / 8; i += RT) {
                int r = i / (D_ / 8), cc = (i % (D_ / 8)) * 8;
                *reinterpret_cast<uint4*>(&sm.mem[r][cc]) = *reinterpret_cast<const uint4*>(mem0 + r * D_ + cc);
            }
        } else {
            for (int i = tid; i < MEM_ * D_ / 4; i += RT) {
                uint4 v = poll_ll(&g_h2[i * 2], flag - 1);
                int r = i / (D_ / 4), cc = (i % (D_ / 4)) * 4;
                *reinterpret_cast<uint2*>(&sm.mem[r][cc]) = make_uint2(v.x, v.z);
            }
        }
        __syncthreads();
        if (w < 12) {
            int kh = w / 6;
            float a0[4] = {0.f, 0.f, 0.f, 0.f}, a1[4] = {0.f, 0.f, 0.f, 0.f};
            uint32_t base = smem_u32(&sm.mem[lane & 7][kh * 320 + (lane >> 3) * 8]);
#pragma unroll
            for (int i = 0; i < 20; i += 2) {
                uint32_t b[4];
                ldsm_x4(b, base + i * 32);
                mma16816(a0, wf[i], b[0], b[1]);
                mma16816(a1, wf[i + 1], b[2], b[3]);
            }
            float* rp = sm.red[w];
            rp[g * 8 + 2 * t] = a0[0] + a1[0]; rp[g * 8 + 2 * t + 1] = a0[1] + a1[1];
            rp[(g + 8) * 8 + 2 * t] = a0[2] + a1[2]; rp[(g + 8) * 8 + 2 * t + 1] = a0[3] + a1[3];
        }
        __syncthreads();
        if (tid < 384) {
            int mat = tid >> 7, r = (tid >> 4) & 7, pr = tid & 15;
            int mt = mat * 2 + (pr >> 3), f = (pr & 7) * 2;
            float v0 = sm.red[mt][f * 8 + r] + sm.red[mt + 6][f * 8 + r];
            float v1 = sm.red[mt][(f + 1) * 8 + r] + sm.red[mt + 6][(f + 1) * 8 + r];
            uint32_t pk = pack_bf16(v0, v1);
            st_relaxed_v2(&g_hx[((h * 4 + c) * 3 + mat) * 128 + r * 16 + pr], pk, flag);
            if (mat) {
                bf16* dst = (mat == 1 ? g_kmem : g_vmem) + ((size_t)s * MEM_ + r) * HD_ + h * DH_ + c * 32 + pr * 2;
                *reinterpret_cast<uint32_t*>(dst) = pk;
            }
        }
        if (s == NSEG_ - 1) break;
        for (int i = tid; i < 4 * 3 * 128 / 2; i += RT) {
            uint4 v = poll_ll(&g_hx[h * 4 * 384 + i * 2], flag);
            int cc = i / 192, rem = i % 192, mat = rem >> 6, r = (rem >> 3) & 7, pr = (rem & 7) * 2;
            int col = cc * 32 + pr * 2;
            bf16* dst = mat == 0 ? &sm.qm[r][col] : (mat == 1 ? &sm.kall[buf][r][col] : &sm.vall[buf][r][col]);
            *reinterpret_cast<uint2*>(dst) = make_uint2(v.x, v.z);
        }
        cp_async_wait<0>();
        __syncthreads();
        prefetch_kv(s + 1, buf ^ 1);
        if (w == 0) {
            float sc[3][4];
#pragma unroll
            for (int m = 0; m < 3; m++) { sc[m][0] = sc[m][1] = sc[m][2] = sc[m][3] = 0.f; }
            uint32_t qb = smem_u32(&sm.qm[lane & 7][(lane >> 3) * 8]);
#pragma unroll
            for (int kk = 0; kk < 8; kk += 2) {
                uint32_t b[4];
                ldsm_x4(b, qb + kk * 32);
#pragma unroll
                for (int m = 0; m < 3; m++) {
                    uint32_t a[4];
                    ldsm_x4(a, smem_u32(&sm.kall[buf][m * 16 + (lane & 15)][kk * 16 + (lane >> 4) * 8]));
                    mma16816(sc[m], a, b[0], b[1]);
                    ldsm_x4(a, smem_u32(&sm.kall[buf][m * 16 + (lane & 15)][kk * 16 + 16 + (lane >> 4) * 8]));
                    mma16816(sc[m], a, b[2], b[3]);
                }
            }
            const float scale = 0.08838834764831845f;
            float mx0 = -INFINITY, mx1 = -INFINITY;
#pragma unroll
            for (int m = 0; m < 3; m++)
#pragma unroll
                for (int e = 0; e < 4; e++) {
                    int key = m * 16 + g + (e >> 1) * 8;
                    float v = rbf(rbf(sc[m][e]) * scale);
                    sc[m][e] = v;
                    if (key < 40) { if (e & 1) mx1 = fmaxf(mx1, v); else mx0 = fmaxf(mx0, v); }
                }
#pragma unroll
            for (int o = 4; o < 32; o <<= 1) { mx0 = fmaxf(mx0, __shfl_xor_sync(0xffffffffu, mx0, o)); mx1 = fmaxf(mx1, __shfl_xor_sync(0xffffffffu, mx1, o)); }
            float sm0 = 0.f, sm1 = 0.f;
#pragma unroll
            for (int m = 0; m < 3; m++)
#pragma unroll
                for (int e = 0; e < 4; e++) {
                    int key = m * 16 + g + (e >> 1) * 8;
                    float ev = (key < 40) ? __expf(sc[m][e] - ((e & 1) ? mx1 : mx0)) : 0.f;
                    sc[m][e] = ev;
                    if (e & 1) sm1 += ev; else sm0 += ev;
                }
#pragma unroll
            for (int o = 4; o < 32; o <<= 1) { sm0 += __shfl_xor_sync(0xffffffffu, sm0, o); sm1 += __shfl_xor_sync(0xffffffffu, sm1, o); }
            float i0 = 1.0f / sm0, i1 = 1.0f / sm1;
#pragma unroll
            for (int m = 0; m < 3; m++)
#pragma unroll
                for (int e = 0; e < 4; e++) {
                    int key = m * 16 + g + (e >> 1) * 8;
                    sm.p[2 * t + (e & 1)][key] = __float2bfloat16_rn(sc[m][e] * ((e & 1) ? i1 : i0));
                }
        }
        __syncthreads();
        if (w < 8) {
            float o[4] = {0.f, 0.f, 0.f, 0.f};
#pragma unroll
            for (int kt = 0; kt < 3; kt++) {
                uint32_t a[4], b[2];
                ldsm_x4_t(a, smem_u32(&sm.vall[buf][kt * 16 + (lane & 7) + ((lane >> 4) & 1) * 8][w * 16 + ((lane >> 3) & 1) * 8]));
                asm volatile("ldmatrix.sync.aligned.m8n8.x2.shared.b16 {%0,%1}, [%2];" : "=r"(b[0]), "=r"(b[1])
                             : "r"(smem_u32(&sm.p[lane & 7][kt * 16 + ((lane >> 3) & 1) * 8])));
                mma16816(o, a, b[0], b[1]);
            }
            sm.om[2 * t][w * 16 + g] = __float2bfloat16_rn(o[0]);
            sm.om[2 * t + 1][w * 16 + g] = __float2bfloat16_rn(o[1]);
            sm.om[2 * t][w * 16 + g + 8] = __float2bfloat16_rn(o[2]);
            sm.om[2 * t + 1][w * 16 + g + 8] = __float2bfloat16_rn(o[3]);
        }
        __syncthreads();
        if (w >= 12) {
            int j = w - 12, mg = j >> 1, kh = j & 1;
            float acc[5][4];
#pragma unroll
            for (int mi = 0; mi < 5; mi++) { acc[mi][0] = acc[mi][1] = acc[mi][2] = acc[mi][3] = 0.f; }
            uint32_t ob = smem_u32(&sm.om[lane & 7][kh * 64 + (lane >> 3) * 8]);
#pragma unroll
            for (int ki = 0; ki < 4; ki += 2) {
                uint32_t b[4];
                ldsm_x4(b, ob + ki * 32);
#pragma unroll
                for (int mi = 0; mi < 5; mi++) { mma16816(acc[mi], wf[mi * 4 + ki], b[0], b[1]); mma16816(acc[mi], wf[mi * 4 + ki + 1], b[2], b[3]); }
            }
            if (kh == 1) {
#pragma unroll
                for (int mi = 0; mi < 5; mi++)
                    *reinterpret_cast<float4*>(&sm.wred[mg][mi][lane * 4]) = make_float4(acc[mi][0], acc[mi][1], acc[mi][2], acc[mi][3]);
            }
            asm volatile("bar.sync %0, 64;" ::"r"(1 + mg) : "memory");
            if (kh == 0) {
#pragma unroll
                for (int mi = 0; mi < 5; mi++) {
                    float4 o2 = *reinterpret_cast<float4*>(&sm.wred[mg][mi][lane * 4]);
                    int col = c * 160 + (mg * 5 + mi) * 16 + g;
                    uint2* dst = g_h1 + (size_t)h * (MEM_ * D_);
                    st_relaxed_v2(dst + (2 * t) * D_ + col, __float_as_uint(acc[mi][0] + o2.x), flag);
                    st_relaxed_v2(dst + (2 * t + 1) * D_ + col, __float_as_uint(acc[mi][1] + o2.y), flag);
                    st_relaxed_v2(dst + (2 * t) * D_ + col + 8, __float_as_uint(acc[mi][2] + o2.z), flag);
                    st_relaxed_v2(dst + (2 * t + 1) * D_ + col + 8, __float_as_uint(acc[mi][3] + o2.w), flag);
                }
            }
        }
        if (w < 10) {
            int e0 = blockIdx.x * 40 + w * 4;
            const uint2* src = g_h1 + (size_t)lane * (MEM_ * D_) + e0;
            uint4 v0 = poll_ll(src, flag), v1 = poll_ll(src + 2, flag);
            float x0 = __uint_as_float(v0.x), x1 = __uint_as_float(v0.z), x2 = __uint_as_float(v1.x), x3 = __uint_as_float(v1.z);
#pragma unroll
            for (int o = 1; o < 32; o <<= 1) {
                x0 += __shfl_xor_sync(0xffffffffu, x0, o); x1 += __shfl_xor_sync(0xffffffffu, x1, o);
                x2 += __shfl_xor_sync(0xffffffffu, x2, o); x3 += __shfl_xor_sync(0xffffffffu, x3, o);
            }
            if (lane == 0) st_relaxed_v4(&g_h2[e0 / 2], pack_bf16(x0, x1), flag, pack_bf16(x2, x3), flag);
        }
    }
}

__global__ void __launch_bounds__(128)
attn_x_kernel() {
    __shared__ __align__(16) bf16 sq[32][HL], sk[48][HL], sv[48][HL];
    const int s = blockIdx.x >> 5, h = blockIdx.x & 31;
    const int tid = threadIdx.x, lane = tid & 31, w = tid >> 5, g = lane >> 2, t = lane & 3;
    for (int i = tid; i < (32 + 40 + 40) * 16; i += 128) {
        int r = i >> 4, ch = i & 15;
        const bf16* src; bf16* dst;
        if (r < 32) { src = g_qkv + (size_t)(s * SEG_ + r) * (3 * HD_) + h * DH_; dst = sq[r]; }
        else if (r < 72) { int rr = r - 32; dst = sk[rr];
            src = rr < 8 ? g_kmem + ((size_t)s * MEM_ + rr) * HD_ + h * DH_ : g_qkv + (size_t)(s * SEG_ + rr - 8) * (3 * HD_) + HD_ + h * DH_; }
        else { int rr = r - 72; dst = sv[rr];
            src = rr < 8 ? g_vmem + ((size_t)s * MEM_ + rr) * HD_ + h * DH_ : g_qkv + (size_t)(s * SEG_ + rr - 8) * (3 * HD_) + 2 * HD_ + h * DH_; }
        *reinterpret_cast<uint4*>(dst + ch * 8) = *reinterpret_cast<const uint4*>(src + ch * 8);
    }
    for (int i = tid; i < 8 * 16; i += 128) *reinterpret_cast<uint4*>(&sv[40 + (i >> 4)][(i & 15) * 8]) = make_uint4(0, 0, 0, 0);
    __syncthreads();
    const int rh = w & 1, dhh = w >> 1;
    float sc[5][4];
#pragma unroll
    for (int n = 0; n < 5; n++) sc[n][0] = sc[n][1] = sc[n][2] = sc[n][3] = 0.f;
#pragma unroll
    for (int kk = 0; kk < 8; kk++) {
        uint32_t a[4];
        ldsm_x4(a, smem_u32(&sq[rh * 16 + (lane & 15)][kk * 16 + (lane >> 4) * 8]));
#pragma unroll
        for (int n = 0; n < 5; n++) {
            uint32_t b[2];
            asm volatile("ldmatrix.sync.aligned.m8n8.x2.shared.b16 {%0,%1}, [%2];" : "=r"(b[0]), "=r"(b[1])
                         : "r"(smem_u32(&sk[n * 8 + (lane & 7)][kk * 16 + ((lane >> 3) & 1) * 8])));
            mma16816(sc[n], a, b[0], b[1]);
        }
    }
    const float scale = 0.08838834764831845f;
    float mx[2] = {-INFINITY, -INFINITY};
#pragma unroll
    for (int n = 0; n < 5; n++)
#pragma unroll
        for (int e = 0; e < 4; e++) {
            int row = rh * 16 + g + (e >> 1) * 8, key = n * 8 + 2 * t + (e & 1);
            float v = rbf(rbf(sc[n][e]) * scale);
            if (key > row + MEM_) v = -INFINITY;
            sc[n][e] = v;
            mx[e >> 1] = fmaxf(mx[e >> 1], v);
        }
#pragma unroll
    for (int o = 1; o < 4; o <<= 1) { mx[0] = fmaxf(mx[0], __shfl_xor_sync(0xffffffffu, mx[0], o)); mx[1] = fmaxf(mx[1], __shfl_xor_sync(0xffffffffu, mx[1], o)); }
    float sum[2] = {0.f, 0.f};
#pragma unroll
    for (int n = 0; n < 5; n++)
#pragma unroll
        for (int e = 0; e < 4; e++) { float ev = __expf(sc[n][e] - mx[e >> 1]); sc[n][e] = ev; sum[e >> 1] += ev; }
#pragma unroll
    for (int o = 1; o < 4; o <<= 1) { sum[0] += __shfl_xor_sync(0xffffffffu, sum[0], o); sum[1] += __shfl_xor_sync(0xffffffffu, sum[1], o); }
    float inv[2] = {1.0f / sum[0], 1.0f / sum[1]};
    uint32_t pa[3][4];
#pragma unroll
    for (int kt = 0; kt < 3; kt++) {
        pa[kt][0] = pack_bf16(sc[2 * kt][0] * inv[0], sc[2 * kt][1] * inv[0]);
        pa[kt][1] = pack_bf16(sc[2 * kt][2] * inv[1], sc[2 * kt][3] * inv[1]);
        if (kt < 2) {
            pa[kt][2] = pack_bf16(sc[2 * kt + 1][0] * inv[0], sc[2 * kt + 1][1] * inv[0]);
            pa[kt][3] = pack_bf16(sc[2 * kt + 1][2] * inv[1], sc[2 * kt + 1][3] * inv[1]);
        } else { pa[kt][2] = 0u; pa[kt][3] = 0u; }
    }
#pragma unroll
    for (int n = 0; n < 8; n++) {
        float o[4] = {0.f, 0.f, 0.f, 0.f};
#pragma unroll
        for (int kt = 0; kt < 3; kt++) {
            uint32_t b[2];
            asm volatile("ldmatrix.sync.aligned.m8n8.x2.trans.shared.b16 {%0,%1}, [%2];" : "=r"(b[0]), "=r"(b[1])
                         : "r"(smem_u32(&sv[kt * 16 + (lane & 15)][dhh * 64 + n * 8])));
            mma16816(o, pa[kt], b[0], b[1]);
        }
        int row = s * SEG_ + rh * 16 + g;
        bf16* dst = g_o + (size_t)row * HD_ + h * DH_ + dhh * 64 + n * 8 + 2 * t;
        *reinterpret_cast<uint32_t*>(dst) = pack_bf16(o[0], o[1]);
        *reinterpret_cast<uint32_t*>(dst + 8 * HD_) = pack_bf16(o[2], o[3]);
    }
}

typedef CUresult (*PFN_encodeTiled)(CUtensorMap*, CUtensorMapDataType, cuuint32_t, void*, const cuuint64_t*,
                                    const cuuint64_t*, const cuuint32_t*, const cuuint32_t*, CUtensorMapInterleave,
                                    CUtensorMapSwizzle, CUtensorMapL2promotion, CUtensorMapFloatOOBfill);
static PFN_encodeTiled p_encode = nullptr;

static CUtensorMap make_map(const void* ptr, uint64_t rows, uint64_t cols, uint64_t ld, uint32_t box_rows) {
    CUtensorMap m;
    cuuint64_t dims[2] = {cols, rows};
    cuuint64_t strides[1] = {ld * 2};
    cuuint32_t box[2] = {64, box_rows};
    cuuint32_t es[2] = {1, 1};
    p_encode(&m, CU_TENSOR_MAP_DATA_TYPE_BFLOAT16, 2, const_cast<void*>(ptr), dims, strides, box, es,
             CU_TENSOR_MAP_INTERLEAVE_NONE, CU_TENSOR_MAP_SWIZZLE_128B, CU_TENSOR_MAP_L2_PROMOTION_L2_128B,
             CU_TENSOR_MAP_FLOAT_OOB_FILL_NONE);
    return m;
}

template <int BN, int EPI>
static void launch_gemm(const CUtensorMap& a, const CUtensorMap& b, int M, int N, int K, EpiParams ep, cudaStream_t st) {
    constexpr int STAGE = 16384 + (BN / 64) * 8192;
    constexpr int NST = (200 * 1024) / STAGE;
    constexpr int SMEM = NST * STAGE + 1024;
    cudaFuncSetAttribute(gemm_kernel<BN, EPI>, cudaFuncAttributeMaxDynamicSharedMemorySize, SMEM);
    dim3 grid((N + BN - 1) / BN, M / 128);
    gemm_kernel<BN, EPI><<<grid, 384, SMEM, st>>>(a, b, M, N, K, ep);
}

extern "C" void kernel_launch(void* const* d_in, const int* in_sizes, int n_in, void* d_out, int out_size) {
    const bf16* x    = (const bf16*)d_in[0];
    const bf16* mem0 = (const bf16*)d_in[1];
    const bf16* Wq   = (const bf16*)d_in[2];
    const bf16* Wk   = (const bf16*)d_in[3];
    const bf16* Wv   = (const bf16*)d_in[4];
    const bf16* Wo   = (const bf16*)d_in[5];
    const bf16* w_in  = (const bf16*)d_in[8];
    const bf16* w_sp  = (const bf16*)d_in[9];
    const bf16* b_sp  = (const bf16*)d_in[10];
    const bf16* w_out = (const bf16*)d_in[11];
    bf16* out = (bf16*)d_out;
    cudaStream_t st = cudaStreamPerThread;

    if (!p_encode) {
        cudaDriverEntryPointQueryResult qr;
        cudaGetDriverEntryPoint("cuTensorMapEncodeTiled", (void**)&p_encode, cudaEnableDefault, &qr);
    }
    void *p_xn, *p_qkv, *p_z, *p_zg, *p_gate, *p_o, *p_h1, *p_h2, *p_hx;
    cudaGetSymbolAddress(&p_xn, g_xn); cudaGetSymbolAddress(&p_qkv, g_qkv); cudaGetSymbolAddress(&p_z, g_z);
    cudaGetSymbolAddress(&p_zg, g_zg); cudaGetSymbolAddress(&p_gate, g_gate); cudaGetSymbolAddress(&p_o, g_o);
    cudaGetSymbolAddress(&p_h1, g_h1); cudaGetSymbolAddress(&p_h2, g_h2); cudaGetSymbolAddress(&p_hx, g_hx);

    CUtensorMap mA_xn  = make_map(p_xn, S_, D_, D_, 128);
    CUtensorMap mA_wsp = make_map(w_sp, S_, S_, S_, 128);
    CUtensorMap mA_zg  = make_map(p_zg, S_, FH_, FH_, 128);
    CUtensorMap mA_o   = make_map(p_o, S_, HD_, HD_, 128);
    CUtensorMap mB_wq  = make_map(Wq, D_, HD_, HD_, 64);
    CUtensorMap mB_wk  = make_map(Wk, D_, HD_, HD_, 64);
    CUtensorMap mB_wv  = make_map(Wv, D_, HD_, HD_, 64);
    CUtensorMap mB_win = make_map(w_in, D_, F_, F_, 64);
    CUtensorMap mB_z2  = make_map((bf16*)p_z + FH_, S_, FH_, F_, 64);
    CUtensorMap mB_wout = make_map(w_out, FH_, D_, D_, 64);
    CUtensorMap mB_wo  = make_map(Wo, HD_, D_, D_, 64);

    cudaMemsetAsync(p_h1, 0, sizeof(uint2) * H_ * MEM_ * D_, st);
    cudaMemsetAsync(p_h2, 0, sizeof(uint2) * MEM_ * D_ / 2, st);
    cudaMemsetAsync(p_hx, 0, sizeof(uint2) * H_ * 4 * 3 * MEM_ * 16, st);

    ln_kernel<<<S_ / 8, 256, 0, st>>>(x);
    for (int i = 0; i < 3; i++) {
        EpiParams ep{(bf16*)p_qkv + i * HD_, 3 * HD_, nullptr, nullptr};
        launch_gemm<128, EPI_STORE>(mA_xn, i == 0 ? mB_wq : (i == 1 ? mB_wk : mB_wv), S_, HD_, D_, ep, st);
    }
    { EpiParams ep{(bf16*)p_z, F_, nullptr, nullptr}; launch_gemm<192, EPI_GELU>(mA_xn, mB_win, S_, F_, D_, ep, st); }
    ln2_kernel<<<S_ / 8, 256, 0, st>>>();
    { EpiParams ep{(bf16*)p_zg, FH_, (const bf16*)p_z, b_sp}; launch_gemm<128, EPI_SP>(mA_wsp, mB_z2, S_, FH_, S_, ep, st); }
    { EpiParams ep{(bf16*)p_gate, D_, nullptr, nullptr}; launch_gemm<128, EPI_SILU>(mA_zg, mB_wout, S_, D_, FH_, ep, st); }
    cudaFuncSetAttribute(recur_kernel, cudaFuncAttributeMaxDynamicSharedMemorySize, (int)sizeof(RecurSmem));
    recur_kernel<<<128, RT, sizeof(RecurSmem), st>>>(mem0, Wq, Wk, Wv, Wo);
    attn_x_kernel<<<NSEG_ * H_, 128, 0, st>>>();
    { EpiParams ep{out, D_, x, (const bf16*)p_gate}; launch_gemm<128, EPI_FINAL>(mA_o, mB_wo, S_, D_, HD_, ep, st); }
}
```

```cpp
#include <cuda_runtime.h>
#include <cuda_bf16.h>
#include <cuda.h>
#include <stdint.h>

typedef __nv_bfloat16 bf16;

constexpr int S_   = 2048;
constexpr int D_   = 640;
constexpr int H_   = 32;
constexpr int DH_  = 128;
constexpr int MEM_ = 8;
constexpr int SEG_ = 32;
constexpr int NSEG_ = S_ / SEG_;
constexpr int HD_  = H_ * DH_;
constexpr int F_   = 1728;
constexpr int FH_  = 864;

__device__ bf16 g_xn[S_ * D_];
__device__ bf16 g_qkv[(size_t)S_ * 3 * HD_];
__device__ bf16 g_z[S_ * F_];
__device__ bf16 g_zg[S_ * FH_];
__device__ bf16 g_gate[S_ * D_];
__device__ bf16 g_kmem[NSEG_ * MEM_ * HD_];
__device__ bf16 g_vmem[NSEG_ * MEM_ * HD_];
__device__ bf16 g_o[(size_t)S_ * HD_];
__device__ uint2 g_h1[H_ * MEM_ * D_];
__device__ uint2 g_h2[MEM_ * D_ / 2];
__device__ uint2 g_hx[H_ * 4 * 3 * MEM_ * 16];

__device__ __forceinline__ uint32_t smem_u32(const void* p) { return (uint32_t)__cvta_generic_to_shared(p); }
__device__ __forceinline__ float bf2f(bf16 v) { return __bfloat162float(v); }
__device__ __forceinline__ float rbf(float v) { return __bfloat162float(__float2bfloat16_rn(v)); }
__device__ __forceinline__ uint32_t pack_bf16(float lo, float hi) {
    __nv_bfloat162 t = __floats2bfloat162_rn(lo, hi);
    return *reinterpret_cast<uint32_t*>(&t);
}
__device__ __forceinline__ float lo_f(uint32_t u) { return __uint_as_float(u << 16); }
__device__ __forceinline__ float hi_f(uint32_t u) { return __uint_as_float(u & 0xffff0000u); }

__device__ __forceinline__ void mbar_init(uint32_t bar, uint32_t cnt) {
    asm volatile("mbarrier.init.shared.b64 [%0], %1;" ::"r"(bar), "r"(cnt));
}
__device__ __forceinline__ void mbar_expect_tx(uint32_t bar, uint32_t bytes) {
    asm volatile("mbarrier.arrive.expect_tx.shared.b64 _, [%0], %1;" ::"r"(bar), "r"(bytes) : "memory");
}
__device__ __forceinline__ void mbar_arrive(uint32_t bar) {
    asm volatile("mbarrier.arrive.shared.b64 _, [%0];" ::"r"(bar) : "memory");
}
__device__ __forceinline__ void mbar_wait(uint32_t bar, uint32_t parity) {
    asm volatile(
        "{\n .reg .pred p;\n"
        "WAIT_%=:\n"
        " mbarrier.try_wait.parity.shared.b64 p, [%0], %1;\n"
        " @p bra DONE_%=;\n"
        " bra WAIT_%=;\n"
        "DONE_%=:\n}\n" ::"r"(bar), "r"(parity) : "memory");
}
__device__ __forceinline__ void tma_load_2d(uint32_t dst, const CUtensorMap* tm, uint32_t bar, int c0, int c1) {
    asm volatile(
        "cp.async.bulk.tensor.2d.shared::cluster.global.mbarrier::complete_tx::bytes [%0], [%1, {%3, %4}], [%2];"
        ::"r"(dst), "l"(tm), "r"(bar), "r"(c0), "r"(c1) : "memory");
}
__device__ __forceinline__ void wgmma_fence() { asm volatile("wgmma.fence.sync.aligned;" ::: "memory"); }
__device__ __forceinline__ void wgmma_commit() { asm volatile("wgmma.commit_group.sync.aligned;" ::: "memory"); }
template <int N> __device__ __forceinline__ void wgmma_wait() { asm volatile("wgmma.wait_group.sync.aligned %0;" ::"n"(N) : "memory"); }

__device__ __forceinline__ uint64_t make_desc(uint32_t addr, uint32_t lbo, uint32_t sbo) {
    return (uint64_t)((addr & 0x3FFFF) >> 4) | ((uint64_t)(lbo >> 4) << 16) | ((uint64_t)(sbo >> 4) << 32) | (1ull << 62);
}

template <int N> struct Wgmma;
template <> struct Wgmma<128> {
    static __device__ __forceinline__ void mma(float* d, uint64_t da, uint64_t db, int sd) {
        asm volatile(
            "{\n.reg .pred p;\nsetp.ne.b32 p, %66, 0;\n"
            "wgmma.mma_async.sync.aligned.m64n128k16.f32.bf16.bf16 "
            "{%0,%1,%2,%3,%4,%5,%6,%7,%8,%9,%10,%11,%12,%13,%14,%15,"
            "%16,%17,%18,%19,%20,%21,%22,%23,%24,%25,%26,%27,%28,%29,%30,%31,"
            "%32,%33,%34,%35,%36,%37,%38,%39,%40,%41,%42,%43,%44,%45,%46,%47,"
            "%48,%49,%50,%51,%52,%53,%54,%55,%56,%57,%58,%59,%60,%61,%62,%63},"
            "%64,%65,p,1,1,0,1;\n}\n"
            : "+f"(d[0]), "+f"(d[1]), "+f"(d[2]), "+f"(d[3]), "+f"(d[4]), "+f"(d[5]), "+f"(d[6]), "+f"(d[7]),
              "+f"(d[8]), "+f"(d[9]), "+f"(d[10]), "+f"(d[11]), "+f"(d[12]), "+f"(d[13]), "+f"(d[14]), "+f"(d[15]),
              "+f"(d[16]), "+f"(d[17]), "+f"(d[18]), "+f"(d[19]), "+f"(d[20]), "+f"(d[21]), "+f"(d[22]), "+f"(d[23]),
              "+f"(d[24]), "+f"(d[25]), "+f"(d[26]), "+f"(d[27]), "+f"(d[28]), "+f"(d[29]), "+f"(d[30]), "+f"(d[31]),
              "+f"(d[32]), "+f"(d[33]), "+f"(d[34]), "+f"(d[35]), "+f"(d[36]), "+f"(d[37]), "+f"(d[38]), "+f"(d[39]),
              "+f"(d[40]), "+f"(d[41]), "+f"(d[42]), "+f"(d[43]), "+f"(d[44]), "+f"(d[45]), "+f"(d[46]), "+f"(d[47]),
              "+f"(d[48]), "+f"(d[49]), "+f"(d[50]), "+f"(d[51]), "+f"(d[52]), "+f"(d[53]), "+f"(d[54]), "+f"(d[55]),
              "+f"(d[56]), "+f"(d[57]), "+f"(d[58]), "+f"(d[59]), "+f"(d[60]), "+f"(d[61]), "+f"(d[62]), "+f"(d[63])
            : "l"(da), "l"(db), "r"(sd));
    }
};
template <> struct Wgmma<192> {
    static __device__ __forceinline__ void mma(float* d, uint64_t da, uint64_t db, int sd) {
        asm volatile(
            "{\n.reg .pred p;\nsetp.ne.b32 p, %98, 0;\n"
            "wgmma.mma_async.sync.aligned.m64n192k16.f32.bf16.bf16 "
            "{%0,%1,%2,%3,%4,%5,%6,%7,%8,%9,%10,%11,%12,%13,%14,%15,"
            "%16,%17,%18,%19,%20,%21,%22,%23,%24,%25,%26,%27,%28,%29,%30,%31,"
            "%32,%33,%34,%35,%36,%37,%38,%39,%40,%41,%42,%43,%44,%45,%46,%47,"
            "%48,%49,%50,%51,%52,%53,%54,%55,%56,%57,%58,%59,%60,%61,%62,%63,"
            "%64,%65,%66,%67,%68,%69,%70,%71,%72,%73,%74,%75,%76,%77,%78,%79,"
            "%80,%81,%82,%83,%84,%85,%86,%87,%88,%89,%90,%91,%92,%93,%94,%95},"
            "%96,%97,p,1,1,0,1;\n}\n"
            : "+f"(d[0]), "+f"(d[1]), "+f"(d[2]), "+f"(d[3]), "+f"(d[4]), "+f"(d[5]), "+f"(d[6]), "+f"(d[7]),
              "+f"(d[8]), "+f"(d[9]), "+f"(d[10]), "+f"(d[11]), "+f"(d[12]), "+f"(d[13]), "+f"(d[14]), "+f"(d[15]),
              "+f"(d[16]), "+f"(d[17]), "+f"(d[18]), "+f"(d[19]), "+f"(d[20]), "+f"(d[21]), "+f"(d[22]), "+f"(d[23]),
              "+f"(d[24]), "+f"(d[25]), "+f"(d[26]), "+f"(d[27]), "+f"(d[28]), "+f"(d[29]), "+f"(d[30]), "+f"(d[31]),
              "+f"(d[32]), "+f"(d[33]), "+f"(d[34]), "+f"(d[35]), "+f"(d[36]), "+f"(d[37]), "+f"(d[38]), "+f"(d[39]),
              "+f"(d[40]), "+f"(d[41]), "+f"(d[42]), "+f"(d[43]), "+f"(d[44]), "+f"(d[45]), "+f"(d[46]), "+f"(d[47]),
              "+f"(d[48]), "+f"(d[49]), "+f"(d[50]), "+f"(d[51]), "+f"(d[52]), "+f"(d[53]), "+f"(d[54]), "+f"(d[55]),
              "+f"(d[56]), "+f"(d[57]), "+f"(d[58]), "+f"(d[59]), "+f"(d[60]), "+f"(d[61]), "+f"(d[62]), "+f"(d[63]),
              "+f"(d[64]), "+f"(d[65]), "+f"(d[66]), "+f"(d[67]), "+f"(d[68]), "+f"(d[69]), "+f"(d[70]), "+f"(d[71]),
              "+f"(d[72]), "+f"(d[73]), "+f"(d[74]), "+f"(d[75]), "+f"(d[76]), "+f"(d[77]), "+f"(d[78]), "+f"(d[79]),
              "+f"(d[80]), "+f"(d[81]), "+f"(d[82]), "+f"(d[83]), "+f"(d[84]), "+f"(d[85]), "+f"(d[86]), "+f"(d[87]),
              "+f"(d[88]), "+f"(d[89]), "+f"(d[90]), "+f"(d[91]), "+f"(d[92]), "+f"(d[93]), "+f"(d[94]), "+f"(d[95])
            : "l"(da), "l"(db), "r"(sd));
    }
};

template <int W>
__device__ __forceinline__ void ln_row(const bf16* __restrict__ src, bf16* __restrict__ dst, int lane) {
    constexpr int NP = W / 64;
    constexpr int REM = (W / 2) % 32;
    uint32_t v[NP + 1];
    const uint32_t* s32 = reinterpret_cast<const uint32_t*>(src);
    float sum = 0.f;
#pragma unroll
    for (int i = 0; i < NP; i++) { v[i] = s32[i * 32 + lane]; sum += lo_f(v[i]) + hi_f(v[i]); }
    if (REM) { v[NP] = (lane < REM) ? s32[NP * 32 + lane] : 0u; if (lane < REM) sum += lo_f(v[NP]) + hi_f(v[NP]); }
#pragma unroll
    for (int o = 16; o; o >>= 1) sum += __shfl_xor_sync(0xffffffffu, sum, o);
    float mean = sum * (1.0f / W);
    float vs = 0.f;
#pragma unroll
    for (int i = 0; i < NP; i++) { float a = lo_f(v[i]) - mean, b = hi_f(v[i]) - mean; vs += a * a + b * b; }
    if (REM && lane < REM) { float a = lo_f(v[NP]) - mean, b = hi_f(v[NP]) - mean; vs += a * a + b * b; }
#pragma unroll
    for (int o = 16; o; o >>= 1) vs += __shfl_xor_sync(0xffffffffu, vs, o);
    float var = rbf(vs * (1.0f / W));
    float mb = rbf(mean);
    float den = rbf(sqrtf(rbf(var + 1e-5f)));
    uint32_t* d32 = reinterpret_cast<uint32_t*>(dst);
#pragma unroll
    for (int i = 0; i < NP; i++) d32[i * 32 + lane] = pack_bf16(rbf(lo_f(v[i]) - mb) / den, rbf(hi_f(v[i]) - mb) / den);
    if (REM && lane < REM) d32[NP * 32 + lane] = pack_bf16(rbf(lo_f(v[NP]) - mb) / den, rbf(hi_f(v[NP]) - mb) / den);
}

__global__ void ln_kernel(const bf16* __restrict__ x) {
    int row = blockIdx.x * 8 + (threadIdx.x >> 5);
    ln_row<D_>(x + (size_t)row * D_, g_xn + (size_t)row * D_, threadIdx.x & 31);
}
__global__ void ln2_kernel() {
    int row = blockIdx.x * 8 + (threadIdx.x >> 5);
    bf16* p = g_z + (size_t)row * F_ + FH_;
    ln_row<FH_>(p, p, threadIdx.x & 31);
}

enum { EPI_STORE = 0, EPI_GELU = 1, EPI_SP = 2, EPI_SILU = 3, EPI_FINAL = 4 };
struct EpiParams {
    bf16* out; int ldo;
    const bf16* aux0;
    const bf16* aux1;
};

__device__ __forceinline__ float gelu_tanh_f(float x) {
    const float k0 = 0.7978845608028654f, k1 = 0.044715f;
    float inner = k0 * (x + k1 * x * x * x);
    return 0.5f * x * (1.0f + tanhf(inner));
}
__device__ __forceinline__ float silu_f(float x) { return x / (1.0f + expf(-x)); }

template <int BN, int EPI>
__global__ void __launch_bounds__(384, 1)
gemm_kernel(const __grid_constant__ CUtensorMap tmA, const __grid_constant__ CUtensorMap tmB,
            int M, int N, int K, EpiParams ep) {
    constexpr int BM = 128, BK = 64;
    constexpr int A_BYTES = BM * BK * 2;
    constexpr int B_BYTES = (BN / 64) * 8192;
    constexpr int STAGE = A_BYTES + B_BYTES;
    constexpr int NST = (200 * 1024) / STAGE;
    extern __shared__ __align__(1024) uint8_t smem_raw[];
    uint8_t* smem = (uint8_t*)(((uintptr_t)smem_raw + 1023) & ~(uintptr_t)1023);
    __shared__ __align__(8) uint64_t full_bar[NST], empty_bar[NST];

    const int tid = threadIdx.x, wg = tid >> 7;
    const int m0 = blockIdx.y * BM, n0 = blockIdx.x * BN;
    const int nk = (K + BK - 1) / BK;

    if (tid == 0) {
        for (int i = 0; i < NST; i++) { mbar_init(smem_u32(&full_bar[i]), 1); mbar_init(smem_u32(&empty_bar[i]), 2); }
        asm volatile("fence.mbarrier_init.release.cluster;" ::: "memory");
    }
    __syncthreads();

    if (wg == 0) {
        if (tid == 0) {
            for (int kt = 0; kt < nk; kt++) {
                int st = kt % NST; uint32_t ph = (kt / NST) & 1;
                mbar_wait(smem_u32(&empty_bar[st]), ph ^ 1);
                uint32_t fb = smem_u32(&full_bar[st]);
                mbar_expect_tx(fb, STAGE);
                uint32_t sa = smem_u32(smem + st * STAGE);
                tma_load_2d(sa, &tmA, fb, kt * BK, m0);
#pragma unroll
                for (int j = 0; j < BN / 64; j++) tma_load_2d(sa + A_BYTES + j * 8192, &tmB, fb, n0 + j * 64, kt * BK);
            }
        }
    } else {
        const int cw = wg - 1;
        float acc[BN / 2];
#pragma unroll
        for (int i = 0; i < BN / 2; i++) acc[i] = 0.f;
        for (int kt = 0; kt < nk; kt++) {
            int st = kt % NST; uint32_t ph = (kt / NST) & 1;
            mbar_wait(smem_u32(&full_bar[st]), ph);
            uint32_t sa = smem_u32(smem + st * STAGE) + cw * 64 * 128;
            uint32_t sb = smem_u32(smem + st * STAGE) + A_BYTES;
            wgmma_fence();
#pragma unroll
            for (int k = 0; k < BK / 16; k++) {
                uint64_t da = make_desc(sa + k * 32, 16, 1024);
                uint64_t db = make_desc(sb + k * 2048, 8192, 1024);
                Wgmma<BN>::mma(acc, da, db, 1);
            }
            wgmma_commit();
            wgmma_wait<0>();
            if ((tid & 127) == 0) mbar_arrive(smem_u32(&empty_bar[st]));
        }
        const int lane = tid & 31, wi = (tid >> 5) & 3, g = lane >> 2, t = lane & 3;
        const int r0 = m0 + cw * 64 + wi * 16 + g;
#pragma unroll
        for (int j = 0; j < BN / 8; j++) {
            int col = n0 + j * 8 + 2 * t;
            if (col >= N) continue;
#pragma unroll
            for (int hh = 0; hh < 2; hh++) {
                int row = r0 + hh * 8;
                float v0 = rbf(acc[4 * j + 2 * hh]), v1 = rbf(acc[4 * j + 2 * hh + 1]);
                uint32_t o;
                if (EPI == EPI_STORE) {
                    o = pack_bf16(v0, v1);
                } else if (EPI == EPI_GELU) {
                    o = pack_bf16(gelu_tanh_f(v0), gelu_tanh_f(v1));
                } else if (EPI == EPI_SP) {
                    float b = bf2f(ep.aux1[row]);
                    float g0 = rbf(v0 + b), g1 = rbf(v1 + b);
                    uint32_t z1 = *reinterpret_cast<const uint32_t*>(ep.aux0 + (size_t)row * F_ + col);
                    o = pack_bf16(lo_f(z1) * g0, hi_f(z1) * g1);
                } else if (EPI == EPI_SILU) {
                    o = pack_bf16(silu_f(v0), silu_f(v1));
                } else {
                    uint32_t xg = *reinterpret_cast<const uint32_t*>(ep.aux0 + (size_t)row * D_ + col);
                    uint32_t gt = *reinterpret_cast<const uint32_t*>(ep.aux1 + (size_t)row * D_ + col);
                    o = pack_bf16(lo_f(xg) + rbf(v0 * lo_f(gt)), hi_f(xg) + rbf(v1 * hi_f(gt)));
                }
                *reinterpret_cast<uint32_t*>(ep.out + (size_t)row * ep.ldo + col) = o;
            }
        }
    }
}

__device__ __forceinline__ void mma16816(float* c, const uint32_t* a, uint32_t b0, uint32_t b1) {
    asm volatile(
        "mma.sync.aligned.m16n8k16.row.col.f32.bf16.bf16.f32 {%0,%1,%2,%3}, {%4,%5,%6,%7}, {%8,%9}, {%0,%1,%2,%3};"
        : "+f"(c[0]), "+f"(c[1]), "+f"(c[2]), "+f"(c[3])
        : "r"(a[0]), "r"(a[1]), "r"(a[2]), "r"(a[3]), "r"(b0), "r"(b1));
}
__device__ __forceinline__ void ldsm_x4(uint32_t* r, uint32_t addr) {
    asm volatile("ldmatrix.sync.aligned.m8n8.x4.shared.b16 {%0,%1,%2,%3}, [%4];"
                 : "=r"(r[0]), "=r"(r[1]), "=r"(r[2]), "=r"(r[3]) : "r"(addr));
}
__device__ __forceinline__ void ldsm_x4_t(uint32_t* r, uint32_t addr) {
    asm volatile("ldmatrix.sync.aligned.m8n8.x4.trans.shared.b16 {%0,%1,%2,%3}, [%4];"
                 : "=r"(r[0]), "=r"(r[1]), "=r"(r[2]), "=r"(r[3]) : "r"(addr));
}
__device__ __forceinline__ uint4 ld_relaxed_v4(const void* p) {
    uint4 v;
    asm volatile("ld.relaxed.gpu.global.v4.u32 {%0,%1,%2,%3}, [%4];" : "=r"(v.x), "=r"(v.y), "=r"(v.z), "=r"(v.w) : "l"(p) : "memory");
    return v;
}
__device__ __forceinline__ void st_relaxed_v4(void* p, uint32_t a, uint32_t b, uint32_t c, uint32_t d) {
    asm volatile("st.relaxed.gpu.global.v4.u32 [%0], {%1,%2,%3,%4};" ::"l"(p), "r"(a), "r"(b), "r"(c), "r"(d) : "memory");
}
__device__ __forceinline__ void st_relaxed_v2(void* p, uint32_t a, uint32_t b) {
    asm volatile("st.relaxed.gpu.global.v2.u32 [%0], {%1,%2};" ::"l"(p), "r"(a), "r"(b) : "memory");
}
__device__ __forceinline__ void cp_async16(uint32_t dst, const void* src) {
    asm volatile("cp.async.cg.shared.global [%0], [%1], 16;" ::"r"(dst), "l"(src) : "memory");
}
__device__ __forceinline__ void cp_async_commit() { asm volatile("cp.async.commit_group;" ::: "memory"); }
template <int N> __device__ __forceinline__ void cp_async_wait() { asm volatile("cp.async.wait_group %0;" ::"n"(N) : "memory"); }

constexpr int SPIN_LIMIT = 4000000;

__device__ __forceinline__ uint4 poll_ll(const void* p, uint32_t flag) {
    uint4 v = ld_relaxed_v4(p);
    int n = 0;
    while ((v.y != flag || v.w != flag) && ++n < SPIN_LIMIT) v = ld_relaxed_v4(p);
    return v;
}

constexpr int RT = 512;
constexpr int MEMS_LD = D_ + 8;
constexpr int HL = DH_ + 8;
struct RecurSmem {
    bf16 mem[MEM_][MEMS_LD];
    bf16 kall[2][48][HL];
    bf16 vall[2][48][HL];
    bf16 qm[MEM_][HL];
    bf16 p[MEM_][48 + 8];
    bf16 om[MEM_][HL];
    float red[12][16 * 8];
    float wred[2][5][16 * 8];
};

__global__ void __launch_bounds__(RT, 1)
recur_kernel(const bf16* __restrict__ mem0, const bf16* __restrict__ Wq, const bf16* __restrict__ Wk,
             const bf16* __restrict__ Wv, const bf16* __restrict__ Wo) {
    extern __shared__ __align__(16) uint8_t smem_raw[];
    RecurSmem& sm = *reinterpret_cast<RecurSmem*>(smem_raw);
    const int tid = threadIdx.x, lane = tid & 31, w = tid >> 5;
    const int g = lane >> 2, t = lane & 3;
    const int h = blockIdx.x >> 2, c = blockIdx.x & 3;

    uint32_t wf[20][4];
    if (w < 12) {
        int mt = w % 6, kh = w / 6;
        const bf16* W = (mt < 2) ? Wq : (mt < 4 ? Wk : Wv);
        int f0 = h * DH_ + c * 32 + (mt & 1) * 16;
#pragma unroll
        for (int i = 0; i < 20; i++) {
            int k0 = (kh * 20 + i) * 16;
            const bf16* p0 = W + (size_t)(k0 + 2 * t) * HD_ + f0 + g;
            uint16_t a, b;
            a = *(const uint16_t*)(p0);            b = *(const uint16_t*)(p0 + HD_);            wf[i][0] = a | ((uint32_t)b << 16);
            a = *(const uint16_t*)(p0 + 8);        b = *(const uint16_t*)(p0 + HD_ + 8);        wf[i][1] = a | ((uint32_t)b << 16);
            a = *(const uint16_t*)(p0 + 8 * HD_);  b = *(const uint16_t*)(p0 + 9 * HD_);        wf[i][2] = a | ((uint32_t)b << 16);
            a = *(const uint16_t*)(p0 + 8 * HD_ + 8); b = *(const uint16_t*)(p0 + 9 * HD_ + 8); wf[i][3] = a | ((uint32_t)b << 16);
        }
    } else {
        int j = w - 12, mg = j >> 1, kh = j & 1;
#pragma unroll
        for (int mi = 0; mi < 5; mi++)
#pragma unroll
            for (int ki = 0; ki < 4; ki++) {
                int col0 = c * 160 + (mg * 5 + mi) * 16;
                int e0 = h * DH_ + (kh * 4 + ki) * 16;
                const bf16* p0 = Wo + (size_t)(e0 + 2 * t) * D_ + col0 + g;
                uint16_t a, b; int i = mi * 4 + ki;
                a = *(const uint16_t*)(p0);           b = *(const uint16_t*)(p0 + D_);           wf[i][0] = a | ((uint32_t)b << 16);
                a = *(const uint16_t*)(p0 + 8);       b = *(const uint16_t*)(p0 + D_ + 8);       wf[i][1] = a | ((uint32_t)b << 16);
                a = *(const uint16_t*)(p0 + 8 * D_);  b = *(const uint16_t*)(p0 + 9 * D_);       wf[i][2] = a | ((uint32_t)b << 16);
                a = *(const uint16_t*)(p0 + 8 * D_ + 8); b = *(const uint16_t*)(p0 + 9 * D_ + 8); wf[i][3] = a | ((uint32_t)b << 16);
            }
    }
    for (int i = tid; i < 2 * 8 * HL; i += RT) {
        int b = i / (8 * HL), r = (i / HL) % 8, cc = i % HL;
        sm.kall[b][40 + r][cc] = __float2bfloat16(0.f);
        sm.vall[b][40 + r][cc] = __float2bfloat16(0.f);
    }
    auto prefetch_kv = [&](int s, int buf) {
        for (int i = tid; i < 1024; i += RT) {
            int which = i >> 9, r = (i >> 4) & 31, ch = i & 15;
            const bf16* src = g_qkv + (size_t)(s * SEG_ + r) * (3 * HD_) + (1 + which) * HD_ + h * DH_ + ch * 8;
            bf16* dst = which ? &sm.vall[buf][MEM_ + r][ch * 8] : &sm.kall[buf][MEM_ + r][ch * 8];
            cp_async16(smem_u32(dst), src);
        }
        cp_async_commit();
    };
    prefetch_kv(0, 0);

    for (int s = 0; s < NSEG_; s++) {
        const int buf = s & 1;
        const uint32_t flag = s + 1;
        if (s == 0) {
            for (int i = tid; i < MEM_ * D_ / 8; i += RT) {
                int r = i / (D_ / 8), cc = (i % (D_ / 8)) * 8;
                *reinterpret_cast<uint4*>(&sm.mem[r][cc]) = *reinterpret_cast<const uint4*>(mem0 + r * D_ + cc);
            }
        } else {
            if (w == 0) (void)poll_ll(&g_h2[(lane * 40 + (blockIdx.x & 31)) * 2], flag - 1);
            __syncthreads();
            for (int i = tid; i < MEM_ * D_ / 4; i += RT) {
                uint4 v = poll_ll(&g_h2[i * 2], flag - 1);
                int r = i / (D_ / 4), cc = (i % (D_ / 4)) * 4;
                *reinterpret_cast<uint2*>(&sm.mem[r][cc]) = make_uint2(v.x, v.z);
            }
        }
        __syncthreads();
        if (w < 12) {
            int kh = w / 6;
            float a0[4] = {0.f, 0.f, 0.f, 0.f}, a1[4] = {0.f, 0.f, 0.f, 0.f};
            uint32_t base = smem_u32(&sm.mem[lane & 7][kh * 320 + (lane >> 3) * 8]);
#pragma unroll
            for (int i = 0; i < 20; i += 2) {
                uint32_t b[4];
                ldsm_x4(b, base + i * 32);
                mma16816(a0, wf[i], b[0], b[1]);
                mma16816(a1, wf[i + 1], b[2], b[3]);
            }
            float* rp = sm.red[w];
            rp[g * 8 + 2 * t] = a0[0] + a1[0]; rp[g * 8 + 2 * t + 1] = a0[1] + a1[1];
            rp[(g + 8) * 8 + 2 * t] = a0[2] + a1[2]; rp[(g + 8) * 8 + 2 * t + 1] = a0[3] + a1[3];
        }
        __syncthreads();
        if (tid < 384) {
            int mat = tid >> 7, r = (tid >> 4) & 7, pr = tid & 15;
            int mt = mat * 2 + (pr >> 3), f = (pr & 7) * 2;
            float v0 = sm.red[mt][f * 8 + r] + sm.red[mt + 6][f * 8 + r];
            float v1 = sm.red[mt][(f + 1) * 8 + r] + sm.red[mt + 6][(f + 1) * 8 + r];
            uint32_t pk = pack_bf16(v0, v1);
            st_relaxed_v2(&g_hx[((h * 4 + c) * 3 + mat) * 128 + r * 16 + pr], pk, flag);
            if (mat) {
                bf16* dst = (mat == 1 ? g_kmem : g_vmem) + ((size_t)s * MEM_ + r) * HD_ + h * DH_ + c * 32 + pr * 2;
                *reinterpret_cast<uint32_t*>(dst) = pk;
            }
        }
        if (s == NSEG_ - 1) break;
        if (w == 0) (void)poll_ll(&g_hx[h * 4 * 384 + (lane * 24 + 7) * 2], flag);
        __syncthreads();
        for (int i = tid; i < 4 * 3 * 128 / 2; i += RT) {
            uint4 v = poll_ll(&g_hx[h * 4 * 384 + i * 2], flag);
            int cc = i / 192, rem = i % 192, mat = rem >> 6, r = (rem >> 3) & 7, pr = (rem & 7) * 2;
            int col = cc * 32 + pr * 2;
            bf16* dst = mat == 0 ? &sm.qm[r][col] : (mat == 1 ? &sm.kall[buf][r][col] : &sm.vall[buf][r][col]);
            *reinterpret_cast<uint2*>(dst) = make_uint2(v.x, v.z);
        }
        cp_async_wait<0>();
        __syncthreads();
        prefetch_kv(s + 1, buf ^ 1);
        if (w == 0) {
            float sc[3][4];
#pragma unroll
            for (int m = 0; m < 3; m++) { sc[m][0] = sc[m][1] = sc[m][2] = sc[m][3] = 0.f; }
            uint32_t qb = smem_u32(&sm.qm[lane & 7][(lane >> 3) * 8]);
#pragma unroll
            for (int kk = 0; kk < 8; kk += 2) {
                uint32_t b[4];
                ldsm_x4(b, qb + kk * 32);
#pragma unroll
                for (int m = 0; m < 3; m++) {
                    uint32_t a[4];
                    ldsm_x4(a, smem_u32(&sm.kall[buf][m * 16 + (lane & 15)][kk * 16 + (lane >> 4) * 8]));
                    mma16816(sc[m], a, b[0], b[1]);
                    ldsm_x4(a, smem_u32(&sm.kall[buf][m * 16 + (lane & 15)][kk * 16 + 16 + (lane >> 4) * 8]));
                    mma16816(sc[m], a, b[2], b[3]);
                }
            }
            const float scale = 0.08838834764831845f;
            float mx0 = -INFINITY, mx1 = -INFINITY;
#pragma unroll
            for (int m = 0; m < 3; m++)
#pragma unroll
                for (int e = 0; e < 4; e++) {
                    int key = m * 16 + g + (e >> 1) * 8;
                    float v = rbf(rbf(sc[m][e]) * scale);
                    sc[m][e] = v;
                    if (key < 40) { if (e & 1) mx1 = fmaxf(mx1, v); else mx0 = fmaxf(mx0, v); }
                }
#pragma unroll
            for (int o = 4; o < 32; o <<= 1) { mx0 = fmaxf(mx0, __shfl_xor_sync(0xffffffffu, mx0, o)); mx1 = fmaxf(mx1, __shfl_xor_sync(0xffffffffu, mx1, o)); }
            float sm0 = 0.f, sm1 = 0.f;
#pragma unroll
            for (int m = 0; m < 3; m++)
#pragma unroll
                for (int e = 0; e < 4; e++) {
                    int key = m * 16 + g + (e >> 1) * 8;
                    float ev = (key < 40) ? __expf(sc[m][e] - ((e & 1) ? mx1 : mx0)) : 0.f;
                    sc[m][e] = ev;
                    if (e & 1) sm1 += ev; else sm0 += ev;
                }
#pragma unroll
            for (int o = 4; o < 32; o <<= 1) { sm0 += __shfl_xor_sync(0xffffffffu, sm0, o); sm1 += __shfl_xor_sync(0xffffffffu, sm1, o); }
            float i0 = 1.0f / sm0, i1 = 1.0f / sm1;
#pragma unroll
            for (int m = 0; m < 3; m++)
#pragma unroll
                for (int e = 0; e < 4; e++) {
                    int key = m * 16 + g + (e >> 1) * 8;
                    sm.p[2 * t + (e & 1)][key] = __float2bfloat16_rn(sc[m][e] * ((e & 1) ? i1 : i0));
                }
        }
        __syncthreads();
        if (w < 8) {
            float o[4] = {0.f, 0.f, 0.f, 0.f};
#pragma unroll
            for (int kt = 0; kt < 3; kt++) {
                uint32_t a[4], b[2];
                ldsm_x4_t(a, smem_u32(&sm.vall[buf][kt * 16 + (lane & 7) + ((lane >> 4) & 1) * 8][w * 16 + ((lane >> 3) & 1) * 8]));
                asm volatile("ldmatrix.sync.aligned.m8n8.x2.shared.b16 {%0,%1}, [%2];" : "=r"(b[0]), "=r"(b[1])
                             : "r"(smem_u32(&sm.p[lane & 7][kt * 16 + ((lane >> 3) & 1) * 8])));
                mma16816(o, a, b[0], b[1]);
            }
            sm.om[2 * t][w * 16 + g] = __float2bfloat16_rn(o[0]);
            sm.om[2 * t + 1][w * 16 + g] = __float2bfloat16_rn(o[1]);
            sm.om[2 * t][w * 16 + g + 8] = __float2bfloat16_rn(o[2]);
            sm.om[2 * t + 1][w * 16 + g + 8] = __float2bfloat16_rn(o[3]);
        }
        __syncthreads();
        if (w >= 12) {
            int j = w - 12, mg = j >> 1, kh = j & 1;
            float acc[5][4];
#pragma unroll
            for (int mi = 0; mi < 5; mi++) { acc[mi][0] = acc[mi][1] = acc[mi][2] = acc[mi][3] = 0.f; }
            uint32_t ob = smem_u32(&sm.om[lane & 7][kh * 64 + (lane >> 3) * 8]);
#pragma unroll
            for (int ki = 0; ki < 4; ki += 2) {
                uint32_t b[4];
                ldsm_x4(b, ob + ki * 32);
#pragma unroll
                for (int mi = 0; mi < 5; mi++) { mma16816(acc[mi], wf[mi * 4 + ki], b[0], b[1]); mma16816(acc[mi], wf[mi * 4 + ki + 1], b[2], b[3]); }
            }
            if (kh == 1) {
#pragma unroll
                for (int mi = 0; mi < 5; mi++)
                    *reinterpret_cast<float4*>(&sm.wred[mg][mi][lane * 4]) = make_float4(acc[mi][0], acc[mi][1], acc[mi][2], acc[mi][3]);
            }
            asm volatile("bar.sync %0, 64;" ::"r"(1 + mg) : "memory");
            if (kh == 0) {
#pragma unroll
                for (int mi = 0; mi < 5; mi++) {
                    float4 o2 = *reinterpret_cast<float4*>(&sm.wred[mg][mi][lane * 4]);
                    int col = c * 160 + (mg * 5 + mi) * 16 + g;
                    uint2* dst = g_h1 + (size_t)h * (MEM_ * D_);
                    st_relaxed_v2(dst + (2 * t) * D_ + col, __float_as_uint(acc[mi][0] + o2.x), flag);
                    st_relaxed_v2(dst + (2 * t + 1) * D_ + col, __float_as_uint(acc[mi][1] + o2.y), flag);
                    st_relaxed_v2(dst + (2 * t) * D_ + col + 8, __float_as_uint(acc[mi][2] + o2.z), flag);
                    st_relaxed_v2(dst + (2 * t + 1) * D_ + col + 8, __float_as_uint(acc[mi][3] + o2.w), flag);
                }
            }
        }
        if (w < 10) {
            int e0 = blockIdx.x * 40 + w * 4;
            const uint2* src = g_h1 + (size_t)lane * (MEM_ * D_) + e0;
            if (w == 0) (void)poll_ll(src + 36, flag);
            asm volatile("bar.sync 3, 320;" ::: "memory");
            uint4 v0 = poll_ll(src, flag), v1 = poll_ll(src + 2, flag);
            float x0 = __uint_as_float(v0.x), x1 = __uint_as_float(v0.z), x2 = __uint_as_float(v1.x), x3 = __uint_as_float(v1.z);
#pragma unroll
            for (int o = 1; o < 32; o <<= 1) {
                x0 += __shfl_xor_sync(0xffffffffu, x0, o); x1 += __shfl_xor_sync(0xffffffffu, x1, o);
                x2 += __shfl_xor_sync(0xffffffffu, x2, o); x3 += __shfl_xor_sync(0xffffffffu, x3, o);
            }
            if (lane == 0) st_relaxed_v4(&g_h2[e0 / 2], pack_bf16(x0, x1), flag, pack_bf16(x2, x3), flag);
        }
    }
}

__global__ void __launch_bounds__(128)
attn_x_kernel() {
    __shared__ __align__(16) bf16 sq[32][HL], sk[48][HL], sv[48][HL];
    const int s = blockIdx.x >> 5, h = blockIdx.x & 31;
    const int tid = threadIdx.x, lane = tid & 31, w = tid >> 5, g = lane >> 2, t = lane & 3;
    for (int i = tid; i < (32 + 40 + 40) * 16; i += 128) {
        int r = i >> 4, ch = i & 15;
        const bf16* src; bf16* dst;
        if (r < 32) { src = g_qkv + (size_t)(s * SEG_ + r) * (3 * HD_) + h * DH_; dst = sq[r]; }
        else if (r < 72) { int rr = r - 32; dst = sk[rr];
            src = rr < 8 ? g_kmem + ((size_t)s * MEM_ + rr) * HD_ + h * DH_ : g_qkv + (size_t)(s * SEG_ + rr - 8) * (3 * HD_) + HD_ + h * DH_; }
        else { int rr = r - 72; dst = sv[rr];
            src = rr < 8 ? g_vmem + ((size_t)s * MEM_ + rr) * HD_ + h * DH_ : g_qkv + (size_t)(s * SEG_ + rr - 8) * (3 * HD_) + 2 * HD_ + h * DH_; }
        *reinterpret_cast<uint4*>(dst + ch * 8) = *reinterpret_cast<const uint4*>(src + ch * 8);
    }
    for (int i = tid; i < 8 * 16; i += 128) *reinterpret_cast<uint4*>(&sv[40 + (i >> 4)][(i & 15) * 8]) = make_uint4(0, 0, 0, 0);
    __syncthreads();
    const int rh = w & 1, dhh = w >> 1;
    float sc[5][4];
#pragma unroll
    for (int n = 0; n < 5; n++) sc[n][0] = sc[n][1] = sc[n][2] = sc[n][3] = 0.f;
#pragma unroll
    for (int kk = 0; kk < 8; kk++) {
        uint32_t a[4];
        ldsm_x4(a, smem_u32(&sq[rh * 16 + (lane & 15)][kk * 16 + (lane >> 4) * 8]));
#pragma unroll
        for (int n = 0; n < 5; n++) {
            uint32_t b[2];
            asm volatile("ldmatrix.sync.aligned.m8n8.x2.shared.b16 {%0,%1}, [%2];" : "=r"(b[0]), "=r"(b[1])
                         : "r"(smem_u32(&sk[n * 8 + (lane & 7)][kk * 16 + ((lane >> 3) & 1) * 8])));
            mma16816(sc[n], a, b[0], b[1]);
        }
    }
    const float scale = 0.08838834764831845f;
    float mx[2] = {-INFINITY, -INFINITY};
#pragma unroll
    for (int n = 0; n < 5; n++)
#pragma unroll
        for (int e = 0; e < 4; e++) {
            int row = rh * 16 + g + (e >> 1) * 8, key = n * 8 + 2 * t + (e & 1);
            float v = rbf(rbf(sc[n][e]) * scale);
            if (key > row + MEM_) v = -INFINITY;
            sc[n][e] = v;
            mx[e >> 1] = fmaxf(mx[e >> 1], v);
        }
#pragma unroll
    for (int o = 1; o < 4; o <<= 1) { mx[0] = fmaxf(mx[0], __shfl_xor_sync(0xffffffffu, mx[0], o)); mx[1] = fmaxf(mx[1], __shfl_xor_sync(0xffffffffu, mx[1], o)); }
    float sum[2] = {0.f, 0.f};
#pragma unroll
    for (int n = 0; n < 5; n++)
#pragma unroll
        for (int e = 0; e < 4; e++) { float ev = __expf(sc[n][e] - mx[e >> 1]); sc[n][e] = ev; sum[e >> 1] += ev; }
#pragma unroll
    for (int o = 1; o < 4; o <<= 1) { sum[0] += __shfl_xor_sync(0xffffffffu, sum[0], o); sum[1] += __shfl_xor_sync(0xffffffffu, sum[1], o); }
    float inv[2] = {1.0f / sum[0], 1.0f / sum[1]};
    uint32_t pa[3][4];
#pragma unroll
    for (int kt = 0; kt < 3; kt++) {
        pa[kt][0] = pack_bf16(sc[2 * kt][0] * inv[0], sc[2 * kt][1] * inv[0]);
        pa[kt][1] = pack_bf16(sc[2 * kt][2] * inv[1], sc[2 * kt][3] * inv[1]);
        if (kt < 2) {
            pa[kt][2] = pack_bf16(sc[2 * kt + 1][0] * inv[0], sc[2 * kt + 1][1] * inv[0]);
            pa[kt][3] = pack_bf16(sc[2 * kt + 1][2] * inv[1], sc[2 * kt + 1][3] * inv[1]);
        } else { pa[kt][2] = 0u; pa[kt][3] = 0u; }
    }
#pragma unroll
    for (int n = 0; n < 8; n++) {
        float o[4] = {0.f, 0.f, 0.f, 0.f};
#pragma unroll
        for (int kt = 0; kt < 3; kt++) {
            uint32_t b[2];
            asm volatile("ldmatrix.sync.aligned.m8n8.x2.trans.shared.b16 {%0,%1}, [%2];" : "=r"(b[0]), "=r"(b[1])
                         : "r"(smem_u32(&sv[kt * 16 + (lane & 15)][dhh * 64 + n * 8])));
            mma16816(o, pa[kt], b[0], b[1]);
        }
        int row = s * SEG_ + rh * 16 + g;
        bf16* dst = g_o + (size_t)row * HD_ + h * DH_ + dhh * 64 + n * 8 + 2 * t;
        *reinterpret_cast<uint32_t*>(dst) = pack_bf16(o[0], o[1]);
        *reinterpret_cast<uint32_t*>(dst + 8 * HD_) = pack_bf16(o[2], o[3]);
    }
}

typedef CUresult (*PFN_encodeTiled)(CUtensorMap*, CUtensorMapDataType, cuuint32_t, void*, const cuuint64_t*,
                                    const cuuint64_t*, const cuuint32_t*, const cuuint32_t*, CUtensorMapInterleave,
                                    CUtensorMapSwizzle, CUtensorMapL2promotion, CUtensorMapFloatOOBfill);
static PFN_encodeTiled p_encode = nullptr;

static CUtensorMap make_map(const void* ptr, uint64_t rows, uint64_t cols, uint64_t ld, uint32_t box_rows) {
    CUtensorMap m;
    cuuint64_t dims[2] = {cols, rows};
    cuuint64_t strides[1] = {ld * 2};
    cuuint32_t box[2] = {64, box_rows};
    cuuint32_t es[2] = {1, 1};
    p_encode(&m, CU_TENSOR_MAP_DATA_TYPE_BFLOAT16, 2, const_cast<void*>(ptr), dims, strides, box, es,
             CU_TENSOR_MAP_INTERLEAVE_NONE, CU_TENSOR_MAP_SWIZZLE_128B, CU_TENSOR_MAP_L2_PROMOTION_L2_128B,
             CU_TENSOR_MAP_FLOAT_OOB_FILL_NONE);
    return m;
}

template <int BN, int EPI>
static void launch_gemm(const CUtensorMap& a, const CUtensorMap& b, int M, int N, int K, EpiParams ep, cudaStream_t st) {
    constexpr int STAGE = 16384 + (BN / 64) * 8192;
    constexpr int NST = (200 * 1024) / STAGE;
    constexpr int SMEM = NST * STAGE + 1024;
    cudaFuncSetAttribute(gemm_kernel<BN, EPI>, cudaFuncAttributeMaxDynamicSharedMemorySize, SMEM);
    dim3 grid((N + BN - 1) / BN, M / 128);
    gemm_kernel<BN, EPI><<<grid, 384, SMEM, st>>>(a, b, M, N, K, ep);
}

extern "C" void kernel_launch(void* const* d_in, const int* in_sizes, int n_in, void* d_out, int out_size) {
    const bf16* x    = (const bf16*)d_in[0];
    const bf16* mem0 = (const bf16*)d_in[1];
    const bf16* Wq   = (const bf16*)d_in[2];
    const bf16* Wk   = (const bf16*)d_in[3];
    const bf16* Wv   = (const bf16*)d_in[4];
    const bf16* Wo   = (const bf16*)d_in[5];
    const bf16* w_in  = (const bf16*)d_in[8];
    const bf16* w_sp  = (const bf16*)d_in[9];
    const bf16* b_sp  = (const bf16*)d_in[10];
    const bf16* w_out = (const bf16*)d_in[11];
    bf16* out = (bf16*)d_out;
    cudaStream_t st = cudaStreamPerThread;

    if (!p_encode) {
        cudaDriverEntryPointQueryResult qr;
        cudaGetDriverEntryPoint("cuTensorMapEncodeTiled", (void**)&p_encode, cudaEnableDefault, &qr);
    }
    void *p_xn, *p_qkv, *p_z, *p_zg, *p_gate, *p_o, *p_h1, *p_h2, *p_hx;
    cudaGetSymbolAddress(&p_xn, g_xn); cudaGetSymbolAddress(&p_qkv, g_qkv); cudaGetSymbolAddress(&p_z, g_z);
    cudaGetSymbolAddress(&p_zg, g_zg); cudaGetSymbolAddress(&p_gate, g_gate); cudaGetSymbolAddress(&p_o, g_o);
    cudaGetSymbolAddress(&p_h1, g_h1); cudaGetSymbolAddress(&p_h2, g_h2); cudaGetSymbolAddress(&p_hx, g_hx);

    CUtensorMap mA_xn  = make_map(p_xn, S_, D_, D_, 128);
    CUtensorMap mA_wsp = make_map(w_sp, S_, S_, S_, 128);
    CUtensorMap mA_zg  = make_map(p_zg, S_, FH_, FH_, 128);
    CUtensorMap mA_o   = make_map(p_o, S_, HD_, HD_, 128);
    CUtensorMap mB_wq  = make_map(Wq, D_, HD_, HD_, 64);
    CUtensorMap mB_wk  = make_map(Wk, D_, HD_, HD_, 64);
    CUtensorMap mB_wv  = make_map(Wv, D_, HD_, HD_, 64);
    CUtensorMap mB_win = make_map(w_in, D_, F_, F_, 64);
    CUtensorMap mB_z2  = make_map((bf16*)p_z + FH_, S_, FH_, F_, 64);
    CUtensorMap mB_wout = make_map(w_out, FH_, D_, D_, 64);
    CUtensorMap mB_wo  = make_map(Wo, HD_, D_, D_, 64);

    cudaMemsetAsync(p_h1, 0, sizeof(uint2) * H_ * MEM_ * D_, st);
    cudaMemsetAsync(p_h2, 0, sizeof(uint2) * MEM_ * D_ / 2, st);
    cudaMemsetAsync(p_hx, 0, sizeof(uint2) * H_ * 4 * 3 * MEM_ * 16, st);

    ln_kernel<<<S_ / 8, 256, 0, st>>>(x);
    for (int i = 0; i < 3; i++) {
        EpiParams ep{(bf16*)p_qkv + i * HD_, 3 * HD_, nullptr, nullptr};
        launch_gemm<128, EPI_STORE>(mA_xn, i == 0 ? mB_wq : (i == 1 ? mB_wk : mB_wv), S_, HD_, D_, ep, st);
    }
    { EpiParams ep{(bf16*)p_z, F_, nullptr, nullptr}; launch_gemm<192, EPI_GELU>(mA_xn, mB_win, S_, F_, D_, ep, st); }
    ln2_kernel<<<S_ / 8, 256, 0, st>>>();
    { EpiParams ep{(bf16*)p_zg, FH_, (const bf16*)p_z, b_sp}; launch_gemm<128, EPI_SP>(mA_wsp, mB_z2, S_, FH_, S_, ep, st); }
    { EpiParams ep{(bf16*)p_gate, D_, nullptr, nullptr}; launch_gemm<128, EPI_SILU>(mA_zg, mB_wout, S_, D_, FH_, ep, st); }
    cudaFuncSetAttribute(recur_kernel, cudaFuncAttributeMaxDynamicSharedMemorySize, (int)sizeof(RecurSmem));
    recur_kernel<<<128, RT, sizeof(RecurSmem), st>>>(mem0, Wq, Wk, Wv, Wo);
    attn_x_kernel<<<NSEG_ * H_, 128, 0, st>>>();
    { EpiParams ep{out, D_, x, (const bf16*)p_gate}; launch_gemm<128, EPI_FINAL>(mA_o, mB_wo, S_, D_, HD_, ep, st); }
}
```

```cpp
#include <cuda_runtime.h>
#include <cuda_bf16.h>
#include <cuda.h>
#include <stdint.h>

typedef __nv_bfloat16 bf16;

constexpr int S_   = 2048;
constexpr int D_   = 640;
constexpr int H_   = 32;
constexpr int DH_  = 128;
constexpr int MEM_ = 8;
constexpr int SEG_ = 32;
constexpr int NSEG_ = S_ / SEG_;
constexpr int HD_  = H_ * DH_;
constexpr int F_   = 1728;
constexpr int FH_  = 864;

__device__ bf16 g_xn[S_ * D_];
__device__ bf16 g_qkv[(size_t)S_ * 3 * HD_];
__device__ bf16 g_z[S_ * F_];
__device__ bf16 g_zg[S_ * FH_];
__device__ bf16 g_gate[S_ * D_];
__device__ bf16 g_kmem[NSEG_ * MEM_ * HD_];
__device__ bf16 g_vmem[NSEG_ * MEM_ * HD_];
__device__ bf16 g_o[(size_t)S_ * HD_];
__device__ uint2 g_h1[H_ * MEM_ * D_];
__device__ uint2 g_h2[MEM_ * 256 * 2];
__device__ uint2 g_hx[H_ * 4 * 256 * 2];

__device__ __forceinline__ uint32_t smem_u32(const void* p) { return (uint32_t)__cvta_generic_to_shared(p); }
__device__ __forceinline__ float bf2f(bf16 v) { return __bfloat162float(v); }
__device__ __forceinline__ float rbf(float v) { return __bfloat162float(__float2bfloat16_rn(v)); }
__device__ __forceinline__ uint32_t pack_bf16(float lo, float hi) {
    __nv_bfloat162 t = __floats2bfloat162_rn(lo, hi);
    return *reinterpret_cast<uint32_t*>(&t);
}
__device__ __forceinline__ float lo_f(uint32_t u) { return __uint_as_float(u << 16); }
__device__ __forceinline__ float hi_f(uint32_t u) { return __uint_as_float(u & 0xffff0000u); }

__device__ __forceinline__ void mbar_init(uint32_t bar, uint32_t cnt) {
    asm volatile("mbarrier.init.shared.b64 [%0], %1;" ::"r"(bar), "r"(cnt));
}
__device__ __forceinline__ void mbar_expect_tx(uint32_t bar, uint32_t bytes) {
    asm volatile("mbarrier.arrive.expect_tx.shared.b64 _, [%0], %1;" ::"r"(bar), "r"(bytes) : "memory");
}
__device__ __forceinline__ void mbar_arrive(uint32_t bar) {
    asm volatile("mbarrier.arrive.shared.b64 _, [%0];" ::"r"(bar) : "memory");
}
__device__ __forceinline__ void mbar_wait(uint32_t bar, uint32_t parity) {
    asm volatile(
        "{\n .reg .pred p;\n"
        "WAIT_%=:\n"
        " mbarrier.try_wait.parity.shared.b64 p, [%0], %1;\n"
        " @p bra DONE_%=;\n"
        " bra WAIT_%=;\n"
        "DONE_%=:\n}\n" ::"r"(bar), "r"(parity) : "memory");
}
__device__ __forceinline__ void tma_load_2d(uint32_t dst, const CUtensorMap* tm, uint32_t bar, int c0, int c1) {
    asm volatile(
        "cp.async.bulk.tensor.2d.shared::cluster.global.mbarrier::complete_tx::bytes [%0], [%1, {%3, %4}], [%2];"
        ::"r"(dst), "l"(tm), "r"(bar), "r"(c0), "r"(c1) : "memory");
}
__device__ __forceinline__ void wgmma_fence() { asm volatile("wgmma.fence.sync.aligned;" ::: "memory"); }
__device__ __forceinline__ void wgmma_commit() { asm volatile("wgmma.commit_group.sync.aligned;" ::: "memory"); }
template <int N> __device__ __forceinline__ void wgmma_wait() { asm volatile("wgmma.wait_group.sync.aligned %0;" ::"n"(N) : "memory"); }

__device__ __forceinline__ uint64_t make_desc(uint32_t addr, uint32_t lbo, uint32_t sbo) {
    return (uint64_t)((addr & 0x3FFFF) >> 4) | ((uint64_t)(lbo >> 4) << 16) | ((uint64_t)(sbo >> 4) << 32) | (1ull << 62);
}

template <int N> struct Wgmma;
template <> struct Wgmma<128> {
    static __device__ __forceinline__ void mma(float* d, uint64_t da, uint64_t db, int sd) {
        asm volatile(
            "{\n.reg .pred p;\nsetp.ne.b32 p, %66, 0;\n"
            "wgmma.mma_async.sync.aligned.m64n128k16.f32.bf16.bf16 "
            "{%0,%1,%2,%3,%4,%5,%6,%7,%8,%9,%10,%11,%12,%13,%14,%15,"
            "%16,%17,%18,%19,%20,%21,%22,%23,%24,%25,%26,%27,%28,%29,%30,%31,"
            "%32,%33,%34,%35,%36,%37,%38,%39,%40,%41,%42,%43,%44,%45,%46,%47,"
            "%48,%49,%50,%51,%52,%53,%54,%55,%56,%57,%58,%59,%60,%61,%62,%63},"
            "%64,%65,p,1,1,0,1;\n}\n"
            : "+f"(d[0]), "+f"(d[1]), "+f"(d[2]), "+f"(d[3]), "+f"(d[4]), "+f"(d[5]), "+f"(d[6]), "+f"(d[7]),
              "+f"(d[8]), "+f"(d[9]), "+f"(d[10]), "+f"(d[11]), "+f"(d[12]), "+f"(d[13]), "+f"(d[14]), "+f"(d[15]),
              "+f"(d[16]), "+f"(d[17]), "+f"(d[18]), "+f"(d[19]), "+f"(d[20]), "+f"(d[21]), "+f"(d[22]), "+f"(d[23]),
              "+f"(d[24]), "+f"(d[25]), "+f"(d[26]), "+f"(d[27]), "+f"(d[28]), "+f"(d[29]), "+f"(d[30]), "+f"(d[31]),
              "+f"(d[32]), "+f"(d[33]), "+f"(d[34]), "+f"(d[35]), "+f"(d[36]), "+f"(d[37]), "+f"(d[38]), "+f"(d[39]),
              "+f"(d[40]), "+f"(d[41]), "+f"(d[42]), "+f"(d[43]), "+f"(d[44]), "+f"(d[45]), "+f"(d[46]), "+f"(d[47]),
              "+f"(d[48]), "+f"(d[49]), "+f"(d[50]), "+f"(d[51]), "+f"(d[52]), "+f"(d[53]), "+f"(d[54]), "+f"(d[55]),
              "+f"(d[56]), "+f"(d[57]), "+f"(d[58]), "+f"(d[59]), "+f"(d[60]), "+f"(d[61]), "+f"(d[62]), "+f"(d[63])
            : "l"(da), "l"(db), "r"(sd));
    }
};
template <> struct Wgmma<192> {
    static __device__ __forceinline__ void mma(float* d, uint64_t da, uint64_t db, int sd) {
        asm volatile(
            "{\n.reg .pred p;\nsetp.ne.b32 p, %98, 0;\n"
            "wgmma.mma_async.sync.aligned.m64n192k16.f32.bf16.bf16 "
            "{%0,%1,%2,%3,%4,%5,%6,%7,%8,%9,%10,%11,%12,%13,%14,%15,"
            "%16,%17,%18,%19,%20,%21,%22,%23,%24,%25,%26,%27,%28,%29,%30,%31,"
            "%32,%33,%34,%35,%36,%37,%38,%39,%40,%41,%42,%43,%44,%45,%46,%47,"
            "%48,%49,%50,%51,%52,%53,%54,%55,%56,%57,%58,%59,%60,%61,%62,%63,"
            "%64,%65,%66,%67,%68,%69,%70,%71,%72,%73,%74,%75,%76,%77,%78,%79,"
            "%80,%81,%82,%83,%84,%85,%86,%87,%88,%89,%90,%91,%92,%93,%94,%95},"
            "%96,%97,p,1,1,0,1;\n}\n"
            : "+f"(d[0]), "+f"(d[1]), "+f"(d[2]), "+f"(d[3]), "+f"(d[4]), "+f"(d[5]), "+f"(d[6]), "+f"(d[7]),
              "+f"(d[8]), "+f"(d[9]), "+f"(d[10]), "+f"(d[11]), "+f"(d[12]), "+f"(d[13]), "+f"(d[14]), "+f"(d[15]),
              "+f"(d[16]), "+f"(d[17]), "+f"(d[18]), "+f"(d[19]), "+f"(d[20]), "+f"(d[21]), "+f"(d[22]), "+f"(d[23]),
              "+f"(d[24]), "+f"(d[25]), "+f"(d[26]), "+f"(d[27]), "+f"(d[28]), "+f"(d[29]), "+f"(d[30]), "+f"(d[31]),
              "+f"(d[32]), "+f"(d[33]), "+f"(d[34]), "+f"(d[35]), "+f"(d[36]), "+f"(d[37]), "+f"(d[38]), "+f"(d[39]),
              "+f"(d[40]), "+f"(d[41]), "+f"(d[42]), "+f"(d[43]), "+f"(d[44]), "+f"(d[45]), "+f"(d[46]), "+f"(d[47]),
              "+f"(d[48]), "+f"(d[49]), "+f"(d[50]), "+f"(d[51]), "+f"(d[52]), "+f"(d[53]), "+f"(d[54]), "+f"(d[55]),
              "+f"(d[56]), "+f"(d[57]), "+f"(d[58]), "+f"(d[59]), "+f"(d[60]), "+f"(d[61]), "+f"(d[62]), "+f"(d[63]),
              "+f"(d[64]), "+f"(d[65]), "+f"(d[66]), "+f"(d[67]), "+f"(d[68]), "+f"(d[69]), "+f"(d[70]), "+f"(d[71]),
              "+f"(d[72]), "+f"(d[73]), "+f"(d[74]), "+f"(d[75]), "+f"(d[76]), "+f"(d[77]), "+f"(d[78]), "+f"(d[79]),
              "+f"(d[80]), "+f"(d[81]), "+f"(d[82]), "+f"(d[83]), "+f"(d[84]), "+f"(d[85]), "+f"(d[86]), "+f"(d[87]),
              "+f"(d[88]), "+f"(d[89]), "+f"(d[90]), "+f"(d[91]), "+f"(d[92]), "+f"(d[93]), "+f"(d[94]), "+f"(d[95])
            : "l"(da), "l"(db), "r"(sd));
    }
};

template <int W>
__device__ __forceinline__ void ln_row(const bf16* __restrict__ src, bf16* __restrict__ dst, int lane) {
    constexpr int NP = W / 64;
    constexpr int REM = (W / 2) % 32;
    uint32_t v[NP + 1];
    const uint32_t* s32 = reinterpret_cast<const uint32_t*>(src);
    float sum = 0.f;
#pragma unroll
    for (int i = 0; i < NP; i++) { v[i] = s32[i * 32 + lane]; sum += lo_f(v[i]) + hi_f(v[i]); }
    if (REM) { v[NP] = (lane < REM) ? s32[NP * 32 + lane] : 0u; if (lane < REM) sum += lo_f(v[NP]) + hi_f(v[NP]); }
#pragma unroll
    for (int o = 16; o; o >>= 1) sum += __shfl_xor_sync(0xffffffffu, sum, o);
    float mean = sum * (1.0f / W);
    float vs = 0.f;
#pragma unroll
    for (int i = 0; i < NP; i++) { float a = lo_f(v[i]) - mean, b = hi_f(v[i]) - mean; vs += a * a + b * b; }
    if (REM && lane < REM) { float a = lo_f(v[NP]) - mean, b = hi_f(v[NP]) - mean; vs += a * a + b * b; }
#pragma unroll
    for (int o = 16; o; o >>= 1) vs += __shfl_xor_sync(0xffffffffu, vs, o);
    float var = rbf(vs * (1.0f / W));
    float mb = rbf(mean);
    float den = rbf(sqrtf(rbf(var + 1e-5f)));
    uint32_t* d32 = reinterpret_cast<uint32_t*>(dst);
#pragma unroll
    for (int i = 0; i < NP; i++) d32[i * 32 + lane] = pack_bf16(rbf(lo_f(v[i]) - mb) / den, rbf(hi_f(v[i]) - mb) / den);
    if (REM && lane < REM) d32[NP * 32 + lane] = pack_bf16(rbf(lo_f(v[NP]) - mb) / den, rbf(hi_f(v[NP]) - mb) / den);
}

__global__ void ln_kernel(const bf16* __restrict__ x) {
    int row = blockIdx.x * 8 + (threadIdx.x >> 5);
    ln_row<D_>(x + (size_t)row * D_, g_xn + (size_t)row * D_, threadIdx.x & 31);
}
__global__ void ln2_kernel() {
    int row = blockIdx.x * 8 + (threadIdx.x >> 5);
    bf16* p = g_z + (size_t)row * F_ + FH_;
    ln_row<FH_>(p, p, threadIdx.x & 31);
}

enum { EPI_STORE = 0, EPI_GELU = 1, EPI_SP = 2, EPI_SILU = 3, EPI_FINAL = 4 };
struct EpiParams {
    bf16* out; int ldo;
    const bf16* aux0;
    const bf16* aux1;
};

__device__ __forceinline__ float gelu_tanh_f(float x) {
    const float k0 = 0.7978845608028654f, k1 = 0.044715f;
    float inner = k0 * (x + k1 * x * x * x);
    return 0.5f * x * (1.0f + tanhf(inner));
}
__device__ __forceinline__ float silu_f(float x) { return x / (1.0f + expf(-x)); }

template <int BN, int EPI>
__global__ void __launch_bounds__(384, 1)
gemm_kernel(const __grid_constant__ CUtensorMap tmA, const __grid_constant__ CUtensorMap tmB,
            int M, int N, int K, EpiParams ep) {
    constexpr int BM = 128, BK = 64;
    constexpr int A_BYTES = BM * BK * 2;
    constexpr int B_BYTES = (BN / 64) * 8192;
    constexpr int STAGE = A_BYTES + B_BYTES;
    constexpr int NST = (200 * 1024) / STAGE;
    extern __shared__ __align__(1024) uint8_t smem_raw[];
    uint8_t* smem = (uint8_t*)(((uintptr_t)smem_raw + 1023) & ~(uintptr_t)1023);
    __shared__ __align__(8) uint64_t full_bar[NST], empty_bar[NST];

    const int tid = threadIdx.x, wg = tid >> 7;
    const int m0 = blockIdx.y * BM, n0 = blockIdx.x * BN;
    const int nk = (K + BK - 1) / BK;

    if (tid == 0) {
        for (int i = 0; i < NST; i++) { mbar_init(smem_u32(&full_bar[i]), 1); mbar_init(smem_u32(&empty_bar[i]), 2); }
        asm volatile("fence.mbarrier_init.release.cluster;" ::: "memory");
    }
    __syncthreads();

    if (wg == 0) {
        if (tid == 0) {
            for (int kt = 0; kt < nk; kt++) {
                int st = kt % NST; uint32_t ph = (kt / NST) & 1;
                mbar_wait(smem_u32(&empty_bar[st]), ph ^ 1);
                uint32_t fb = smem_u32(&full_bar[st]);
                mbar_expect_tx(fb, STAGE);
                uint32_t sa = smem_u32(smem + st * STAGE);
                tma_load_2d(sa, &tmA, fb, kt * BK, m0);
#pragma unroll
                for (int j = 0; j < BN / 64; j++) tma_load_2d(sa + A_BYTES + j * 8192, &tmB, fb, n0 + j * 64, kt * BK);
            }
        }
    } else {
        const int cw = wg - 1;
        float acc[BN / 2];
#pragma unroll
        for (int i = 0; i < BN / 2; i++) acc[i] = 0.f;
        for (int kt = 0; kt < nk; kt++) {
            int st = kt % NST; uint32_t ph = (kt / NST) & 1;
            mbar_wait(smem_u32(&full_bar[st]), ph);
            uint32_t sa = smem_u32(smem + st * STAGE) + cw * 64 * 128;
            uint32_t sb = smem_u32(smem + st * STAGE) + A_BYTES;
            wgmma_fence();
#pragma unroll
            for (int k = 0; k < BK / 16; k++) {
                uint64_t da = make_desc(sa + k * 32, 16, 1024);
                uint64_t db = make_desc(sb + k * 2048, 8192, 1024);
                Wgmma<BN>::mma(acc, da, db, 1);
            }
            wgmma_commit();
            wgmma_wait<0>();
            if ((tid & 127) == 0) mbar_arrive(smem_u32(&empty_bar[st]));
        }
        const int lane = tid & 31, wi = (tid >> 5) & 3, g = lane >> 2, t = lane & 3;
        const int r0 = m0 + cw * 64 + wi * 16 + g;
#pragma unroll
        for (int j = 0; j < BN / 8; j++) {
            int col = n0 + j * 8 + 2 * t;
            if (col >= N) continue;
#pragma unroll
            for (int hh = 0; hh < 2; hh++) {
                int row = r0 + hh * 8;
                float v0 = rbf(acc[4 * j + 2 * hh]), v1 = rbf(acc[4 * j + 2 * hh + 1]);
                uint32_t o;
                if (EPI == EPI_STORE) {
                    o = pack_bf16(v0, v1);
                } else if (EPI == EPI_GELU) {
                    o = pack_bf16(gelu_tanh_f(v0), gelu_tanh_f(v1));
                } else if (EPI == EPI_SP) {
                    float b = bf2f(ep.aux1[row]);
                    float g0 = rbf(v0 + b), g1 = rbf(v1 + b);
                    uint32_t z1 = *reinterpret_cast<const uint32_t*>(ep.aux0 + (size_t)row * F_ + col);
                    o = pack_bf16(lo_f(z1) * g0, hi_f(z1) * g1);
                } else if (EPI == EPI_SILU) {
                    o = pack_bf16(silu_f(v0), silu_f(v1));
                } else {
                    uint32_t xg = *reinterpret_cast<const uint32_t*>(ep.aux0 + (size_t)row * D_ + col);
                    uint32_t gt = *reinterpret_cast<const uint32_t*>(ep.aux1 + (size_t)row * D_ + col);
                    o = pack_bf16(lo_f(xg) + rbf(v0 * lo_f(gt)), hi_f(xg) + rbf(v1 * hi_f(gt)));
                }
                *reinterpret_cast<uint32_t*>(ep.out + (size_t)row * ep.ldo + col) = o;
            }
        }
    }
}

__device__ __forceinline__ void mma16816(float* c, const uint32_t* a, uint32_t b0, uint32_t b1) {
    asm volatile(
        "mma.sync.aligned.m16n8k16.row.col.f32.bf16.bf16.f32 {%0,%1,%2,%3}, {%4,%5,%6,%7}, {%8,%9}, {%0,%1,%2,%3};"
        : "+f"(c[0]), "+f"(c[1]), "+f"(c[2]), "+f"(c[3])
        : "r"(a[0]), "r"(a[1]), "r"(a[2]), "r"(a[3]), "r"(b0), "r"(b1));
}
__device__ __forceinline__ void ldsm_x4(uint32_t* r, uint32_t addr) {
    asm volatile("ldmatrix.sync.aligned.m8n8.x4.shared.b16 {%0,%1,%2,%3}, [%4];"
                 : "=r"(r[0]), "=r"(r[1]), "=r"(r[2]), "=r"(r[3]) : "r"(addr));
}
__device__ __forceinline__ void ldsm_x4_t(uint32_t* r, uint32_t addr) {
    asm volatile("ldmatrix.sync.aligned.m8n8.x4.trans.shared.b16 {%0,%1,%2,%3}, [%4];"
                 : "=r"(r[0]), "=r"(r[1]), "=r"(r[2]), "=r"(r[3]) : "r"(addr));
}
__device__ __forceinline__ uint4 ld_relaxed_v4(const void* p) {
    uint4 v;
    asm volatile("ld.relaxed.gpu.global.v4.u32 {%0,%1,%2,%3}, [%4];" : "=r"(v.x), "=r"(v.y), "=r"(v.z), "=r"(v.w) : "l"(p) : "memory");
    return v;
}
__device__ __forceinline__ void st_relaxed_v4(void* p, uint32_t a, uint32_t b, uint32_t c, uint32_t d) {
    asm volatile("st.relaxed.gpu.global.v4.u32 [%0], {%1,%2,%3,%4};" ::"l"(p), "r"(a), "r"(b), "r"(c), "r"(d) : "memory");
}
__device__ __forceinline__ void st_relaxed_v2(void* p, uint32_t a, uint32_t b) {
    asm volatile("st.relaxed.gpu.global.v2.u32 [%0], {%1,%2};" ::"l"(p), "r"(a), "r"(b) : "memory");
}
__device__ __forceinline__ void cp_async16(uint32_t dst, const void* src) {
    asm volatile("cp.async.cg.shared.global [%0], [%1], 16;" ::"r"(dst), "l"(src) : "memory");
}
__device__ __forceinline__ void cp_async_commit() { asm volatile("cp.async.commit_group;" ::: "memory"); }
template <int N> __device__ __forceinline__ void cp_async_wait() { asm volatile("cp.async.wait_group %0;" ::"n"(N) : "memory"); }

#define PROF(i) do {} while (0)
constexpr int SPIN_LIMIT = 4000000;

__device__ __forceinline__ uint4 poll_ll(const void* p, uint32_t flag) {
    uint4 v = ld_relaxed_v4(p);
    int n = 0;
    while ((v.y != flag || v.w != flag) && ++n < SPIN_LIMIT) v = ld_relaxed_v4(p);
    return v;
}

constexpr int RT = 512;
constexpr int MEMS_LD = D_ + 8;
constexpr int HL = DH_ + 8;
struct RecurSmem {
    bf16 mem[MEM_][MEMS_LD];
    bf16 kall[2][48][HL];
    bf16 vall[2][48][HL];
    bf16 qm[16][HL];
    float sc[MEM_][40];
    bf16 p[MEM_][48 + 8];
    bf16 om[MEM_][HL];
    float red[12][16 * 8];
    float wred[2][5][16 * 8];
};

__global__ void __launch_bounds__(RT, 1)
recur_kernel(const bf16* __restrict__ mem0, const bf16* __restrict__ Wq, const bf16* __restrict__ Wk,
             const bf16* __restrict__ Wv, const bf16* __restrict__ Wo) {
    extern __shared__ __align__(16) uint8_t smem_raw[];
    RecurSmem& sm = *reinterpret_cast<RecurSmem*>(smem_raw);
    const int tid = threadIdx.x, lane = tid & 31, w = tid >> 5;
    const int g = lane >> 2, t = lane & 3;
    const int h = blockIdx.x >> 2, c = blockIdx.x & 3;

    uint32_t wf[20][4];
    if (w < 12) {
        int mt = w % 6, kh = w / 6;
        const bf16* W = (mt < 2) ? Wq : (mt < 4 ? Wk : Wv);
        int f0 = h * DH_ + c * 32 + (mt & 1) * 16;
#pragma unroll
        for (int i = 0; i < 20; i++) {
            int k0 = (kh * 20 + i) * 16;
            const bf16* p0 = W + (size_t)(k0 + 2 * t) * HD_ + f0 + g;
            uint16_t a, b;
            a = *(const uint16_t*)(p0);            b = *(const uint16_t*)(p0 + HD_);            wf[i][0] = a | ((uint32_t)b << 16);
            a = *(const uint16_t*)(p0 + 8);        b = *(const uint16_t*)(p0 + HD_ + 8);        wf[i][1] = a | ((uint32_t)b << 16);
            a = *(const uint16_t*)(p0 + 8 * HD_);  b = *(const uint16_t*)(p0 + 9 * HD_);        wf[i][2] = a | ((uint32_t)b << 16);
            a = *(const uint16_t*)(p0 + 8 * HD_ + 8); b = *(const uint16_t*)(p0 + 9 * HD_ + 8); wf[i][3] = a | ((uint32_t)b << 16);
        }
    } else {
        int j = w - 12, mg = j >> 1, kh = j & 1;
#pragma unroll
        for (int mi = 0; mi < 5; mi++)
#pragma unroll
            for (int ki = 0; ki < 4; ki++) {
                int col0 = c * 160 + (mg * 5 + mi) * 16;
                int e0 = h * DH_ + (kh * 4 + ki) * 16;
                const bf16* p0 = Wo + (size_t)(e0 + 2 * t) * D_ + col0 + g;
                uint16_t a, b; int i = mi * 4 + ki;
                a = *(const uint16_t*)(p0);           b = *(const uint16_t*)(p0 + D_);           wf[i][0] = a | ((uint32_t)b << 16);
                a = *(const uint16_t*)(p0 + 8);       b = *(const uint16_t*)(p0 + D_ + 8);       wf[i][1] = a | ((uint32_t)b << 16);
                a = *(const uint16_t*)(p0 + 8 * D_);  b = *(const uint16_t*)(p0 + 9 * D_);       wf[i][2] = a | ((uint32_t)b << 16);
                a = *(const uint16_t*)(p0 + 8 * D_ + 8); b = *(const uint16_t*)(p0 + 9 * D_ + 8); wf[i][3] = a | ((uint32_t)b << 16);
            }
    }
    for (int i = tid; i < 2 * 8 * HL; i += RT) {
        int b = i / (8 * HL), r = (i / HL) % 8, cc = i % HL;
        sm.kall[b][40 + r][cc] = __float2bfloat16(0.f);
        sm.vall[b][40 + r][cc] = __float2bfloat16(0.f);
    }
    for (int i = tid; i < 8 * HL; i += RT) sm.qm[8 + i / HL][i % HL] = __float2bfloat16(0.f);
    for (int i = tid; i < 8 * 56; i += RT) sm.p[i / 56][i % 56] = __float2bfloat16(0.f);

    const bf16* kv_src = g_qkv + (size_t)((tid >> 4) & 31) * (3 * HD_) + HD_ + h * DH_ + (tid & 15) * 8;
    const uint32_t kv_dst0 = smem_u32(&sm.kall[0][MEM_ + ((tid >> 4) & 31)][(tid & 15) * 8]);
    const uint32_t kv_dst1 = smem_u32(&sm.vall[0][MEM_ + ((tid >> 4) & 31)][(tid & 15) * 8]);
    constexpr uint32_t KV_BUF = 48 * HL * 2;
    auto prefetch_kv = [&](int s, int buf) {
        const bf16* src = kv_src + (size_t)s * SEG_ * (3 * HD_);
        cp_async16(kv_dst0 + buf * KV_BUF, src);
        cp_async16(kv_dst1 + buf * KV_BUF, src + HD_);
        cp_async_commit();
    };
    const uint4* h2_src = reinterpret_cast<const uint4*>(g_h2) + (tid >> 6) * 256 + (tid & 63);
    const uint32_t h2_dst = smem_u32(&sm.mem[tid >> 6][(tid & 63) * 4]);
    const uint4* hx_base = reinterpret_cast<const uint4*>(g_hx) + h * 1024;
    const int hx_i = tid & 127, hx_cc = tid >> 7;
    uint32_t hx_dst[2];
#pragma unroll
    for (int j = 0; j < 2; j++) {
        int idx = hx_i + j * 128, mat = idx >> 6, r = (idx >> 3) & 7, q = idx & 7;
        int col = hx_cc * 32 + q * 4;
        hx_dst[j] = mat == 0 ? smem_u32(&sm.qm[r][col]) : (mat == 1 ? smem_u32(&sm.kall[0][r][col]) : smem_u32(&sm.vall[0][r][col]));
    }
    const uint32_t hx_bufoff1 = (hx_i >= 64) ? KV_BUF : 0;
    const int pb_mat = tid >> 7, pb_r = (tid >> 4) & 7, pb_pr = tid & 15;
    uint2* pb_dst = g_hx + (h * 1024 + c * 256 + pb_mat * 64 + pb_r * 8) * 2 + pb_pr;
    const float* pb_src = &sm.red[pb_mat * 2 + (pb_pr >> 3)][(pb_pr & 7) * 16 + pb_r];
    bf16* pb_kv = (pb_mat == 1 ? g_kmem : g_vmem) + (size_t)pb_r * HD_ + h * DH_ + c * 32 + pb_pr * 2;

    prefetch_kv(0, 0);

    for (int s = 0; s < NSEG_; s++) {
        const int buf = s & 1;
        const uint32_t flag = s + 1;
        PROF(0);
        if (s == 0) {
            for (int i = tid; i < MEM_ * D_ / 8; i += RT) {
                int r = i / (D_ / 8), cc = (i % (D_ / 8)) * 8;
                *reinterpret_cast<uint4*>(&sm.mem[r][cc]) = *reinterpret_cast<const uint4*>(mem0 + r * D_ + cc);
            }
        } else {
            if (w == 0) (void)poll_ll(reinterpret_cast<const uint4*>(g_h2) + (lane & 7) * 256 + (lane >> 3) * 40 + (blockIdx.x & 31), s);
            __syncthreads();
            PROF(1);
            uint4 v0 = ld_relaxed_v4(h2_src), v1 = ld_relaxed_v4(h2_src + 64), v2;
            const bool has2 = (tid & 63) < 32;
            if (has2) v2 = ld_relaxed_v4(h2_src + 128);
            if (v0.y != s || v0.w != s) v0 = poll_ll(h2_src, s);
            asm volatile("st.shared.v2.u32 [%0], {%1,%2};" ::"r"(h2_dst), "r"(v0.x), "r"(v0.z));
            if (v1.y != s || v1.w != s) v1 = poll_ll(h2_src + 64, s);
            asm volatile("st.shared.v2.u32 [%0], {%1,%2};" ::"r"(h2_dst + 512), "r"(v1.x), "r"(v1.z));
            if (has2) {
                if (v2.y != s || v2.w != s) v2 = poll_ll(h2_src + 128, s);
                asm volatile("st.shared.v2.u32 [%0], {%1,%2};" ::"r"(h2_dst + 1024), "r"(v2.x), "r"(v2.z));
            }
        }
        __syncthreads();
        PROF(2);
        if (w < 12) {
            int kh = w / 6;
            float a0[4] = {0.f, 0.f, 0.f, 0.f}, a1[4] = {0.f, 0.f, 0.f, 0.f};
            uint32_t base = smem_u32(&sm.mem[lane & 7][kh * 320 + (lane >> 3) * 8]);
            uint32_t b[10][4];
#pragma unroll
            for (int i = 0; i < 10; i++) ldsm_x4(b[i], base + i * 64);
#pragma unroll
            for (int i = 0; i < 10; i++) {
                mma16816(a0, wf[2 * i], b[i][0], b[i][1]);
                mma16816(a1, wf[2 * i + 1], b[i][2], b[i][3]);
            }
            float* rp = sm.red[w];
            *reinterpret_cast<float2*>(&rp[g * 8 + 2 * t]) = make_float2(a0[0] + a1[0], a0[1] + a1[1]);
            *reinterpret_cast<float2*>(&rp[(g + 8) * 8 + 2 * t]) = make_float2(a0[2] + a1[2], a0[3] + a1[3]);
        }
        __syncthreads();
        PROF(3);
        if (tid < 384) {
            uint32_t pk = pack_bf16(pb_src[0] + pb_src[6 * 128], pb_src[8] + pb_src[6 * 128 + 8]);
            st_relaxed_v2(pb_dst, pk, flag);
            if (pb_mat) *reinterpret_cast<uint32_t*>(pb_kv + (size_t)s * (MEM_ * HD_)) = pk;
        }
        if (s == NSEG_ - 1) break;
        PROF(4);
        if (w == 0) (void)poll_ll(hx_base + (lane >> 3) * 256 + (lane & 7) * 24 + 5, flag);
        __syncthreads();
        PROF(5);
        {
            const uint4* src = hx_base + hx_cc * 256 + hx_i;
            uint4 v0 = ld_relaxed_v4(src), v1;
            const bool has1 = hx_i < 64;
            if (has1) v1 = ld_relaxed_v4(src + 128);
            if (v0.y != flag || v0.w != flag) v0 = poll_ll(src, flag);
            asm volatile("st.shared.v2.u32 [%0], {%1,%2};" ::"r"(hx_dst[0] + (buf ? hx_bufoff1 : 0)), "r"(v0.x), "r"(v0.z));
            if (has1) {
                if (v1.y != flag || v1.w != flag) v1 = poll_ll(src + 128, flag);
                asm volatile("st.shared.v2.u32 [%0], {%1,%2};" ::"r"(hx_dst[1] + buf * KV_BUF), "r"(v1.x), "r"(v1.z));
            }
        }
        cp_async_wait<0>();
        __syncthreads();
        PROF(6);
        if (w < 5) {
            uint32_t a[8][4], b[4][4];
            uint32_t qa = smem_u32(&sm.qm[lane & 15][(lane >> 4) * 8]);
            uint32_t kb = smem_u32(&sm.kall[buf][w * 8 + (lane & 7)][(lane >> 3) * 8]);
#pragma unroll
            for (int kk = 0; kk < 4; kk++) ldsm_x4(b[kk], kb + kk * 64);
#pragma unroll
            for (int kk = 0; kk < 8; kk++) ldsm_x4(a[kk], qa + kk * 32);
            float s0[4] = {0.f, 0.f, 0.f, 0.f}, s1[4] = {0.f, 0.f, 0.f, 0.f};
#pragma unroll
            for (int kk = 0; kk < 4; kk++) { mma16816(s0, a[2 * kk], b[kk][0], b[kk][1]); mma16816(s1, a[2 * kk + 1], b[kk][2], b[kk][3]); }
            const float scale = 0.08838834764831845f;
            *reinterpret_cast<float2*>(&sm.sc[g][w * 8 + 2 * t]) =
                make_float2(rbf(rbf(s0[0] + s1[0]) * scale), rbf(rbf(s0[1] + s1[1]) * scale));
        } else if (w == 5) {
            prefetch_kv(s + 1, buf ^ 1);
        }
        if (w >= 6) prefetch_kv(s + 1, buf ^ 1);
        else if (w < 5) prefetch_kv(s + 1, buf ^ 1);
        __syncthreads();
        if (w < 8) {
            float v0 = sm.sc[w][lane], v1 = (lane < 8) ? sm.sc[w][32 + lane] : -INFINITY;
            float mx = fmaxf(v0, v1);
#pragma unroll
            for (int o = 16; o; o >>= 1) mx = fmaxf(mx, __shfl_xor_sync(0xffffffffu, mx, o));
            float e0 = __expf(v0 - mx), e1 = (lane < 8) ? __expf(v1 - mx) : 0.f;
            float sum = e0 + e1;
#pragma unroll
            for (int o = 16; o; o >>= 1) sum += __shfl_xor_sync(0xffffffffu, sum, o);
            float inv = 1.0f / sum;
            sm.p[w][lane] = __float2bfloat16_rn(e0 * inv);
            if (lane < 8) sm.p[w][32 + lane] = __float2bfloat16_rn(e1 * inv);
        }
        __syncthreads();
        PROF(7);
        if (w < 8) {
            float o[4] = {0.f, 0.f, 0.f, 0.f};
            uint32_t a[3][4], b[3][2];
#pragma unroll
            for (int kt = 0; kt < 3; kt++) {
                ldsm_x4_t(a[kt], smem_u32(&sm.vall[buf][kt * 16 + (lane & 7) + ((lane >> 4) & 1) * 8][w * 16 + ((lane >> 3) & 1) * 8]));
                asm volatile("ldmatrix.sync.aligned.m8n8.x2.shared.b16 {%0,%1}, [%2];" : "=r"(b[kt][0]), "=r"(b[kt][1])
                             : "r"(smem_u32(&sm.p[lane & 7][kt * 16 + ((lane >> 3) & 1) * 8])));
            }
#pragma unroll
            for (int kt = 0; kt < 3; kt++) mma16816(o, a[kt], b[kt][0], b[kt][1]);
            sm.om[2 * t][w * 16 + g] = __float2bfloat16_rn(o[0]);
            sm.om[2 * t + 1][w * 16 + g] = __float2bfloat16_rn(o[1]);
            sm.om[2 * t][w * 16 + g + 8] = __float2bfloat16_rn(o[2]);
            sm.om[2 * t + 1][w * 16 + g + 8] = __float2bfloat16_rn(o[3]);
        }
        __syncthreads();
        PROF(8);
        if (w >= 12) {
            int j = w - 12, mg = j >> 1, kh = j & 1;
            float acc[5][4];
#pragma unroll
            for (int mi = 0; mi < 5; mi++) { acc[mi][0] = acc[mi][1] = acc[mi][2] = acc[mi][3] = 0.f; }
            uint32_t ob = smem_u32(&sm.om[lane & 7][kh * 64 + (lane >> 3) * 8]);
            uint32_t b[2][4];
            ldsm_x4(b[0], ob); ldsm_x4(b[1], ob + 64);
#pragma unroll
            for (int ki = 0; ki < 4; ki++)
#pragma unroll
                for (int mi = 0; mi < 5; mi++) mma16816(acc[mi], wf[mi * 4 + ki], b[ki >> 1][(ki & 1) * 2], b[ki >> 1][(ki & 1) * 2 + 1]);
            if (kh == 1) {
#pragma unroll
                for (int mi = 0; mi < 5; mi++)
                    *reinterpret_cast<float4*>(&sm.wred[mg][mi][lane * 4]) = make_float4(acc[mi][0], acc[mi][1], acc[mi][2], acc[mi][3]);
            }
            asm volatile("bar.sync %0, 64;" ::"r"(1 + mg) : "memory");
            if (kh == 0) {
                uint2* dst = g_h1 + (size_t)h * (MEM_ * D_) + (2 * t) * D_ + c * 160 + mg * 80 + g;
#pragma unroll
                for (int mi = 0; mi < 5; mi++) {
                    float4 o2 = *reinterpret_cast<float4*>(&sm.wred[mg][mi][lane * 4]);
                    st_relaxed_v2(dst + mi * 16, __float_as_uint(acc[mi][0] + o2.x), flag);
                    st_relaxed_v2(dst + mi * 16 + D_, __float_as_uint(acc[mi][1] + o2.y), flag);
                    st_relaxed_v2(dst + mi * 16 + 8, __float_as_uint(acc[mi][2] + o2.z), flag);
                    st_relaxed_v2(dst + mi * 16 + D_ + 8, __float_as_uint(acc[mi][3] + o2.w), flag);
                }
            }
        }
        if (w < 10) {
            int e0 = blockIdx.x * 40 + w * 4;
            const uint2* src = g_h1 + (size_t)lane * (MEM_ * D_) + e0;
            if (w == 0) (void)poll_ll(src + 36, flag);
            asm volatile("bar.sync 3, 320;" ::: "memory");
            PROF(9);
            uint4 v0 = ld_relaxed_v4(src), v1 = ld_relaxed_v4(src + 2);
            if (v0.y != flag || v0.w != flag) v0 = poll_ll(src, flag);
            if (v1.y != flag || v1.w != flag) v1 = poll_ll(src + 2, flag);
            float x0 = __uint_as_float(v0.x), x1 = __uint_as_float(v0.z), x2 = __uint_as_float(v1.x), x3 = __uint_as_float(v1.z);
#pragma unroll
            for (int o = 1; o < 32; o <<= 1) {
                x0 += __shfl_xor_sync(0xffffffffu, x0, o); x1 += __shfl_xor_sync(0xffffffffu, x1, o);
                x2 += __shfl_xor_sync(0xffffffffu, x2, o); x3 += __shfl_xor_sync(0xffffffffu, x3, o);
            }
            if (lane == 0) {
                int r = e0 / D_, ch = (e0 - r * D_) >> 2;
                st_relaxed_v4(reinterpret_cast<uint4*>(g_h2) + r * 256 + ch, pack_bf16(x0, x1), flag, pack_bf16(x2, x3), flag);
            }
            PROF(10);
        }
    }
}

__global__ void __launch_bounds__(128)
attn_x_kernel() {
    __shared__ __align__(16) bf16 sq[32][HL], sk[48][HL], sv[48][HL];
    const int s = blockIdx.x >> 5, h = blockIdx.x & 31;
    const int tid = threadIdx.x, lane = tid & 31, w = tid >> 5, g = lane >> 2, t = lane & 3;
    for (int i = tid; i < (32 + 40 + 40) * 16; i += 128) {
        int r = i >> 4, ch = i & 15;
        const bf16* src; bf16* dst;
        if (r < 32) { src = g_qkv + (size_t)(s * SEG_ + r) * (3 * HD_) + h * DH_; dst = sq[r]; }
        else if (r < 72) { int rr = r - 32; dst = sk[rr];
            src = rr < 8 ? g_kmem + ((size_t)s * MEM_ + rr) * HD_ + h * DH_ : g_qkv + (size_t)(s * SEG_ + rr - 8) * (3 * HD_) + HD_ + h * DH_; }
        else { int rr = r - 72; dst = sv[rr];
            src = rr < 8 ? g_vmem + ((size_t)s * MEM_ + rr) * HD_ + h * DH_ : g_qkv + (size_t)(s * SEG_ + rr - 8) * (3 * HD_) + 2 * HD_ + h * DH_; }
        *reinterpret_cast<uint4*>(dst + ch * 8) = *reinterpret_cast<const uint4*>(src + ch * 8);
    }
    for (int i = tid; i < 8 * 16; i += 128) *reinterpret_cast<uint4*>(&sv[40 + (i >> 4)][(i & 15) * 8]) = make_uint4(0, 0, 0, 0);
    __syncthreads();
    const int rh = w & 1, dhh = w >> 1;
    float sc[5][4];
#pragma unroll
    for (int n = 0; n < 5; n++) sc[n][0] = sc[n][1] = sc[n][2] = sc[n][3] = 0.f;
#pragma unroll
    for (int kk = 0; kk < 8; kk++) {
        uint32_t a[4];
        ldsm_x4(a, smem_u32(&sq[rh * 16 + (lane & 15)][kk * 16 + (lane >> 4) * 8]));
#pragma unroll
        for (int n = 0; n < 5; n++) {
            uint32_t b[2];
            asm volatile("ldmatrix.sync.aligned.m8n8.x2.shared.b16 {%0,%1}, [%2];" : "=r"(b[0]), "=r"(b[1])
                         : "r"(smem_u32(&sk[n * 8 + (lane & 7)][kk * 16 + ((lane >> 3) & 1) * 8])));
            mma16816(sc[n], a, b[0], b[1]);
        }
    }
    const float scale = 0.08838834764831845f;
    float mx[2] = {-INFINITY, -INFINITY};
#pragma unroll
    for (int n = 0; n < 5; n++)
#pragma unroll
        for (int e = 0; e < 4; e++) {
            int row = rh * 16 + g + (e >> 1) * 8, key = n * 8 + 2 * t + (e & 1);
            float v = rbf(rbf(sc[n][e]) * scale);
            if (key > row + MEM_) v = -INFINITY;
            sc[n][e] = v;
            mx[e >> 1] = fmaxf(mx[e >> 1], v);
        }
#pragma unroll
    for (int o = 1; o < 4; o <<= 1) { mx[0] = fmaxf(mx[0], __shfl_xor_sync(0xffffffffu, mx[0], o)); mx[1] = fmaxf(mx[1], __shfl_xor_sync(0xffffffffu, mx[1], o)); }
    float sum[2] = {0.f, 0.f};
#pragma unroll
    for (int n = 0; n < 5; n++)
#pragma unroll
        for (int e = 0; e < 4; e++) { float ev = __expf(sc[n][e] - mx[e >> 1]); sc[n][e] = ev; sum[e >> 1] += ev; }
#pragma unroll
    for (int o = 1; o < 4; o <<= 1) { sum[0] += __shfl_xor_sync(0xffffffffu, sum[0], o); sum[1] += __shfl_xor_sync(0xffffffffu, sum[1], o); }
    float inv[2] = {1.0f / sum[0], 1.0f / sum[1]};
    uint32_t pa[3][4];
#pragma unroll
    for (int kt = 0; kt < 3; kt++) {
        pa[kt][0] = pack_bf16(sc[2 * kt][0] * inv[0], sc[2 * kt][1] * inv[0]);
        pa[kt][1] = pack_bf16(sc[2 * kt][2] * inv[1], sc[2 * kt][3] * inv[1]);
        if (kt < 2) {
            pa[kt][2] = pack_bf16(sc[2 * kt + 1][0] * inv[0], sc[2 * kt + 1][1] * inv[0]);
            pa[kt][3] = pack_bf16(sc[2 * kt + 1][2] * inv[1], sc[2 * kt + 1][3] * inv[1]);
        } else { pa[kt][2] = 0u; pa[kt][3] = 0u; }
    }
#pragma unroll
    for (int n = 0; n < 8; n++) {
        float o[4] = {0.f, 0.f, 0.f, 0.f};
#pragma unroll
        for (int kt = 0; kt < 3; kt++) {
            uint32_t b[2];
            asm volatile("ldmatrix.sync.aligned.m8n8.x2.trans.shared.b16 {%0,%1}, [%2];" : "=r"(b[0]), "=r"(b[1])
                         : "r"(smem_u32(&sv[kt * 16 + (lane & 15)][dhh * 64 + n * 8])));
            mma16816(o, pa[kt], b[0], b[1]);
        }
        int row = s * SEG_ + rh * 16 + g;
        bf16* dst = g_o + (size_t)row * HD_ + h * DH_ + dhh * 64 + n * 8 + 2 * t;
        *reinterpret_cast<uint32_t*>(dst) = pack_bf16(o[0], o[1]);
        *reinterpret_cast<uint32_t*>(dst + 8 * HD_) = pack_bf16(o[2], o[3]);
    }
}

typedef CUresult (*PFN_encodeTiled)(CUtensorMap*, CUtensorMapDataType, cuuint32_t, void*, const cuuint64_t*,
                                    const cuuint64_t*, const cuuint32_t*, const cuuint32_t*, CUtensorMapInterleave,
                                    CUtensorMapSwizzle, CUtensorMapL2promotion, CUtensorMapFloatOOBfill);
static PFN_encodeTiled p_encode = nullptr;

static CUtensorMap make_map(const void* ptr, uint64_t rows, uint64_t cols, uint64_t ld, uint32_t box_rows) {
    CUtensorMap m;
    cuuint64_t dims[2] = {cols, rows};
    cuuint64_t strides[1] = {ld * 2};
    cuuint32_t box[2] = {64, box_rows};
    cuuint32_t es[2] = {1, 1};
    p_encode(&m, CU_TENSOR_MAP_DATA_TYPE_BFLOAT16, 2, const_cast<void*>(ptr), dims, strides, box, es,
             CU_TENSOR_MAP_INTERLEAVE_NONE, CU_TENSOR_MAP_SWIZZLE_128B, CU_TENSOR_MAP_L2_PROMOTION_L2_128B,
             CU_TENSOR_MAP_FLOAT_OOB_FILL_NONE);
    return m;
}

template <int BN, int EPI>
static void launch_gemm(const CUtensorMap& a, const CUtensorMap& b, int M, int N, int K, EpiParams ep, cudaStream_t st) {
    constexpr int STAGE = 16384 + (BN / 64) * 8192;
    constexpr int NST = (200 * 1024) / STAGE;
    constexpr int SMEM = NST * STAGE + 1024;
    cudaFuncSetAttribute(gemm_kernel<BN, EPI>, cudaFuncAttributeMaxDynamicSharedMemorySize, SMEM);
    dim3 grid((N + BN - 1) / BN, M / 128);
    gemm_kernel<BN, EPI><<<grid, 384, SMEM, st>>>(a, b, M, N, K, ep);
}

extern "C" void kernel_launch(void* const* d_in, const int* in_sizes, int n_in, void* d_out, int out_size) {
    const bf16* x    = (const bf16*)d_in[0];
    const bf16* mem0 = (const bf16*)d_in[1];
    const bf16* Wq   = (const bf16*)d_in[2];
    const bf16* Wk   = (const bf16*)d_in[3];
    const bf16* Wv   = (const bf16*)d_in[4];
    const bf16* Wo   = (const bf16*)d_in[5];
    const bf16* w_in  = (const bf16*)d_in[8];
    const bf16* w_sp  = (const bf16*)d_in[9];
    const bf16* b_sp  = (const bf16*)d_in[10];
    const bf16* w_out = (const bf16*)d_in[11];
    bf16* out = (bf16*)d_out;
    cudaStream_t st = cudaStreamPerThread;

    if (!p_encode) {
        cudaDriverEntryPointQueryResult qr;
        cudaGetDriverEntryPoint("cuTensorMapEncodeTiled", (void**)&p_encode, cudaEnableDefault, &qr);
    }
    void *p_xn, *p_qkv, *p_z, *p_zg, *p_gate, *p_o, *p_h1, *p_h2, *p_hx;
    cudaGetSymbolAddress(&p_xn, g_xn); cudaGetSymbolAddress(&p_qkv, g_qkv); cudaGetSymbolAddress(&p_z, g_z);
    cudaGetSymbolAddress(&p_zg, g_zg); cudaGetSymbolAddress(&p_gate, g_gate); cudaGetSymbolAddress(&p_o, g_o);
    cudaGetSymbolAddress(&p_h1, g_h1); cudaGetSymbolAddress(&p_h2, g_h2); cudaGetSymbolAddress(&p_hx, g_hx);

    CUtensorMap mA_xn  = make_map(p_xn, S_, D_, D_, 128);
    CUtensorMap mA_wsp = make_map(w_sp, S_, S_, S_, 128);
    CUtensorMap mA_zg  = make_map(p_zg, S_, FH_, FH_, 128);
    CUtensorMap mA_o   = make_map(p_o, S_, HD_, HD_, 128);
    CUtensorMap mB_wq  = make_map(Wq, D_, HD_, HD_, 64);
    CUtensorMap mB_wk  = make_map(Wk, D_, HD_, HD_, 64);
    CUtensorMap mB_wv  = make_map(Wv, D_, HD_, HD_, 64);
    CUtensorMap mB_win = make_map(w_in, D_, F_, F_, 64);
    CUtensorMap mB_z2  = make_map((bf16*)p_z + FH_, S_, FH_, F_, 64);
    CUtensorMap mB_wout = make_map(w_out, FH_, D_, D_, 64);
    CUtensorMap mB_wo  = make_map(Wo, HD_, D_, D_, 64);

    cudaMemsetAsync(p_h1, 0, sizeof(uint2) * H_ * MEM_ * D_, st);
    cudaMemsetAsync(p_h2, 0, sizeof(uint2) * MEM_ * 256 * 2, st);
    cudaMemsetAsync(p_hx, 0, sizeof(uint2) * H_ * 4 * 256 * 2, st);

    ln_kernel<<<S_ / 8, 256, 0, st>>>(x);
    for (int i = 0; i < 3; i++) {
        EpiParams ep{(bf16*)p_qkv + i * HD_, 3 * HD_, nullptr, nullptr};
        launch_gemm<128, EPI_STORE>(mA_xn, i == 0 ? mB_wq : (i == 1 ? mB_wk : mB_wv), S_, HD_, D_, ep, st);
    }
    { EpiParams ep{(bf16*)p_z, F_, nullptr, nullptr}; launch_gemm<192, EPI_GELU>(mA_xn, mB_win, S_, F_, D_, ep, st); }
    ln2_kernel<<<S_ / 8, 256, 0, st>>>();
    { EpiParams ep{(bf16*)p_zg, FH_, (const bf16*)p_z, b_sp}; launch_gemm<128, EPI_SP>(mA_wsp, mB_z2, S_, FH_, S_, ep, st); }
    { EpiParams ep{(bf16*)p_gate, D_, nullptr, nullptr}; launch_gemm<128, EPI_SILU>(mA_zg, mB_wout, S_, D_, FH_, ep, st); }
    cudaFuncSetAttribute(recur_kernel, cudaFuncAttributeMaxDynamicSharedMemorySize, (int)sizeof(RecurSmem));
    recur_kernel<<<128, RT, sizeof(RecurSmem), st>>>(mem0, Wq, Wk, Wv, Wo);
    attn_x_kernel<<<NSEG_ * H_, 128, 0, st>>>();
    { EpiParams ep{out, D_, x, (const bf16*)p_gate}; launch_gemm<128, EPI_FINAL>(mA_o, mB_wo, S_, D_, HD_, ep, st); }
}
```

```cpp
#include <cuda_runtime.h>
#include <cuda_bf16.h>
#include <cuda.h>
#include <stdint.h>

typedef __nv_bfloat16 bf16;

constexpr int S_   = 2048;
constexpr int D_   = 640;
constexpr int H_   = 32;
constexpr int DH_  = 128;
constexpr int MEM_ = 8;
constexpr int SEG_ = 32;
constexpr int NSEG_ = S_ / SEG_;
constexpr int HD_  = H_ * DH_;
constexpr int F_   = 1728;
constexpr int FH_  = 864;

__device__ bf16 g_xn[S_ * D_];
__device__ bf16 g_qkv[(size_t)S_ * 3 * HD_];
__device__ bf16 g_z[S_ * F_];
__device__ bf16 g_zg[S_ * FH_];
__device__ bf16 g_gate[S_ * D_];
__device__ bf16 g_kmem[NSEG_ * MEM_ * HD_];
__device__ bf16 g_vmem[NSEG_ * MEM_ * HD_];
__device__ bf16 g_o[(size_t)S_ * HD_];
__device__ uint2 g_h1[H_ * MEM_ * D_];
__device__ uint2 g_h2[MEM_ * 256 * 2];
__device__ uint2 g_hx[H_ * 4 * 256 * 2];

__device__ __forceinline__ uint32_t smem_u32(const void* p) { return (uint32_t)__cvta_generic_to_shared(p); }
__device__ __forceinline__ float bf2f(bf16 v) { return __bfloat162float(v); }
__device__ __forceinline__ float rbf(float v) { return __bfloat162float(__float2bfloat16_rn(v)); }
__device__ __forceinline__ uint32_t pack_bf16(float lo, float hi) {
    __nv_bfloat162 t = __floats2bfloat162_rn(lo, hi);
    return *reinterpret_cast<uint32_t*>(&t);
}
__device__ __forceinline__ float lo_f(uint32_t u) { return __uint_as_float(u << 16); }
__device__ __forceinline__ float hi_f(uint32_t u) { return __uint_as_float(u & 0xffff0000u); }

__device__ __forceinline__ void mbar_init(uint32_t bar, uint32_t cnt) {
    asm volatile("mbarrier.init.shared.b64 [%0], %1;" ::"r"(bar), "r"(cnt));
}
__device__ __forceinline__ void mbar_expect_tx(uint32_t bar, uint32_t bytes) {
    asm volatile("mbarrier.arrive.expect_tx.shared.b64 _, [%0], %1;" ::"r"(bar), "r"(bytes) : "memory");
}
__device__ __forceinline__ void mbar_arrive(uint32_t bar) {
    asm volatile("mbarrier.arrive.shared.b64 _, [%0];" ::"r"(bar) : "memory");
}
__device__ __forceinline__ void mbar_wait(uint32_t bar, uint32_t parity) {
    asm volatile(
        "{\n .reg .pred p;\n"
        "WAIT_%=:\n"
        " mbarrier.try_wait.parity.shared.b64 p, [%0], %1;\n"
        " @p bra DONE_%=;\n"
        " bra WAIT_%=;\n"
        "DONE_%=:\n}\n" ::"r"(bar), "r"(parity) : "memory");
}
__device__ __forceinline__ void tma_load_2d(uint32_t dst, const CUtensorMap* tm, uint32_t bar, int c0, int c1) {
    asm volatile(
        "cp.async.bulk.tensor.2d.shared::cluster.global.mbarrier::complete_tx::bytes [%0], [%1, {%3, %4}], [%2];"
        ::"r"(dst), "l"(tm), "r"(bar), "r"(c0), "r"(c1) : "memory");
}
__device__ __forceinline__ void wgmma_fence() { asm volatile("wgmma.fence.sync.aligned;" ::: "memory"); }
__device__ __forceinline__ void wgmma_commit() { asm volatile("wgmma.commit_group.sync.aligned;" ::: "memory"); }
template <int N> __device__ __forceinline__ void wgmma_wait() { asm volatile("wgmma.wait_group.sync.aligned %0;" ::"n"(N) : "memory"); }

__device__ __forceinline__ uint64_t make_desc(uint32_t addr, uint32_t lbo, uint32_t sbo) {
    return (uint64_t)((addr & 0x3FFFF) >> 4) | ((uint64_t)(lbo >> 4) << 16) | ((uint64_t)(sbo >> 4) << 32) | (1ull << 62);
}

template <int N> struct Wgmma;
template <> struct Wgmma<128> {
    static __device__ __forceinline__ void mma(float* d, uint64_t da, uint64_t db, int sd) {
        asm volatile(
            "{\n.reg .pred p;\nsetp.ne.b32 p, %66, 0;\n"
            "wgmma.mma_async.sync.aligned.m64n128k16.f32.bf16.bf16 "
            "{%0,%1,%2,%3,%4,%5,%6,%7,%8,%9,%10,%11,%12,%13,%14,%15,"
            "%16,%17,%18,%19,%20,%21,%22,%23,%24,%25,%26,%27,%28,%29,%30,%31,"
            "%32,%33,%34,%35,%36,%37,%38,%39,%40,%41,%42,%43,%44,%45,%46,%47,"
            "%48,%49,%50,%51,%52,%53,%54,%55,%56,%57,%58,%59,%60,%61,%62,%63},"
            "%64,%65,p,1,1,0,1;\n}\n"
            : "+f"(d[0]), "+f"(d[1]), "+f"(d[2]), "+f"(d[3]), "+f"(d[4]), "+f"(d[5]), "+f"(d[6]), "+f"(d[7]),
              "+f"(d[8]), "+f"(d[9]), "+f"(d[10]), "+f"(d[11]), "+f"(d[12]), "+f"(d[13]), "+f"(d[14]), "+f"(d[15]),
              "+f"(d[16]), "+f"(d[17]), "+f"(d[18]), "+f"(d[19]), "+f"(d[20]), "+f"(d[21]), "+f"(d[22]), "+f"(d[23]),
              "+f"(d[24]), "+f"(d[25]), "+f"(d[26]), "+f"(d[27]), "+f"(d[28]), "+f"(d[29]), "+f"(d[30]), "+f"(d[31]),
              "+f"(d[32]), "+f"(d[33]), "+f"(d[34]), "+f"(d[35]), "+f"(d[36]), "+f"(d[37]), "+f"(d[38]), "+f"(d[39]),
              "+f"(d[40]), "+f"(d[41]), "+f"(d[42]), "+f"(d[43]), "+f"(d[44]), "+f"(d[45]), "+f"(d[46]), "+f"(d[47]),
              "+f"(d[48]), "+f"(d[49]), "+f"(d[50]), "+f"(d[51]), "+f"(d[52]), "+f"(d[53]), "+f"(d[54]), "+f"(d[55]),
              "+f"(d[56]), "+f"(d[57]), "+f"(d[58]), "+f"(d[59]), "+f"(d[60]), "+f"(d[61]), "+f"(d[62]), "+f"(d[63])
            : "l"(da), "l"(db), "r"(sd));
    }
};
template <> struct Wgmma<192> {
    static __device__ __forceinline__ void mma(float* d, uint64_t da, uint64_t db, int sd) {
        asm volatile(
            "{\n.reg .pred p;\nsetp.ne.b32 p, %98, 0;\n"
            "wgmma.mma_async.sync.aligned.m64n192k16.f32.bf16.bf16 "
            "{%0,%1,%2,%3,%4,%5,%6,%7,%8,%9,%10,%11,%12,%13,%14,%15,"
            "%16,%17,%18,%19,%20,%21,%22,%23,%24,%25,%26,%27,%28,%29,%30,%31,"
            "%32,%33,%34,%35,%36,%37,%38,%39,%40,%41,%42,%43,%44,%45,%46,%47,"
            "%48,%49,%50,%51,%52,%53,%54,%55,%56,%57,%58,%59,%60,%61,%62,%63,"
            "%64,%65,%66,%67,%68,%69,%70,%71,%72,%73,%74,%75,%76,%77,%78,%79,"
            "%80,%81,%82,%83,%84,%85,%86,%87,%88,%89,%90,%91,%92,%93,%94,%95},"
            "%96,%97,p,1,1,0,1;\n}\n"
            : "+f"(d[0]), "+f"(d[1]), "+f"(d[2]), "+f"(d[3]), "+f"(d[4]), "+f"(d[5]), "+f"(d[6]), "+f"(d[7]),
              "+f"(d[8]), "+f"(d[9]), "+f"(d[10]), "+f"(d[11]), "+f"(d[12]), "+f"(d[13]), "+f"(d[14]), "+f"(d[15]),
              "+f"(d[16]), "+f"(d[17]), "+f"(d[18]), "+f"(d[19]), "+f"(d[20]), "+f"(d[21]), "+f"(d[22]), "+f"(d[23]),
              "+f"(d[24]), "+f"(d[25]), "+f"(d[26]), "+f"(d[27]), "+f"(d[28]), "+f"(d[29]), "+f"(d[30]), "+f"(d[31]),
              "+f"(d[32]), "+f"(d[33]), "+f"(d[34]), "+f"(d[35]), "+f"(d[36]), "+f"(d[37]), "+f"(d[38]), "+f"(d[39]),
              "+f"(d[40]), "+f"(d[41]), "+f"(d[42]), "+f"(d[43]), "+f"(d[44]), "+f"(d[45]), "+f"(d[46]), "+f"(d[47]),
              "+f"(d[48]), "+f"(d[49]), "+f"(d[50]), "+f"(d[51]), "+f"(d[52]), "+f"(d[53]), "+f"(d[54]), "+f"(d[55]),
              "+f"(d[56]), "+f"(d[57]), "+f"(d[58]), "+f"(d[59]), "+f"(d[60]), "+f"(d[61]), "+f"(d[62]), "+f"(d[63]),
              "+f"(d[64]), "+f"(d[65]), "+f"(d[66]), "+f"(d[67]), "+f"(d[68]), "+f"(d[69]), "+f"(d[70]), "+f"(d[71]),
              "+f"(d[72]), "+f"(d[73]), "+f"(d[74]), "+f"(d[75]), "+f"(d[76]), "+f"(d[77]), "+f"(d[78]), "+f"(d[79]),
              "+f"(d[80]), "+f"(d[81]), "+f"(d[82]), "+f"(d[83]), "+f"(d[84]), "+f"(d[85]), "+f"(d[86]), "+f"(d[87]),
              "+f"(d[88]), "+f"(d[89]), "+f"(d[90]), "+f"(d[91]), "+f"(d[92]), "+f"(d[93]), "+f"(d[94]), "+f"(d[95])
            : "l"(da), "l"(db), "r"(sd));
    }
};

template <int W>
__device__ __forceinline__ void ln_row(const bf16* __restrict__ src, bf16* __restrict__ dst, int lane) {
    constexpr int NP = W / 64;
    constexpr int REM = (W / 2) % 32;
    uint32_t v[NP + 1];
    const uint32_t* s32 = reinterpret_cast<const uint32_t*>(src);
    float sum = 0.f;
#pragma unroll
    for (int i = 0; i < NP; i++) { v[i] = s32[i * 32 + lane]; sum += lo_f(v[i]) + hi_f(v[i]); }
    if (REM) { v[NP] = (lane < REM) ? s32[NP * 32 + lane] : 0u; if (lane < REM) sum += lo_f(v[NP]) + hi_f(v[NP]); }
#pragma unroll
    for (int o = 16; o; o >>= 1) sum += __shfl_xor_sync(0xffffffffu, sum, o);
    float mean = sum * (1.0f / W);
    float vs = 0.f;
#pragma unroll
    for (int i = 0; i < NP; i++) { float a = lo_f(v[i]) - mean, b = hi_f(v[i]) - mean; vs += a * a + b * b; }
    if (REM && lane < REM) { float a = lo_f(v[NP]) - mean, b = hi_f(v[NP]) - mean; vs += a * a + b * b; }
#pragma unroll
    for (int o = 16; o; o >>= 1) vs += __shfl_xor_sync(0xffffffffu, vs, o);
    float var = rbf(vs * (1.0f / W));
    float mb = rbf(mean);
    float den = rbf(sqrtf(rbf(var + 1e-5f)));
    uint32_t* d32 = reinterpret_cast<uint32_t*>(dst);
#pragma unroll
    for (int i = 0; i < NP; i++) d32[i * 32 + lane] = pack_bf16(rbf(lo_f(v[i]) - mb) / den, rbf(hi_f(v[i]) - mb) / den);
    if (REM && lane < REM) d32[NP * 32 + lane] = pack_bf16(rbf(lo_f(v[NP]) - mb) / den, rbf(hi_f(v[NP]) - mb) / den);
}

__global__ void ln_kernel(const bf16* __restrict__ x) {
    int row = blockIdx.x * 8 + (threadIdx.x >> 5);
    ln_row<D_>(x + (size_t)row * D_, g_xn + (size_t)row * D_, threadIdx.x & 31);
}
__global__ void ln2_kernel() {
    int row = blockIdx.x * 8 + (threadIdx.x >> 5);
    bf16* p = g_z + (size_t)row * F_ + FH_;
    ln_row<FH_>(p, p, threadIdx.x & 31);
}

enum { EPI_STORE = 0, EPI_GELU = 1, EPI_SP = 2, EPI_SILU = 3, EPI_FINAL = 4 };
struct EpiParams {
    bf16* out; int ldo;
    const bf16* aux0;
    const bf16* aux1;
};

__device__ __forceinline__ float gelu_tanh_f(float x) {
    const float k0 = 0.7978845608028654f, k1 = 0.044715f;
    float inner = k0 * (x + k1 * x * x * x);
    return 0.5f * x * (1.0f + tanhf(inner));
}
__device__ __forceinline__ float silu_f(float x) { return x / (1.0f + expf(-x)); }

template <int BN, int EPI>
__global__ void __launch_bounds__(384, 1)
gemm_kernel(const __grid_constant__ CUtensorMap tmA, const __grid_constant__ CUtensorMap tmB,
            int M, int N, int K, EpiParams ep) {
    constexpr int BM = 128, BK = 64;
    constexpr int A_BYTES = BM * BK * 2;
    constexpr int B_BYTES = (BN / 64) * 8192;
    constexpr int STAGE = A_BYTES + B_BYTES;
    constexpr int NST = (200 * 1024) / STAGE;
    extern __shared__ __align__(1024) uint8_t smem_raw[];
    uint8_t* smem = (uint8_t*)(((uintptr_t)smem_raw + 1023) & ~(uintptr_t)1023);
    __shared__ __align__(8) uint64_t full_bar[NST], empty_bar[NST];

    const int tid = threadIdx.x, wg = tid >> 7;
    const int m0 = blockIdx.y * BM, n0 = blockIdx.x * BN;
    const int nk = (K + BK - 1) / BK;

    if (tid == 0) {
        for (int i = 0; i < NST; i++) { mbar_init(smem_u32(&full_bar[i]), 1); mbar_init(smem_u32(&empty_bar[i]), 2); }
        asm volatile("fence.mbarrier_init.release.cluster;" ::: "memory");
    }
    __syncthreads();

    if (wg == 0) {
        if (tid == 0) {
            for (int kt = 0; kt < nk; kt++) {
                int st = kt % NST; uint32_t ph = (kt / NST) & 1;
                mbar_wait(smem_u32(&empty_bar[st]), ph ^ 1);
                uint32_t fb = smem_u32(&full_bar[st]);
                mbar_expect_tx(fb, STAGE);
                uint32_t sa = smem_u32(smem + st * STAGE);
                tma_load_2d(sa, &tmA, fb, kt * BK, m0);
#pragma unroll
                for (int j = 0; j < BN / 64; j++) tma_load_2d(sa + A_BYTES + j * 8192, &tmB, fb, n0 + j * 64, kt * BK);
            }
        }
    } else {
        const int cw = wg - 1;
        float acc[BN / 2];
#pragma unroll
        for (int i = 0; i < BN / 2; i++) acc[i] = 0.f;
        for (int kt = 0; kt < nk; kt++) {
            int st = kt % NST; uint32_t ph = (kt / NST) & 1;
            mbar_wait(smem_u32(&full_bar[st]), ph);
            uint32_t sa = smem_u32(smem + st * STAGE) + cw * 64 * 128;
            uint32_t sb = smem_u32(smem + st * STAGE) + A_BYTES;
            wgmma_fence();
#pragma unroll
            for (int k = 0; k < BK / 16; k++) {
                uint64_t da = make_desc(sa + k * 32, 16, 1024);
                uint64_t db = make_desc(sb + k * 2048, 8192, 1024);
                Wgmma<BN>::mma(acc, da, db, 1);
            }
            wgmma_commit();
            wgmma_wait<0>();
            if ((tid & 127) == 0) mbar_arrive(smem_u32(&empty_bar[st]));
        }
        const int lane = tid & 31, wi = (tid >> 5) & 3, g = lane >> 2, t = lane & 3;
        const int r0 = m0 + cw * 64 + wi * 16 + g;
#pragma unroll
        for (int j = 0; j < BN / 8; j++) {
            int col = n0 + j * 8 + 2 * t;
            if (col >= N) continue;
#pragma unroll
            for (int hh = 0; hh < 2; hh++) {
                int row = r0 + hh * 8;
                float v0 = rbf(acc[4 * j + 2 * hh]), v1 = rbf(acc[4 * j + 2 * hh + 1]);
                uint32_t o;
                if (EPI == EPI_STORE) {
                    o = pack_bf16(v0, v1);
                } else if (EPI == EPI_GELU) {
                    o = pack_bf16(gelu_tanh_f(v0), gelu_tanh_f(v1));
                } else if (EPI == EPI_SP) {
                    float b = bf2f(ep.aux1[row]);
                    float g0 = rbf(v0 + b), g1 = rbf(v1 + b);
                    uint32_t z1 = *reinterpret_cast<const uint32_t*>(ep.aux0 + (size_t)row * F_ + col);
                    o = pack_bf16(lo_f(z1) * g0, hi_f(z1) * g1);
                } else if (EPI == EPI_SILU) {
                    o = pack_bf16(silu_f(v0), silu_f(v1));
                } else {
                    uint32_t xg = *reinterpret_cast<const uint32_t*>(ep.aux0 + (size_t)row * D_ + col);
                    uint32_t gt = *reinterpret_cast<const uint32_t*>(ep.aux1 + (size_t)row * D_ + col);
                    o = pack_bf16(lo_f(xg) + rbf(v0 * lo_f(gt)), hi_f(xg) + rbf(v1 * hi_f(gt)));
                }
                *reinterpret_cast<uint32_t*>(ep.out + (size_t)row * ep.ldo + col) = o;
            }
        }
    }
}

__device__ __forceinline__ void mma16816(float* c, const uint32_t* a, uint32_t b0, uint32_t b1) {
    asm volatile(
        "mma.sync.aligned.m16n8k16.row.col.f32.bf16.bf16.f32 {%0,%1,%2,%3}, {%4,%5,%6,%7}, {%8,%9}, {%0,%1,%2,%3};"
        : "+f"(c[0]), "+f"(c[1]), "+f"(c[2]), "+f"(c[3])
        : "r"(a[0]), "r"(a[1]), "r"(a[2]), "r"(a[3]), "r"(b0), "r"(b1));
}
__device__ __forceinline__ void ldsm_x4(uint32_t* r, uint32_t addr) {
    asm volatile("ldmatrix.sync.aligned.m8n8.x4.shared.b16 {%0,%1,%2,%3}, [%4];"
                 : "=r"(r[0]), "=r"(r[1]), "=r"(r[2]), "=r"(r[3]) : "r"(addr));
}
__device__ __forceinline__ void ldsm_x4_t(uint32_t* r, uint32_t addr) {
    asm volatile("ldmatrix.sync.aligned.m8n8.x4.trans.shared.b16 {%0,%1,%2,%3}, [%4];"
                 : "=r"(r[0]), "=r"(r[1]), "=r"(r[2]), "=r"(r[3]) : "r"(addr));
}
__device__ __forceinline__ uint4 ld_relaxed_v4(const void* p) {
    uint4 v;
    asm volatile("ld.relaxed.gpu.global.v4.u32 {%0,%1,%2,%3}, [%4];" : "=r"(v.x), "=r"(v.y), "=r"(v.z), "=r"(v.w) : "l"(p) : "memory");
    return v;
}
__device__ __forceinline__ void st_relaxed_v4(void* p, uint32_t a, uint32_t b, uint32_t c, uint32_t d) {
    asm volatile("st.relaxed.gpu.global.v4.u32 [%0], {%1,%2,%3,%4};" ::"l"(p), "r"(a), "r"(b), "r"(c), "r"(d) : "memory");
}
__device__ __forceinline__ void st_relaxed_v2(void* p, uint32_t a, uint32_t b) {
    asm volatile("st.relaxed.gpu.global.v2.u32 [%0], {%1,%2};" ::"l"(p), "r"(a), "r"(b) : "memory");
}
__device__ __forceinline__ void cp_async16(uint32_t dst, const void* src) {
    asm volatile("cp.async.cg.shared.global [%0], [%1], 16;" ::"r"(dst), "l"(src) : "memory");
}
__device__ __forceinline__ void cp_async_commit() { asm volatile("cp.async.commit_group;" ::: "memory"); }
template <int N> __device__ __forceinline__ void cp_async_wait() { asm volatile("cp.async.wait_group %0;" ::"n"(N) : "memory"); }

#define PROF(i) do {} while (0)
constexpr int SPIN_LIMIT = 4000000;

__device__ __forceinline__ uint4 poll_ll(const void* p, uint32_t flag) {
    uint4 v = ld_relaxed_v4(p);
    int n = 0;
    while ((v.y != flag || v.w != flag) && ++n < SPIN_LIMIT) v = ld_relaxed_v4(p);
    return v;
}

constexpr int RT = 512;
constexpr int MEMS_LD = D_ + 8;
constexpr int HL = DH_ + 8;
struct RecurSmem {
    bf16 mem[MEM_][MEMS_LD];
    bf16 kall[2][48][HL];
    bf16 vall[2][48][HL];
    bf16 qm[16][HL];
    float sc[MEM_][40];
    bf16 p[MEM_][48 + 8];
    bf16 om[MEM_][HL];
    float red[12][16 * 8];
    float wred[2][5][16 * 8];
};

__device__ __forceinline__ void bar_sync(int id, int n) { asm volatile("bar.sync %0, %1;" ::"r"(id), "r"(n) : "memory"); }
__device__ __forceinline__ void bar_arrive(int id, int n) { asm volatile("bar.arrive %0, %1;" ::"r"(id), "r"(n) : "memory"); }
__device__ __forceinline__ void sts64(uint32_t a, uint32_t x, uint32_t y) { asm volatile("st.shared.v2.u32 [%0], {%1,%2};" ::"r"(a), "r"(x), "r"(y) : "memory"); }
__device__ __forceinline__ uint32_t ldg_u16x2(const bf16* p0, const bf16* p1) {
    return (uint32_t)*(const uint16_t*)p0 | ((uint32_t)*(const uint16_t*)p1 << 16);
}
enum { BAR_MEM = 1, BAR_RED = 2, BAR_CTL = 3, BAR_WO = 4 };

__global__ void __launch_bounds__(RT, 1)
recur_kernel(const bf16* __restrict__ mem0, const bf16* __restrict__ Wq, const bf16* __restrict__ Wk,
             const bf16* __restrict__ Wv, const bf16* __restrict__ Wo) {
    extern __shared__ __align__(16) uint8_t smem_raw[];
    RecurSmem& sm = *reinterpret_cast<RecurSmem*>(smem_raw);
    const int tid = threadIdx.x, lane = tid & 31, w = tid >> 5;
    const int g = lane >> 2, t = lane & 3;
    const int h = blockIdx.x >> 2, c = blockIdx.x & 3;

    for (int i = tid; i < 2 * 8 * HL; i += RT) {
        int b = i / (8 * HL), r = (i / HL) % 8, cc = i % HL;
        sm.kall[b][40 + r][cc] = __float2bfloat16(0.f);
        sm.vall[b][40 + r][cc] = __float2bfloat16(0.f);
    }
    for (int i = tid; i < 8 * HL; i += RT) sm.qm[8 + i / HL][i % HL] = __float2bfloat16(0.f);
    for (int i = tid; i < 8 * 56; i += RT) sm.p[i / 56][i % 56] = __float2bfloat16(0.f);
    __syncthreads();

    if (w < 12) {
        asm volatile("setmaxnreg.dec.sync.aligned.u32 104;");
        uint32_t wf[20][4];
        const int mt = w % 6, kh = w / 6;
        {
            const bf16* W = (mt < 2) ? Wq : (mt < 4 ? Wk : Wv);
            int f0 = h * DH_ + c * 32 + (mt & 1) * 16;
#pragma unroll
            for (int i = 0; i < 20; i++) {
                int k0 = (kh * 20 + i) * 16;
                const bf16* p0 = W + (size_t)(k0 + 2 * t) * HD_ + f0 + g;
                wf[i][0] = ldg_u16x2(p0, p0 + HD_);
                wf[i][1] = ldg_u16x2(p0 + 8, p0 + HD_ + 8);
                wf[i][2] = ldg_u16x2(p0 + 8 * HD_, p0 + 9 * HD_);
                wf[i][3] = ldg_u16x2(p0 + 8 * HD_ + 8, p0 + 9 * HD_ + 8);
            }
        }
        const uint32_t base = smem_u32(&sm.mem[lane & 7][kh * 320 + (lane >> 3) * 8]);
        const uint32_t rp = smem_u32(&sm.red[w][g * 8 + 2 * t]);
        for (int s = 0; s < NSEG_; s++) {
            bar_sync(BAR_MEM, RT);
            float a0[4] = {0.f, 0.f, 0.f, 0.f}, a1[4] = {0.f, 0.f, 0.f, 0.f};
#pragma unroll
            for (int i = 0; i < 10; i++) {
                uint32_t b[4];
                ldsm_x4(b, base + i * 64);
                mma16816(a0, wf[2 * i], b[0], b[1]);
                mma16816(a1, wf[2 * i + 1], b[2], b[3]);
            }
            sts64(rp, __float_as_uint(a0[0] + a1[0]), __float_as_uint(a0[1] + a1[1]));
            sts64(rp + 256, __float_as_uint(a0[2] + a1[2]), __float_as_uint(a0[3] + a1[3]));
            bar_arrive(BAR_RED, RT);
        }
    } else {
        asm volatile("setmaxnreg.inc.sync.aligned.u32 200;");
        const int ct = tid - 384, cw = w - 12;
        const int mg = cw >> 1, kh = cw & 1;
        uint32_t wf[20][4];
#pragma unroll
        for (int mi = 0; mi < 5; mi++)
#pragma unroll
            for (int ki = 0; ki < 4; ki++) {
                int col0 = c * 160 + (mg * 5 + mi) * 16;
                int e0 = h * DH_ + (kh * 4 + ki) * 16;
                const bf16* p0 = Wo + (size_t)(e0 + 2 * t) * D_ + col0 + g;
                int i = mi * 4 + ki;
                wf[i][0] = ldg_u16x2(p0, p0 + D_);
                wf[i][1] = ldg_u16x2(p0 + 8, p0 + D_ + 8);
                wf[i][2] = ldg_u16x2(p0 + 8 * D_, p0 + 9 * D_);
                wf[i][3] = ldg_u16x2(p0 + 8 * D_ + 8, p0 + 9 * D_ + 8);
            }
        constexpr uint32_t KV_BUF = 48 * HL * 2;
        const bf16* kv_src = g_qkv + (size_t)(ct >> 4) * (3 * HD_) + HD_ + h * DH_ + (ct & 15) * 8;
        const uint32_t kv_dst0 = smem_u32(&sm.kall[0][MEM_ + (ct >> 4)][(ct & 15) * 8]);
        const uint32_t kv_dst1 = smem_u32(&sm.vall[0][MEM_ + (ct >> 4)][(ct & 15) * 8]);
        auto prefetch_kv = [&](int s, int buf) {
            const bf16* src = kv_src + (size_t)s * SEG_ * (3 * HD_);
#pragma unroll
            for (int j = 0; j < 4; j++) {
                cp_async16(kv_dst0 + buf * KV_BUF + j * (8 * HL * 2), src + (size_t)j * 8 * (3 * HD_));
                cp_async16(kv_dst1 + buf * KV_BUF + j * (8 * HL * 2), src + (size_t)j * 8 * (3 * HD_) + HD_);
            }
            cp_async_commit();
        };
        const uint4* h2_src = reinterpret_cast<const uint4*>(g_h2) + (ct >> 4) * 256 + (ct & 15);
        const uint32_t h2_dst = smem_u32(&sm.mem[ct >> 4][(ct & 15) * 4]);
        const uint4* h2_probe = reinterpret_cast<const uint4*>(g_h2) + (lane & 7) * 256 + (lane >> 3) * 40 + (blockIdx.x & 31);
        const uint4* hx_base = reinterpret_cast<const uint4*>(g_hx) + h * 1024;
        const int hx_rq = ct & 63, hx_half = ct >> 6;
        const uint4* hx_src = hx_base + hx_half * 64 + hx_rq;
        const uint32_t hx_col = (hx_rq & 7) * 8, hx_r = hx_rq >> 3;
        const uint32_t hx_dstA = (hx_half == 0 ? smem_u32(&sm.qm[hx_r][0]) : smem_u32(&sm.kall[0][hx_r][0])) + hx_col;
        const uint32_t hx_dstB = smem_u32(&sm.vall[0][hx_r][0]) + hx_col;
        const uint4* hx_probe = hx_base + (lane >> 3) * 256 + ((lane & 7) % 3) * 64 + (lane & 7) * 8 + 3;
        const int pb_r = ct >> 4, pb_pr = ct & 15;
        uint2* pb_dst = g_hx + (h * 1024 + c * 256 + pb_r * 8) * 2 + pb_pr;
        const float* pb_src = &sm.red[pb_pr >> 3][(pb_pr & 7) * 16 + pb_r];
        bf16* pb_k = g_kmem + (size_t)pb_r * HD_ + h * DH_ + c * 32 + pb_pr * 2;
        bf16* pb_v = g_vmem + (size_t)pb_r * HD_ + h * DH_ + c * 32 + pb_pr * 2;
        const uint32_t qa = smem_u32(&sm.qm[lane & 15][(lane >> 4) * 8]);
        const uint32_t kb0 = smem_u32(&sm.kall[0][cw * 8 + (lane & 7)][(lane >> 3) * 8]);
        const uint32_t va0 = smem_u32(&sm.vall[0][(lane & 7) + ((lane >> 4) & 1) * 8][cw * 32 + ((lane >> 3) & 1) * 8]);
        const uint32_t pbaddr = smem_u32(&sm.p[lane & 7][((lane >> 3) & 1) * 8]);
        const uint32_t ob = smem_u32(&sm.om[lane & 7][kh * 64 + (lane >> 3) * 8]);
        uint2* h1_dst = g_h1 + (size_t)h * (MEM_ * D_) + (2 * t) * D_ + c * 160 + mg * 80 + g;
        const int e0 = blockIdx.x * 40;
        const uint2* h1_src = g_h1 + (size_t)lane * (MEM_ * D_) + e0 + cw * 4;
        uint4* h2_out = reinterpret_cast<uint4*>(g_h2) + (e0 / D_) * 256 + ((e0 % D_) >> 2) + cw;

        prefetch_kv(0, 0);
        for (int s = 0; s < NSEG_; s++) {
            const int buf = s & 1;
            const uint32_t flag = s + 1;
            const uint32_t bo = buf * KV_BUF;
            PROF(0);
            if (s == 0) {
                for (int i = ct; i < MEM_ * D_ / 8; i += 128) {
                    int r = i / (D_ / 8), cc = (i % (D_ / 8)) * 8;
                    *reinterpret_cast<uint4*>(&sm.mem[r][cc]) = *reinterpret_cast<const uint4*>(mem0 + r * D_ + cc);
                }
            } else {
                if (cw == 0) (void)poll_ll(h2_probe, s);
                bar_sync(BAR_CTL, 128);
                PROF(1);
                uint4 v[10];
#pragma unroll
                for (int j = 0; j < 10; j++) v[j] = ld_relaxed_v4(h2_src + 16 * j);
#pragma unroll
                for (int j = 0; j < 10; j++) {
                    if (v[j].y != (uint32_t)s || v[j].w != (uint32_t)s) v[j] = poll_ll(h2_src + 16 * j, s);
                    sts64(h2_dst + j * 128, v[j].x, v[j].z);
                }
            }
            bar_arrive(BAR_MEM, RT);
            PROF(2);
            bar_sync(BAR_RED, RT);
            PROF(3);
            {
                uint32_t pk0 = pack_bf16(pb_src[0] + pb_src[768], pb_src[8] + pb_src[768 + 8]);
                uint32_t pk1 = pack_bf16(pb_src[256] + pb_src[1024], pb_src[256 + 8] + pb_src[1024 + 8]);
                uint32_t pk2 = pack_bf16(pb_src[512] + pb_src[1280], pb_src[512 + 8] + pb_src[1280 + 8]);
                st_relaxed_v2(pb_dst, pk0, flag);
                st_relaxed_v2(pb_dst + 128, pk1, flag);
                st_relaxed_v2(pb_dst + 256, pk2, flag);
                *reinterpret_cast<uint32_t*>(pb_k + (size_t)s * (MEM_ * HD_)) = pk1;
                *reinterpret_cast<uint32_t*>(pb_v + (size_t)s * (MEM_ * HD_)) = pk2;
            }
            if (s == NSEG_ - 1) break;
            PROF(4);
            if (cw == 0) (void)poll_ll(hx_probe, flag);
            bar_sync(BAR_CTL, 128);
            PROF(5);
            {
                uint4 v[8];
#pragma unroll
                for (int j = 0; j < 4; j++) v[j] = ld_relaxed_v4(hx_src + j * 256);
                if (hx_half == 0) {
#pragma unroll
                    for (int j = 0; j < 4; j++) v[4 + j] = ld_relaxed_v4(hx_src + j * 256 + 128);
                }
#pragma unroll
                for (int j = 0; j < 4; j++) {
                    if (v[j].y != flag || v[j].w != flag) v[j] = poll_ll(hx_src + j * 256, flag);
                    sts64(hx_dstA + j * 64 + (hx_half ? bo : 0), v[j].x, v[j].z);
                }
                if (hx_half == 0) {
#pragma unroll
                    for (int j = 0; j < 4; j++) {
                        if (v[4 + j].y != flag || v[4 + j].w != flag) v[4 + j] = poll_ll(hx_src + j * 256 + 128, flag);
                        sts64(hx_dstB + j * 64 + bo, v[4 + j].x, v[4 + j].z);
                    }
                }
            }
            cp_async_wait<0>();
            bar_sync(BAR_CTL, 128);
            PROF(6);
            {
                uint32_t a[8][4], b[4][4], b2[4][4];
#pragma unroll
                for (int kk = 0; kk < 4; kk++) ldsm_x4(b[kk], kb0 + bo + kk * 64);
                if (cw == 0) {
#pragma unroll
                    for (int kk = 0; kk < 4; kk++) ldsm_x4(b2[kk], kb0 + bo + 32 * HL * 2 + kk * 64);
                }
#pragma unroll
                for (int kk = 0; kk < 8; kk++) ldsm_x4(a[kk], qa + kk * 32);
                float s0[4] = {0.f, 0.f, 0.f, 0.f}, s1[4] = {0.f, 0.f, 0.f, 0.f};
#pragma unroll
                for (int kk = 0; kk < 4; kk++) { mma16816(s0, a[2 * kk], b[kk][0], b[kk][1]); mma16816(s1, a[2 * kk + 1], b[kk][2], b[kk][3]); }
                const float scale = 0.08838834764831845f;
                *reinterpret_cast<float2*>(&sm.sc[g][cw * 8 + 2 * t]) =
                    make_float2(rbf(rbf(s0[0] + s1[0]) * scale), rbf(rbf(s0[1] + s1[1]) * scale));
                if (cw == 0) {
                    float u0[4] = {0.f, 0.f, 0.f, 0.f}, u1[4] = {0.f, 0.f, 0.f, 0.f};
#pragma unroll
                    for (int kk = 0; kk < 4; kk++) { mma16816(u0, a[2 * kk], b2[kk][0], b2[kk][1]); mma16816(u1, a[2 * kk + 1], b2[kk][2], b2[kk][3]); }
                    *reinterpret_cast<float2*>(&sm.sc[g][32 + 2 * t]) =
                        make_float2(rbf(rbf(u0[0] + u1[0]) * scale), rbf(rbf(u0[1] + u1[1]) * scale));
                }
            }
            bar_sync(BAR_CTL, 128);
            {
                float v0 = sm.sc[cw][lane], v1 = (lane < 8) ? sm.sc[cw][32 + lane] : -INFINITY;
                float y0 = sm.sc[cw + 4][lane], y1 = (lane < 8) ? sm.sc[cw + 4][32 + lane] : -INFINITY;
                float mx = fmaxf(v0, v1), my = fmaxf(y0, y1);
#pragma unroll
                for (int o = 16; o; o >>= 1) { mx = fmaxf(mx, __shfl_xor_sync(0xffffffffu, mx, o)); my = fmaxf(my, __shfl_xor_sync(0xffffffffu, my, o)); }
                float e0 = __expf(v0 - mx), e1 = (lane < 8) ? __expf(v1 - mx) : 0.f;
                float f0 = __expf(y0 - my), f1 = (lane < 8) ? __expf(y1 - my) : 0.f;
                float sx = e0 + e1, sy = f0 + f1;
#pragma unroll
                for (int o = 16; o; o >>= 1) { sx += __shfl_xor_sync(0xffffffffu, sx, o); sy += __shfl_xor_sync(0xffffffffu, sy, o); }
                float ix = 1.0f / sx, iy = 1.0f / sy;
                sm.p[cw][lane] = __float2bfloat16_rn(e0 * ix);
                sm.p[cw + 4][lane] = __float2bfloat16_rn(f0 * iy);
                if (lane < 8) { sm.p[cw][32 + lane] = __float2bfloat16_rn(e1 * ix); sm.p[cw + 4][32 + lane] = __float2bfloat16_rn(f1 * iy); }
            }
            bar_sync(BAR_CTL, 128);
            PROF(7);
            {
                uint32_t a[2][3][4], b[3][2];
#pragma unroll
                for (int kt = 0; kt < 3; kt++) {
                    asm volatile("ldmatrix.sync.aligned.m8n8.x2.shared.b16 {%0,%1}, [%2];" : "=r"(b[kt][0]), "=r"(b[kt][1]) : "r"(pbaddr + kt * 32));
                    ldsm_x4_t(a[0][kt], va0 + bo + kt * 16 * HL * 2);
                    ldsm_x4_t(a[1][kt], va0 + bo + kt * 16 * HL * 2 + 32);
                }
#pragma unroll
                for (int m = 0; m < 2; m++) {
                    float o[4] = {0.f, 0.f, 0.f, 0.f};
#pragma unroll
                    for (int kt = 0; kt < 3; kt++) mma16816(o, a[m][kt], b[kt][0], b[kt][1]);
                    int d0 = cw * 32 + m * 16 + g;
                    sm.om[2 * t][d0] = __float2bfloat16_rn(o[0]);
                    sm.om[2 * t + 1][d0] = __float2bfloat16_rn(o[1]);
                    sm.om[2 * t][d0 + 8] = __float2bfloat16_rn(o[2]);
                    sm.om[2 * t + 1][d0 + 8] = __float2bfloat16_rn(o[3]);
                }
            }
            bar_sync(BAR_CTL, 128);
            PROF(8);
            {
                float acc[5][4];
#pragma unroll
                for (int mi = 0; mi < 5; mi++) { acc[mi][0] = acc[mi][1] = acc[mi][2] = acc[mi][3] = 0.f; }
                uint32_t b[2][4];
                ldsm_x4(b[0], ob); ldsm_x4(b[1], ob + 64);
#pragma unroll
                for (int ki = 0; ki < 4; ki++)
#pragma unroll
                    for (int mi = 0; mi < 5; mi++) mma16816(acc[mi], wf[mi * 4 + ki], b[ki >> 1][(ki & 1) * 2], b[ki >> 1][(ki & 1) * 2 + 1]);
                if (kh == 1) {
#pragma unroll
                    for (int mi = 0; mi < 5; mi++)
                        *reinterpret_cast<float4*>(&sm.wred[mg][mi][lane * 4]) = make_float4(acc[mi][0], acc[mi][1], acc[mi][2], acc[mi][3]);
                }
                bar_sync(BAR_WO + mg, 64);
                if (kh == 0) {
#pragma unroll
                    for (int mi = 0; mi < 5; mi++) {
                        float4 o2 = *reinterpret_cast<float4*>(&sm.wred[mg][mi][lane * 4]);
                        st_relaxed_v2(h1_dst + mi * 16, __float_as_uint(acc[mi][0] + o2.x), flag);
                        st_relaxed_v2(h1_dst + mi * 16 + D_, __float_as_uint(acc[mi][1] + o2.y), flag);
                        st_relaxed_v2(h1_dst + mi * 16 + 8, __float_as_uint(acc[mi][2] + o2.z), flag);
                        st_relaxed_v2(h1_dst + mi * 16 + D_ + 8, __float_as_uint(acc[mi][3] + o2.w), flag);
                    }
                }
            }
            prefetch_kv(s + 1, buf ^ 1);
            {
                if (cw == 0) (void)poll_ll(h1_src + 36, flag);
                bar_sync(BAR_CTL, 128);
                PROF(9);
                uint4 v[6];
#pragma unroll
                for (int j = 0; j < 2; j++) { v[2 * j] = ld_relaxed_v4(h1_src + 16 * j); v[2 * j + 1] = ld_relaxed_v4(h1_src + 16 * j + 2); }
                if (cw < 2) { v[4] = ld_relaxed_v4(h1_src + 32); v[5] = ld_relaxed_v4(h1_src + 34); }
#pragma unroll
                for (int j = 0; j < 3; j++) {
                    if (j == 2 && cw >= 2) break;
                    if (v[2 * j].y != flag || v[2 * j].w != flag) v[2 * j] = poll_ll(h1_src + 16 * j, flag);
                    if (v[2 * j + 1].y != flag || v[2 * j + 1].w != flag) v[2 * j + 1] = poll_ll(h1_src + 16 * j + 2, flag);
                    float x0 = __uint_as_float(v[2 * j].x), x1 = __uint_as_float(v[2 * j].z);
                    float x2 = __uint_as_float(v[2 * j + 1].x), x3 = __uint_as_float(v[2 * j + 1].z);
#pragma unroll
                    for (int o = 1; o < 32; o <<= 1) {
                        x0 += __shfl_xor_sync(0xffffffffu, x0, o); x1 += __shfl_xor_sync(0xffffffffu, x1, o);
                        x2 += __shfl_xor_sync(0xffffffffu, x2, o); x3 += __shfl_xor_sync(0xffffffffu, x3, o);
                    }
                    if (lane == 0) st_relaxed_v4(h2_out + 4 * j, pack_bf16(x0, x1), flag, pack_bf16(x2, x3), flag);
                }
                PROF(10);
            }
        }
    }
}

__global__ void __launch_bounds__(128)
attn_x_kernel() {
    __shared__ __align__(16) bf16 sq[32][HL], sk[48][HL], sv[48][HL];
    const int s = blockIdx.x >> 5, h = blockIdx.x & 31;
    const int tid = threadIdx.x, lane = tid & 31, w = tid >> 5, g = lane >> 2, t = lane & 3;
    for (int i = tid; i < (32 + 40 + 40) * 16; i += 128) {
        int r = i >> 4, ch = i & 15;
        const bf16* src; bf16* dst;
        if (r < 32) { src = g_qkv + (size_t)(s * SEG_ + r) * (3 * HD_) + h * DH_; dst = sq[r]; }
        else if (r < 72) { int rr = r - 32; dst = sk[rr];
            src = rr < 8 ? g_kmem + ((size_t)s * MEM_ + rr) * HD_ + h * DH_ : g_qkv + (size_t)(s * SEG_ + rr - 8) * (3 * HD_) + HD_ + h * DH_; }
        else { int rr = r - 72; dst = sv[rr];
            src = rr < 8 ? g_vmem + ((size_t)s * MEM_ + rr) * HD_ + h * DH_ : g_qkv + (size_t)(s * SEG_ + rr - 8) * (3 * HD_) + 2 * HD_ + h * DH_; }
        *reinterpret_cast<uint4*>(dst + ch * 8) = *reinterpret_cast<const uint4*>(src + ch * 8);
    }
    for (int i = tid; i < 8 * 16; i += 128) *reinterpret_cast<uint4*>(&sv[40 + (i >> 4)][(i & 15) * 8]) = make_uint4(0, 0, 0, 0);
    __syncthreads();
    const int rh = w & 1, dhh = w >> 1;
    float sc[5][4];
#pragma unroll
    for (int n = 0; n < 5; n++) sc[n][0] = sc[n][1] = sc[n][2] = sc[n][3] = 0.f;
#pragma unroll
    for (int kk = 0; kk < 8; kk++) {
        uint32_t a[4];
        ldsm_x4(a, smem_u32(&sq[rh * 16 + (lane & 15)][kk * 16 + (lane >> 4) * 8]));
#pragma unroll
        for (int n = 0; n < 5; n++) {
            uint32_t b[2];
            asm volatile("ldmatrix.sync.aligned.m8n8.x2.shared.b16 {%0,%1}, [%2];" : "=r"(b[0]), "=r"(b[1])
                         : "r"(smem_u32(&sk[n * 8 + (lane & 7)][kk * 16 + ((lane >> 3) & 1) * 8])));
            mma16816(sc[n], a, b[0], b[1]);
        }
    }
    const float scale = 0.08838834764831845f;
    float mx[2] = {-INFINITY, -INFINITY};
#pragma unroll
    for (int n = 0; n < 5; n++)
#pragma unroll
        for (int e = 0; e < 4; e++) {
            int row = rh * 16 + g + (e >> 1) * 8, key = n * 8 + 2 * t + (e & 1);
            float v = rbf(rbf(sc[n][e]) * scale);
            if (key > row + MEM_) v = -INFINITY;
            sc[n][e] = v;
            mx[e >> 1] = fmaxf(mx[e >> 1], v);
        }
#pragma unroll
    for (int o = 1; o < 4; o <<= 1) { mx[0] = fmaxf(mx[0], __shfl_xor_sync(0xffffffffu, mx[0], o)); mx[1] = fmaxf(mx[1], __shfl_xor_sync(0xffffffffu, mx[1], o)); }
    float sum[2] = {0.f, 0.f};
#pragma unroll
    for (int n = 0; n < 5; n++)
#pragma unroll
        for (int e = 0; e < 4; e++) { float ev = __expf(sc[n][e] - mx[e >> 1]); sc[n][e] = ev; sum[e >> 1] += ev; }
#pragma unroll
    for (int o = 1; o < 4; o <<= 1) { sum[0] += __shfl_xor_sync(0xffffffffu, sum[0], o); sum[1] += __shfl_xor_sync(0xffffffffu, sum[1], o); }
    float inv[2] = {1.0f / sum[0], 1.0f / sum[1]};
    uint32_t pa[3][4];
#pragma unroll
    for (int kt = 0; kt < 3; kt++) {
        pa[kt][0] = pack_bf16(sc[2 * kt][0] * inv[0], sc[2 * kt][1] * inv[0]);
        pa[kt][1] = pack_bf16(sc[2 * kt][2] * inv[1], sc[2 * kt][3] * inv[1]);
        if (kt < 2) {
            pa[kt][2] = pack_bf16(sc[2 * kt + 1][0] * inv[0], sc[2 * kt + 1][1] * inv[0]);
            pa[kt][3] = pack_bf16(sc[2 * kt + 1][2] * inv[1], sc[2 * kt + 1][3] * inv[1]);
        } else { pa[kt][2] = 0u; pa[kt][3] = 0u; }
    }
#pragma unroll
    for (int n = 0; n < 8; n++) {
        float o[4] = {0.f, 0.f, 0.f, 0.f};
#pragma unroll
        for (int kt = 0; kt < 3; kt++) {
            uint32_t b[2];
            asm volatile("ldmatrix.sync.aligned.m8n8.x2.trans.shared.b16 {%0,%1}, [%2];" : "=r"(b[0]), "=r"(b[1])
                         : "r"(smem_u32(&sv[kt * 16 + (lane & 15)][dhh * 64 + n * 8])));
            mma16816(o, pa[kt], b[0], b[1]);
        }
        int row = s * SEG_ + rh * 16 + g;
        bf16* dst = g_o + (size_t)row * HD_ + h * DH_ + dhh * 64 + n * 8 + 2 * t;
        *reinterpret_cast<uint32_t*>(dst) = pack_bf16(o[0], o[1]);
        *reinterpret_cast<uint32_t*>(dst + 8 * HD_) = pack_bf16(o[2], o[3]);
    }
}

typedef CUresult (*PFN_encodeTiled)(CUtensorMap*, CUtensorMapDataType, cuuint32_t, void*, const cuuint64_t*,
                                    const cuuint64_t*, const cuuint32_t*, const cuuint32_t*, CUtensorMapInterleave,
                                    CUtensorMapSwizzle, CUtensorMapL2promotion, CUtensorMapFloatOOBfill);
static PFN_encodeTiled p_encode = nullptr;

static CUtensorMap make_map(const void* ptr, uint64_t rows, uint64_t cols, uint64_t ld, uint32_t box_rows) {
    CUtensorMap m;
    cuuint64_t dims[2] = {cols, rows};
    cuuint64_t strides[1] = {ld * 2};
    cuuint32_t box[2] = {64, box_rows};
    cuuint32_t es[2] = {1, 1};
    p_encode(&m, CU_TENSOR_MAP_DATA_TYPE_BFLOAT16, 2, const_cast<void*>(ptr), dims, strides, box, es,
             CU_TENSOR_MAP_INTERLEAVE_NONE, CU_TENSOR_MAP_SWIZZLE_128B, CU_TENSOR_MAP_L2_PROMOTION_L2_128B,
             CU_TENSOR_MAP_FLOAT_OOB_FILL_NONE);
    return m;
}

template <int BN, int EPI>
static void launch_gemm(const CUtensorMap& a, const CUtensorMap& b, int M, int N, int K, EpiParams ep, cudaStream_t st) {
    constexpr int STAGE = 16384 + (BN / 64) * 8192;
    constexpr int NST = (200 * 1024) / STAGE;
    constexpr int SMEM = NST * STAGE + 1024;
    cudaFuncSetAttribute(gemm_kernel<BN, EPI>, cudaFuncAttributeMaxDynamicSharedMemorySize, SMEM);
    dim3 grid((N + BN - 1) / BN, M / 128);
    gemm_kernel<BN, EPI><<<grid, 384, SMEM, st>>>(a, b, M, N, K, ep);
}

extern "C" void kernel_launch(void* const* d_in, const int* in_sizes, int n_in, void* d_out, int out_size) {
    const bf16* x    = (const bf16*)d_in[0];
    const bf16* mem0 = (const bf16*)d_in[1];
    const bf16* Wq   = (const bf16*)d_in[2];
    const bf16* Wk   = (const bf16*)d_in[3];
    const bf16* Wv   = (const bf16*)d_in[4];
    const bf16* Wo   = (const bf16*)d_in[5];
    const bf16* w_in  = (const bf16*)d_in[8];
    const bf16* w_sp  = (const bf16*)d_in[9];
    const bf16* b_sp  = (const bf16*)d_in[10];
    const bf16* w_out = (const bf16*)d_in[11];
    bf16* out = (bf16*)d_out;
    cudaStream_t st = cudaStreamPerThread;

    if (!p_encode) {
        cudaDriverEntryPointQueryResult qr;
        cudaGetDriverEntryPoint("cuTensorMapEncodeTiled", (void**)&p_encode, cudaEnableDefault, &qr);
    }
    void *p_xn, *p_qkv, *p_z, *p_zg, *p_gate, *p_o, *p_h1, *p_h2, *p_hx;
    cudaGetSymbolAddress(&p_xn, g_xn); cudaGetSymbolAddress(&p_qkv, g_qkv); cudaGetSymbolAddress(&p_z, g_z);
    cudaGetSymbolAddress(&p_zg, g_zg); cudaGetSymbolAddress(&p_gate, g_gate); cudaGetSymbolAddress(&p_o, g_o);
    cudaGetSymbolAddress(&p_h1, g_h1); cudaGetSymbolAddress(&p_h2, g_h2); cudaGetSymbolAddress(&p_hx, g_hx);

    CUtensorMap mA_xn  = make_map(p_xn, S_, D_, D_, 128);
    CUtensorMap mA_wsp = make_map(w_sp, S_, S_, S_, 128);
    CUtensorMap mA_zg  = make_map(p_zg, S_, FH_, FH_, 128);
    CUtensorMap mA_o   = make_map(p_o, S_, HD_, HD_, 128);
    CUtensorMap mB_wq  = make_map(Wq, D_, HD_, HD_, 64);
    CUtensorMap mB_wk  = make_map(Wk, D_, HD_, HD_, 64);
    CUtensorMap mB_wv  = make_map(Wv, D_, HD_, HD_, 64);
    CUtensorMap mB_win = make_map(w_in, D_, F_, F_, 64);
    CUtensorMap mB_z2  = make_map((bf16*)p_z + FH_, S_, FH_, F_, 64);
    CUtensorMap mB_wout = make_map(w_out, FH_, D_, D_, 64);
    CUtensorMap mB_wo  = make_map(Wo, HD_, D_, D_, 64);

    cudaMemsetAsync(p_h1, 0, sizeof(uint2) * H_ * MEM_ * D_, st);
    cudaMemsetAsync(p_h2, 0, sizeof(uint2) * MEM_ * 256 * 2, st);
    cudaMemsetAsync(p_hx, 0, sizeof(uint2) * H_ * 4 * 256 * 2, st);

    ln_kernel<<<S_ / 8, 256, 0, st>>>(x);
    for (int i = 0; i < 3; i++) {
        EpiParams ep{(bf16*)p_qkv + i * HD_, 3 * HD_, nullptr, nullptr};
        launch_gemm<128, EPI_STORE>(mA_xn, i == 0 ? mB_wq : (i == 1 ? mB_wk : mB_wv), S_, HD_, D_, ep, st);
    }
    { EpiParams ep{(bf16*)p_z, F_, nullptr, nullptr}; launch_gemm<192, EPI_GELU>(mA_xn, mB_win, S_, F_, D_, ep, st); }
    ln2_kernel<<<S_ / 8, 256, 0, st>>>();
    { EpiParams ep{(bf16*)p_zg, FH_, (const bf16*)p_z, b_sp}; launch_gemm<128, EPI_SP>(mA_wsp, mB_z2, S_, FH_, S_, ep, st); }
    { EpiParams ep{(bf16*)p_gate, D_, nullptr, nullptr}; launch_gemm<128, EPI_SILU>(mA_zg, mB_wout, S_, D_, FH_, ep, st); }
    cudaFuncSetAttribute(recur_kernel, cudaFuncAttributeMaxDynamicSharedMemorySize, (int)sizeof(RecurSmem));
    recur_kernel<<<128, RT, sizeof(RecurSmem), st>>>(mem0, Wq, Wk, Wv, Wo);
    attn_x_kernel<<<NSEG_ * H_, 128, 0, st>>>();
    { EpiParams ep{out, D_, x, (const bf16*)p_gate}; launch_gemm<128, EPI_FINAL>(mA_o, mB_wo, S_, D_, HD_, ep, st); }
}
```

```cpp
#include <cuda_runtime.h>
#include <cuda_bf16.h>
#include <cuda.h>
#include <stdint.h>

typedef __nv_bfloat16 bf16;

constexpr int S_   = 2048;
constexpr int D_   = 640;
constexpr int H_   = 32;
constexpr int DH_  = 128;
constexpr int MEM_ = 8;
constexpr int SEG_ = 32;
constexpr int NSEG_ = S_ / SEG_;
constexpr int HD_  = H_ * DH_;
constexpr int F_   = 1728;
constexpr int FH_  = 864;

__device__ bf16 g_xn[S_ * D_];
__device__ bf16 g_qkv[(size_t)S_ * 3 * HD_];
__device__ bf16 g_z[S_ * F_];
__device__ bf16 g_zg[S_ * FH_];
__device__ bf16 g_gate[S_ * D_];
__device__ bf16 g_kmem[NSEG_ * MEM_ * HD_];
__device__ bf16 g_vmem[NSEG_ * MEM_ * HD_];
__device__ bf16 g_o[(size_t)S_ * HD_];
__device__ float g_acc[NSEG_ * MEM_ * D_];
__device__ unsigned g_cnt[NSEG_ * 32];
__device__ uint2 g_hx[H_ * 4 * 256 * 2];

__device__ __forceinline__ uint32_t smem_u32(const void* p) { return (uint32_t)__cvta_generic_to_shared(p); }
__device__ __forceinline__ float bf2f(bf16 v) { return __bfloat162float(v); }
__device__ __forceinline__ float rbf(float v) { return __bfloat162float(__float2bfloat16_rn(v)); }
__device__ __forceinline__ uint32_t pack_bf16(float lo, float hi) {
    __nv_bfloat162 t = __floats2bfloat162_rn(lo, hi);
    return *reinterpret_cast<uint32_t*>(&t);
}
__device__ __forceinline__ float lo_f(uint32_t u) { return __uint_as_float(u << 16); }
__device__ __forceinline__ float hi_f(uint32_t u) { return __uint_as_float(u & 0xffff0000u); }

__device__ __forceinline__ void mbar_init(uint32_t bar, uint32_t cnt) {
    asm volatile("mbarrier.init.shared.b64 [%0], %1;" ::"r"(bar), "r"(cnt));
}
__device__ __forceinline__ void mbar_expect_tx(uint32_t bar, uint32_t bytes) {
    asm volatile("mbarrier.arrive.expect_tx.shared.b64 _, [%0], %1;" ::"r"(bar), "r"(bytes) : "memory");
}
__device__ __forceinline__ void mbar_arrive(uint32_t bar) {
    asm volatile("mbarrier.arrive.shared.b64 _, [%0];" ::"r"(bar) : "memory");
}
__device__ __forceinline__ void mbar_wait(uint32_t bar, uint32_t parity) {
    asm volatile(
        "{\n .reg .pred p;\n"
        "WAIT_%=:\n"
        " mbarrier.try_wait.parity.shared.b64 p, [%0], %1;\n"
        " @p bra DONE_%=;\n"
        " bra WAIT_%=;\n"
        "DONE_%=:\n}\n" ::"r"(bar), "r"(parity) : "memory");
}
__device__ __forceinline__ void tma_load_2d(uint32_t dst, const CUtensorMap* tm, uint32_t bar, int c0, int c1) {
    asm volatile(
        "cp.async.bulk.tensor.2d.shared::cluster.global.mbarrier::complete_tx::bytes [%0], [%1, {%3, %4}], [%2];"
        ::"r"(dst), "l"(tm), "r"(bar), "r"(c0), "r"(c1) : "memory");
}
__device__ __forceinline__ void wgmma_fence() { asm volatile("wgmma.fence.sync.aligned;" ::: "memory"); }
__device__ __forceinline__ void wgmma_commit() { asm volatile("wgmma.commit_group.sync.aligned;" ::: "memory"); }
template <int N> __device__ __forceinline__ void wgmma_wait() { asm volatile("wgmma.wait_group.sync.aligned %0;" ::"n"(N) : "memory"); }

__device__ __forceinline__ uint64_t make_desc(uint32_t addr, uint32_t lbo, uint32_t sbo) {
    return (uint64_t)((addr & 0x3FFFF) >> 4) | ((uint64_t)(lbo >> 4) << 16) | ((uint64_t)(sbo >> 4) << 32) | (1ull << 62);
}

template <int N> struct Wgmma;
template <> struct Wgmma<128> {
    static __device__ __forceinline__ void mma(float* d, uint64_t da, uint64_t db, int sd) {
        asm volatile(
            "{\n.reg .pred p;\nsetp.ne.b32 p, %66, 0;\n"
            "wgmma.mma_async.sync.aligned.m64n128k16.f32.bf16.bf16 "
            "{%0,%1,%2,%3,%4,%5,%6,%7,%8,%9,%10,%11,%12,%13,%14,%15,"
            "%16,%17,%18,%19,%20,%21,%22,%23,%24,%25,%26,%27,%28,%29,%30,%31,"
            "%32,%33,%34,%35,%36,%37,%38,%39,%40,%41,%42,%43,%44,%45,%46,%47,"
            "%48,%49,%50,%51,%52,%53,%54,%55,%56,%57,%58,%59,%60,%61,%62,%63},"
            "%64,%65,p,1,1,0,1;\n}\n"
            : "+f"(d[0]), "+f"(d[1]), "+f"(d[2]), "+f"(d[3]), "+f"(d[4]), "+f"(d[5]), "+f"(d[6]), "+f"(d[7]),
              "+f"(d[8]), "+f"(d[9]), "+f"(d[10]), "+f"(d[11]), "+f"(d[12]), "+f"(d[13]), "+f"(d[14]), "+f"(d[15]),
              "+f"(d[16]), "+f"(d[17]), "+f"(d[18]), "+f"(d[19]), "+f"(d[20]), "+f"(d[21]), "+f"(d[22]), "+f"(d[23]),
              "+f"(d[24]), "+f"(d[25]), "+f"(d[26]), "+f"(d[27]), "+f"(d[28]), "+f"(d[29]), "+f"(d[30]), "+f"(d[31]),
              "+f"(d[32]), "+f"(d[33]), "+f"(d[34]), "+f"(d[35]), "+f"(d[36]), "+f"(d[37]), "+f"(d[38]), "+f"(d[39]),
              "+f"(d[40]), "+f"(d[41]), "+f"(d[42]), "+f"(d[43]), "+f"(d[44]), "+f"(d[45]), "+f"(d[46]), "+f"(d[47]),
              "+f"(d[48]), "+f"(d[49]), "+f"(d[50]), "+f"(d[51]), "+f"(d[52]), "+f"(d[53]), "+f"(d[54]), "+f"(d[55]),
              "+f"(d[56]), "+f"(d[57]), "+f"(d[58]), "+f"(d[59]), "+f"(d[60]), "+f"(d[61]), "+f"(d[62]), "+f"(d[63])
            : "l"(da), "l"(db), "r"(sd));
    }
};
template <> struct Wgmma<192> {
    static __device__ __forceinline__ void mma(float* d, uint64_t da, uint64_t db, int sd) {
        asm volatile(
            "{\n.reg .pred p;\nsetp.ne.b32 p, %98, 0;\n"
            "wgmma.mma_async.sync.aligned.m64n192k16.f32.bf16.bf16 "
            "{%0,%1,%2,%3,%4,%5,%6,%7,%8,%9,%10,%11,%12,%13,%14,%15,"
            "%16,%17,%18,%19,%20,%21,%22,%23,%24,%25,%26,%27,%28,%29,%30,%31,"
            "%32,%33,%34,%35,%36,%37,%38,%39,%40,%41,%42,%43,%44,%45,%46,%47,"
            "%48,%49,%50,%51,%52,%53,%54,%55,%56,%57,%58,%59,%60,%61,%62,%63,"
            "%64,%65,%66,%67,%68,%69,%70,%71,%72,%73,%74,%75,%76,%77,%78,%79,"
            "%80,%81,%82,%83,%84,%85,%86,%87,%88,%89,%90,%91,%92,%93,%94,%95},"
            "%96,%97,p,1,1,0,1;\n}\n"
            : "+f"(d[0]), "+f"(d[1]), "+f"(d[2]), "+f"(d[3]), "+f"(d[4]), "+f"(d[5]), "+f"(d[6]), "+f"(d[7]),
              "+f"(d[8]), "+f"(d[9]), "+f"(d[10]), "+f"(d[11]), "+f"(d[12]), "+f"(d[13]), "+f"(d[14]), "+f"(d[15]),
              "+f"(d[16]), "+f"(d[17]), "+f"(d[18]), "+f"(d[19]), "+f"(d[20]), "+f"(d[21]), "+f"(d[22]), "+f"(d[23]),
              "+f"(d[24]), "+f"(d[25]), "+f"(d[26]), "+f"(d[27]), "+f"(d[28]), "+f"(d[29]), "+f"(d[30]), "+f"(d[31]),
              "+f"(d[32]), "+f"(d[33]), "+f"(d[34]), "+f"(d[35]), "+f"(d[36]), "+f"(d[37]), "+f"(d[38]), "+f"(d[39]),
              "+f"(d[40]), "+f"(d[41]), "+f"(d[42]), "+f"(d[43]), "+f"(d[44]), "+f"(d[45]), "+f"(d[46]), "+f"(d[47]),
              "+f"(d[48]), "+f"(d[49]), "+f"(d[50]), "+f"(d[51]), "+f"(d[52]), "+f"(d[53]), "+f"(d[54]), "+f"(d[55]),
              "+f"(d[56]), "+f"(d[57]), "+f"(d[58]), "+f"(d[59]), "+f"(d[60]), "+f"(d[61]), "+f"(d[62]), "+f"(d[63]),
              "+f"(d[64]), "+f"(d[65]), "+f"(d[66]), "+f"(d[67]), "+f"(d[68]), "+f"(d[69]), "+f"(d[70]), "+f"(d[71]),
              "+f"(d[72]), "+f"(d[73]), "+f"(d[74]), "+f"(d[75]), "+f"(d[76]), "+f"(d[77]), "+f"(d[78]), "+f"(d[79]),
              "+f"(d[80]), "+f"(d[81]), "+f"(d[82]), "+f"(d[83]), "+f"(d[84]), "+f"(d[85]), "+f"(d[86]), "+f"(d[87]),
              "+f"(d[88]), "+f"(d[89]), "+f"(d[90]), "+f"(d[91]), "+f"(d[92]), "+f"(d[93]), "+f"(d[94]), "+f"(d[95])
            : "l"(da), "l"(db), "r"(sd));
    }
};

template <int W>
__device__ __forceinline__ void ln_row(const bf16* __restrict__ src, bf16* __restrict__ dst, int lane) {
    constexpr int NP = W / 64;
    constexpr int REM = (W / 2) % 32;
    uint32_t v[NP + 1];
    const uint32_t* s32 = reinterpret_cast<const uint32_t*>(src);
    float sum = 0.f;
#pragma unroll
    for (int i = 0; i < NP; i++) { v[i] = s32[i * 32 + lane]; sum += lo_f(v[i]) + hi_f(v[i]); }
    if (REM) { v[NP] = (lane < REM) ? s32[NP * 32 + lane] : 0u; if (lane < REM) sum += lo_f(v[NP]) + hi_f(v[NP]); }
#pragma unroll
    for (int o = 16; o; o >>= 1) sum += __shfl_xor_sync(0xffffffffu, sum, o);
    float mean = sum * (1.0f / W);
    float vs = 0.f;
#pragma unroll
    for (int i = 0; i < NP; i++) { float a = lo_f(v[i]) - mean, b = hi_f(v[i]) - mean; vs += a * a + b * b; }
    if (REM && lane < REM) { float a = lo_f(v[NP]) - mean, b = hi_f(v[NP]) - mean; vs += a * a + b * b; }
#pragma unroll
    for (int o = 16; o; o >>= 1) vs += __shfl_xor_sync(0xffffffffu, vs, o);
    float var = rbf(vs * (1.0f / W));
    float mb = rbf(mean);
    float den = rbf(sqrtf(rbf(var + 1e-5f)));
    uint32_t* d32 = reinterpret_cast<uint32_t*>(dst);
#pragma unroll
    for (int i = 0; i < NP; i++) d32[i * 32 + lane] = pack_bf16(rbf(lo_f(v[i]) - mb) / den, rbf(hi_f(v[i]) - mb) / den);
    if (REM && lane < REM) d32[NP * 32 + lane] = pack_bf16(rbf(lo_f(v[NP]) - mb) / den, rbf(hi_f(v[NP]) - mb) / den);
}

__global__ void ln_kernel(const bf16* __restrict__ x) {
    int row = blockIdx.x * 8 + (threadIdx.x >> 5);
    ln_row<D_>(x + (size_t)row * D_, g_xn + (size_t)row * D_, threadIdx.x & 31);
}
__global__ void ln2_kernel() {
    int row = blockIdx.x * 8 + (threadIdx.x >> 5);
    bf16* p = g_z + (size_t)row * F_ + FH_;
    ln_row<FH_>(p, p, threadIdx.x & 31);
}

enum { EPI_STORE = 0, EPI_GELU = 1, EPI_SP = 2, EPI_SILU = 3, EPI_FINAL = 4 };
struct EpiParams {
    bf16* out; int ldo;
    const bf16* aux0;
    const bf16* aux1;
};

__device__ __forceinline__ float gelu_tanh_f(float x) {
    const float k0 = 0.7978845608028654f, k1 = 0.044715f;
    float inner = k0 * (x + k1 * x * x * x);
    return 0.5f * x * (1.0f + tanhf(inner));
}
__device__ __forceinline__ float silu_f(float x) { return x / (1.0f + expf(-x)); }

template <int BN, int EPI>
__global__ void __launch_bounds__(384, 1)
gemm_kernel(const __grid_constant__ CUtensorMap tmA, const __grid_constant__ CUtensorMap tmB,
            int M, int N, int K, EpiParams ep) {
    constexpr int BM = 128, BK = 64;
    constexpr int A_BYTES = BM * BK * 2;
    constexpr int B_BYTES = (BN / 64) * 8192;
    constexpr int STAGE = A_BYTES + B_BYTES;
    constexpr int NST = (200 * 1024) / STAGE;
    extern __shared__ __align__(1024) uint8_t smem_raw[];
    uint8_t* smem = (uint8_t*)(((uintptr_t)smem_raw + 1023) & ~(uintptr_t)1023);
    __shared__ __align__(8) uint64_t full_bar[NST], empty_bar[NST];

    const int tid = threadIdx.x, wg = tid >> 7;
    const int m0 = blockIdx.y * BM, n0 = blockIdx.x * BN;
    const int nk = (K + BK - 1) / BK;

    if (tid == 0) {
        for (int i = 0; i < NST; i++) { mbar_init(smem_u32(&full_bar[i]), 1); mbar_init(smem_u32(&empty_bar[i]), 2); }
        asm volatile("fence.mbarrier_init.release.cluster;" ::: "memory");
    }
    __syncthreads();

    if (wg == 0) {
        if (tid == 0) {
            for (int kt = 0; kt < nk; kt++) {
                int st = kt % NST; uint32_t ph = (kt / NST) & 1;
                mbar_wait(smem_u32(&empty_bar[st]), ph ^ 1);
                uint32_t fb = smem_u32(&full_bar[st]);
                mbar_expect_tx(fb, STAGE);
                uint32_t sa = smem_u32(smem + st * STAGE);
                tma_load_2d(sa, &tmA, fb, kt * BK, m0);
#pragma unroll
                for (int j = 0; j < BN / 64; j++) tma_load_2d(sa + A_BYTES + j * 8192, &tmB, fb, n0 + j * 64, kt * BK);
            }
        }
    } else {
        const int cw = wg - 1;
        float acc[BN / 2];
#pragma unroll
        for (int i = 0; i < BN / 2; i++) acc[i] = 0.f;
        for (int kt = 0; kt < nk; kt++) {
            int st = kt % NST; uint32_t ph = (kt / NST) & 1;
            mbar_wait(smem_u32(&full_bar[st]), ph);
            uint32_t sa = smem_u32(smem + st * STAGE) + cw * 64 * 128;
            uint32_t sb = smem_u32(smem + st * STAGE) + A_BYTES;
            wgmma_fence();
#pragma unroll
            for (int k = 0; k < BK / 16; k++) {
                uint64_t da = make_desc(sa + k * 32, 16, 1024);
                uint64_t db = make_desc(sb + k * 2048, 8192, 1024);
                Wgmma<BN>::mma(acc, da, db, 1);
            }
            wgmma_commit();
            wgmma_wait<0>();
            if ((tid & 127) == 0) mbar_arrive(smem_u32(&empty_bar[st]));
        }
        const int lane = tid & 31, wi = (tid >> 5) & 3, g = lane >> 2, t = lane & 3;
        const int r0 = m0 + cw * 64 + wi * 16 + g;
#pragma unroll
        for (int j = 0; j < BN / 8; j++) {
            int col = n0 + j * 8 + 2 * t;
            if (col >= N) continue;
#pragma unroll
            for (int hh = 0; hh < 2; hh++) {
                int row = r0 + hh * 8;
                float v0 = rbf(acc[4 * j + 2 * hh]), v1 = rbf(acc[4 * j + 2 * hh + 1]);
                uint32_t o;
                if (EPI == EPI_STORE) {
                    o = pack_bf16(v0, v1);
                } else if (EPI == EPI_GELU) {
                    o = pack_bf16(gelu_tanh_f(v0), gelu_tanh_f(v1));
                } else if (EPI == EPI_SP) {
                    float b = bf2f(ep.aux1[row]);
                    float g0 = rbf(v0 + b), g1 = rbf(v1 + b);
                    uint32_t z1 = *reinterpret_cast<const uint32_t*>(ep.aux0 + (size_t)row * F_ + col);
                    o = pack_bf16(lo_f(z1) * g0, hi_f(z1) * g1);
                } else if (EPI == EPI_SILU) {
                    o = pack_bf16(silu_f(v0), silu_f(v1));
                } else {
                    uint32_t xg = *reinterpret_cast<const uint32_t*>(ep.aux0 + (size_t)row * D_ + col);
                    uint32_t gt = *reinterpret_cast<const uint32_t*>(ep.aux1 + (size_t)row * D_ + col);
                    o = pack_bf16(lo_f(xg) + rbf(v0 * lo_f(gt)), hi_f(xg) + rbf(v1 * hi_f(gt)));
                }
                *reinterpret_cast<uint32_t*>(ep.out + (size_t)row * ep.ldo + col) = o;
            }
        }
    }
}

__device__ __forceinline__ void mma16816(float* c, const uint32_t* a, uint32_t b0, uint32_t b1) {
    asm volatile(
        "mma.sync.aligned.m16n8k16.row.col.f32.bf16.bf16.f32 {%0,%1,%2,%3}, {%4,%5,%6,%7}, {%8,%9}, {%0,%1,%2,%3};"
        : "+f"(c[0]), "+f"(c[1]), "+f"(c[2]), "+f"(c[3])
        : "r"(a[0]), "r"(a[1]), "r"(a[2]), "r"(a[3]), "r"(b0), "r"(b1));
}
__device__ __forceinline__ void ldsm_x4(uint32_t* r, uint32_t addr) {
    asm volatile("ldmatrix.sync.aligned.m8n8.x4.shared.b16 {%0,%1,%2,%3}, [%4];"
                 : "=r"(r[0]), "=r"(r[1]), "=r"(r[2]), "=r"(r[3]) : "r"(addr));
}
__device__ __forceinline__ void ldsm_x4_t(uint32_t* r, uint32_t addr) {
    asm volatile("ldmatrix.sync.aligned.m8n8.x4.trans.shared.b16 {%0,%1,%2,%3}, [%4];"
                 : "=r"(r[0]), "=r"(r[1]), "=r"(r[2]), "=r"(r[3]) : "r"(addr));
}
__device__ __forceinline__ uint4 ld_relaxed_v4(const void* p) {
    uint4 v;
    asm volatile("ld.relaxed.gpu.global.v4.u32 {%0,%1,%2,%3}, [%4];" : "=r"(v.x), "=r"(v.y), "=r"(v.z), "=r"(v.w) : "l"(p) : "memory");
    return v;
}
__device__ __forceinline__ void st_relaxed_v4(void* p, uint32_t a, uint32_t b, uint32_t c, uint32_t d) {
    asm volatile("st.relaxed.gpu.global.v4.u32 [%0], {%1,%2,%3,%4};" ::"l"(p), "r"(a), "r"(b), "r"(c), "r"(d) : "memory");
}
__device__ __forceinline__ void st_relaxed_v2(void* p, uint32_t a, uint32_t b) {
    asm volatile("st.relaxed.gpu.global.v2.u32 [%0], {%1,%2};" ::"l"(p), "r"(a), "r"(b) : "memory");
}
__device__ __forceinline__ void cp_async16(uint32_t dst, const void* src) {
    asm volatile("cp.async.cg.shared.global [%0], [%1], 16;" ::"r"(dst), "l"(src) : "memory");
}
__device__ __forceinline__ void cp_async_commit() { asm volatile("cp.async.commit_group;" ::: "memory"); }
template <int N> __device__ __forceinline__ void cp_async_wait() { asm volatile("cp.async.wait_group %0;" ::"n"(N) : "memory"); }

#define PROF(i) do {} while (0)
constexpr int SPIN_LIMIT = 4000000;

__device__ __forceinline__ uint4 poll_ll(const void* p, uint32_t flag) {
    uint4 v = ld_relaxed_v4(p);
    int n = 0;
    while ((v.y != flag || v.w != flag) && ++n < SPIN_LIMIT) {
        v = ld_relaxed_v4(p);
    }
    return v;
}

constexpr int RT = 512;
constexpr int MEMS_LD = D_ + 8;
constexpr int HL = DH_ + 8;
struct RecurSmem {
    bf16 mem[MEM_][MEMS_LD];
    bf16 kall[2][48][HL];
    bf16 vall[2][48][HL];
    bf16 qm[16][HL];
    float sc[MEM_][40];
    bf16 p[MEM_][48 + 8];
    bf16 om[MEM_][HL];
    float red[12][16 * 8];
    float wred[2][5][16 * 8];
};

__device__ __forceinline__ void bar_sync(int id, int n) { asm volatile("bar.sync %0, %1;" ::"r"(id), "r"(n) : "memory"); }
__device__ __forceinline__ void bar_arrive(int id, int n) { asm volatile("bar.arrive %0, %1;" ::"r"(id), "r"(n) : "memory"); }
__device__ __forceinline__ void sts64(uint32_t a, uint32_t x, uint32_t y) { asm volatile("st.shared.v2.u32 [%0], {%1,%2};" ::"r"(a), "r"(x), "r"(y) : "memory"); }
__device__ __forceinline__ uint32_t ldg_u16x2(const bf16* p0, const bf16* p1) {
    return (uint32_t)*(const uint16_t*)p0 | ((uint32_t)*(const uint16_t*)p1 << 16);
}
enum { BAR_MEM = 1, BAR_RED = 2, BAR_CTL = 3, BAR_WO = 4 };

__global__ void __launch_bounds__(RT, 1)
recur_kernel(const bf16* __restrict__ mem0, const bf16* __restrict__ Wq, const bf16* __restrict__ Wk,
             const bf16* __restrict__ Wv, const bf16* __restrict__ Wo) {
    extern __shared__ __align__(16) uint8_t smem_raw[];
    RecurSmem& sm = *reinterpret_cast<RecurSmem*>(smem_raw);
    const int tid = threadIdx.x, lane = tid & 31, w = tid >> 5;
    const int g = lane >> 2, t = lane & 3;
    const int h = blockIdx.x >> 2, c = blockIdx.x & 3;

    for (int i = tid; i < 2 * 8 * HL; i += RT) {
        int b = i / (8 * HL), r = (i / HL) % 8, cc = i % HL;
        sm.kall[b][40 + r][cc] = __float2bfloat16(0.f);
        sm.vall[b][40 + r][cc] = __float2bfloat16(0.f);
    }
    for (int i = tid; i < 8 * HL; i += RT) sm.qm[8 + i / HL][i % HL] = __float2bfloat16(0.f);
    for (int i = tid; i < 8 * 56; i += RT) sm.p[i / 56][i % 56] = __float2bfloat16(0.f);
    __syncthreads();

    if (w < 12) {
        asm volatile("setmaxnreg.dec.sync.aligned.u32 104;");
        uint32_t wf[20][4];
        const int mt = w % 6, kh = w / 6;
        {
            const bf16* W = (mt < 2) ? Wq : (mt < 4 ? Wk : Wv);
            int f0 = h * DH_ + c * 32 + (mt & 1) * 16;
#pragma unroll
            for (int i = 0; i < 20; i++) {
                int k0 = (kh * 20 + i) * 16;
                const bf16* p0 = W + (size_t)(k0 + 2 * t) * HD_ + f0 + g;
                wf[i][0] = ldg_u16x2(p0, p0 + HD_);
                wf[i][1] = ldg_u16x2(p0 + 8, p0 + HD_ + 8);
                wf[i][2] = ldg_u16x2(p0 + 8 * HD_, p0 + 9 * HD_);
                wf[i][3] = ldg_u16x2(p0 + 8 * HD_ + 8, p0 + 9 * HD_ + 8);
            }
        }
        const uint32_t base = smem_u32(&sm.mem[lane & 7][kh * 320 + (lane >> 3) * 8]);
        const uint32_t rp = smem_u32(&sm.red[w][g * 8 + 2 * t]);
        for (int s = 0; s < NSEG_; s++) {
            bar_sync(BAR_MEM, RT);
            float a0[4] = {0.f, 0.f, 0.f, 0.f}, a1[4] = {0.f, 0.f, 0.f, 0.f};
#pragma unroll
            for (int i = 0; i < 10; i++) {
                uint32_t b[4];
                ldsm_x4(b, base + i * 64);
                mma16816(a0, wf[2 * i], b[0], b[1]);
                mma16816(a1, wf[2 * i + 1], b[2], b[3]);
            }
            sts64(rp, __float_as_uint(a0[0] + a1[0]), __float_as_uint(a0[1] + a1[1]));
            sts64(rp + 256, __float_as_uint(a0[2] + a1[2]), __float_as_uint(a0[3] + a1[3]));
            bar_arrive(BAR_RED, RT);
        }
    } else {
        asm volatile("setmaxnreg.inc.sync.aligned.u32 200;");
        const int ct = tid - 384, cw = w - 12;
        const int mg = cw >> 1, kh = cw & 1;
        uint32_t wf[20][4];
#pragma unroll
        for (int mi = 0; mi < 5; mi++)
#pragma unroll
            for (int ki = 0; ki < 4; ki++) {
                int col0 = c * 160 + (mg * 5 + mi) * 16;
                int e0 = h * DH_ + (kh * 4 + ki) * 16;
                const bf16* p0 = Wo + (size_t)(e0 + 2 * t) * D_ + col0 + g;
                int i = mi * 4 + ki;
                wf[i][0] = ldg_u16x2(p0, p0 + D_);
                wf[i][1] = ldg_u16x2(p0 + 8, p0 + D_ + 8);
                wf[i][2] = ldg_u16x2(p0 + 8 * D_, p0 + 9 * D_);
                wf[i][3] = ldg_u16x2(p0 + 8 * D_ + 8, p0 + 9 * D_ + 8);
            }
        constexpr uint32_t KV_BUF = 48 * HL * 2;
        const bf16* kv_src = g_qkv + (size_t)(ct >> 4) * (3 * HD_) + HD_ + h * DH_ + (ct & 15) * 8;
        const uint32_t kv_dst0 = smem_u32(&sm.kall[0][MEM_ + (ct >> 4)][(ct & 15) * 8]);
        const uint32_t kv_dst1 = smem_u32(&sm.vall[0][MEM_ + (ct >> 4)][(ct & 15) * 8]);
        auto prefetch_kv = [&](int s, int buf) {
            const bf16* src = kv_src + (size_t)s * SEG_ * (3 * HD_);
#pragma unroll
            for (int j = 0; j < 4; j++) {
                cp_async16(kv_dst0 + buf * KV_BUF + j * (8 * HL * 2), src + (size_t)j * 8 * (3 * HD_));
                cp_async16(kv_dst1 + buf * KV_BUF + j * (8 * HL * 2), src + (size_t)j * 8 * (3 * HD_) + HD_);
            }
            cp_async_commit();
        };
        const float4* acc_src = reinterpret_cast<const float4*>(g_acc) + ct;
        const uint32_t acc_dst = smem_u32(&sm.mem[(ct & 1) * 4][ct >> 1]);
        const uint4* hx_base = reinterpret_cast<const uint4*>(g_hx) + h * 1024;
        const int hx_rq = ct & 63, hx_half = ct >> 6;
        const uint4* hx_src = hx_base + hx_half * 64 + hx_rq;
        const uint32_t hx_col = (hx_rq & 7) * 8, hx_r = hx_rq >> 3;
        const uint32_t hx_dstA = (hx_half == 0 ? smem_u32(&sm.qm[hx_r][0]) : smem_u32(&sm.kall[0][hx_r][0])) + hx_col;
        const uint32_t hx_dstB = smem_u32(&sm.vall[0][hx_r][0]) + hx_col;
        const uint4* hx_probe = hx_base + (lane >> 3) * 256 + ((lane & 7) % 3) * 64 + (lane & 7) * 8 + 3;
        const int pb_r = ct >> 4, pb_pr = ct & 15;
        uint2* pb_dst = g_hx + (h * 1024 + c * 256 + pb_r * 8) * 2 + pb_pr;
        const float* pb_src = &sm.red[pb_pr >> 3][(pb_pr & 7) * 16 + pb_r];
        bf16* pb_k = g_kmem + (size_t)pb_r * HD_ + h * DH_ + c * 32 + pb_pr * 2;
        bf16* pb_v = g_vmem + (size_t)pb_r * HD_ + h * DH_ + c * 32 + pb_pr * 2;
        const uint32_t qa = smem_u32(&sm.qm[lane & 15][(lane >> 4) * 8]);
        const uint32_t kb0 = smem_u32(&sm.kall[0][cw * 8 + (lane & 7)][(lane >> 3) * 8]);
        const uint32_t va0 = smem_u32(&sm.vall[0][(lane & 7) + ((lane >> 4) & 1) * 8][cw * 32 + ((lane >> 3) & 1) * 8]);
        const uint32_t pbaddr = smem_u32(&sm.p[lane & 7][((lane >> 3) & 1) * 8]);
        const uint32_t ob = smem_u32(&sm.om[lane & 7][kh * 64 + (lane >> 3) * 8]);
        float* acc_dst_g = g_acc + (c * 160 + mg * 80 + g) * 8 + 2 * t;

        prefetch_kv(0, 0);
        for (int s = 0; s < NSEG_; s++) {
            const int buf = s & 1;
            const uint32_t flag = s + 1;
            const uint32_t bo = buf * KV_BUF;
            PROF(0);
            if (s == 0) {
                for (int i = ct; i < MEM_ * D_ / 8; i += 128) {
                    int r = i / (D_ / 8), cc = (i % (D_ / 8)) * 8;
                    *reinterpret_cast<uint4*>(&sm.mem[r][cc]) = *reinterpret_cast<const uint4*>(mem0 + r * D_ + cc);
                }
            } else {
                if (ct == 0) {
                    const unsigned* cp = g_cnt + (s - 1) * 32;
                    unsigned v; int n = 0;
                    do { asm volatile("ld.acquire.gpu.global.u32 %0, [%1];" : "=r"(v) : "l"(cp) : "memory"); } while (v < 256u && ++n < SPIN_LIMIT);
                }
                bar_sync(BAR_CTL, 128);
                PROF(1);
                const float4* src = acc_src + (size_t)(s - 1) * (MEM_ * D_ / 4);
                float4 v[10];
#pragma unroll
                for (int j = 0; j < 10; j++)
                    asm volatile("ld.relaxed.gpu.global.v4.f32 {%0,%1,%2,%3}, [%4];" : "=f"(v[j].x), "=f"(v[j].y), "=f"(v[j].z), "=f"(v[j].w) : "l"(src + 128 * j) : "memory");
#pragma unroll
                for (int j = 0; j < 10; j++) {
                    uint32_t lo = pack_bf16(v[j].x, v[j].y), hi = pack_bf16(v[j].z, v[j].w);
                    uint32_t d = acc_dst + j * 128;
                    asm volatile("st.shared.u16 [%0], %1;" ::"r"(d), "h"((uint16_t)(lo & 0xffff)) : "memory");
                    asm volatile("st.shared.u16 [%0], %1;" ::"r"(d + MEMS_LD * 2), "h"((uint16_t)(lo >> 16)) : "memory");
                    asm volatile("st.shared.u16 [%0], %1;" ::"r"(d + MEMS_LD * 4), "h"((uint16_t)(hi & 0xffff)) : "memory");
                    asm volatile("st.shared.u16 [%0], %1;" ::"r"(d + MEMS_LD * 6), "h"((uint16_t)(hi >> 16)) : "memory");
                }
            }
            bar_arrive(BAR_MEM, RT);
            PROF(2);
            bar_sync(BAR_RED, RT);
            PROF(3);
            {
                uint32_t pk0 = pack_bf16(pb_src[0] + pb_src[768], pb_src[8] + pb_src[768 + 8]);
                uint32_t pk1 = pack_bf16(pb_src[256] + pb_src[1024], pb_src[256 + 8] + pb_src[1024 + 8]);
                uint32_t pk2 = pack_bf16(pb_src[512] + pb_src[1280], pb_src[512 + 8] + pb_src[1280 + 8]);
                st_relaxed_v2(pb_dst, pk0, flag);
                st_relaxed_v2(pb_dst + 128, pk1, flag);
                st_relaxed_v2(pb_dst + 256, pk2, flag);
                *reinterpret_cast<uint32_t*>(pb_k + (size_t)s * (MEM_ * HD_)) = pk1;
                *reinterpret_cast<uint32_t*>(pb_v + (size_t)s * (MEM_ * HD_)) = pk2;
            }
            if (s == NSEG_ - 1) break;
            PROF(4);
            if (cw == 0) (void)poll_ll(hx_probe, flag);
            bar_sync(BAR_CTL, 128);
            PROF(5);
            {
                uint4 v[8];
#pragma unroll
                for (int j = 0; j < 4; j++) v[j] = ld_relaxed_v4(hx_src + j * 256);
                if (hx_half == 0) {
#pragma unroll
                    for (int j = 0; j < 4; j++) v[4 + j] = ld_relaxed_v4(hx_src + j * 256 + 128);
                }
#pragma unroll
                for (int j = 0; j < 4; j++) {
                    if (v[j].y != flag || v[j].w != flag) v[j] = poll_ll(hx_src + j * 256, flag);
                    sts64(hx_dstA + j * 64 + (hx_half ? bo : 0), v[j].x, v[j].z);
                }
                if (hx_half == 0) {
#pragma unroll
                    for (int j = 0; j < 4; j++) {
                        if (v[4 + j].y != flag || v[4 + j].w != flag) v[4 + j] = poll_ll(hx_src + j * 256 + 128, flag);
                        sts64(hx_dstB + j * 64 + bo, v[4 + j].x, v[4 + j].z);
                    }
                }
            }
            cp_async_wait<0>();
            bar_sync(BAR_CTL, 128);
            PROF(6);
            {
                uint32_t a[8][4], b[4][4], b2[4][4];
#pragma unroll
                for (int kk = 0; kk < 4; kk++) ldsm_x4(b[kk], kb0 + bo + kk * 64);
                if (cw == 0) {
#pragma unroll
                    for (int kk = 0; kk < 4; kk++) ldsm_x4(b2[kk], kb0 + bo + 32 * HL * 2 + kk * 64);
                }
#pragma unroll
                for (int kk = 0; kk < 8; kk++) ldsm_x4(a[kk], qa + kk * 32);
                float s0[4] = {0.f, 0.f, 0.f, 0.f}, s1[4] = {0.f, 0.f, 0.f, 0.f};
#pragma unroll
                for (int kk = 0; kk < 4; kk++) { mma16816(s0, a[2 * kk], b[kk][0], b[kk][1]); mma16816(s1, a[2 * kk + 1], b[kk][2], b[kk][3]); }
                const float scale = 0.08838834764831845f;
                *reinterpret_cast<float2*>(&sm.sc[g][cw * 8 + 2 * t]) =
                    make_float2(rbf(rbf(s0[0] + s1[0]) * scale), rbf(rbf(s0[1] + s1[1]) * scale));
                if (cw == 0) {
                    float u0[4] = {0.f, 0.f, 0.f, 0.f}, u1[4] = {0.f, 0.f, 0.f, 0.f};
#pragma unroll
                    for (int kk = 0; kk < 4; kk++) { mma16816(u0, a[2 * kk], b2[kk][0], b2[kk][1]); mma16816(u1, a[2 * kk + 1], b2[kk][2], b2[kk][3]); }
                    *reinterpret_cast<float2*>(&sm.sc[g][32 + 2 * t]) =
                        make_float2(rbf(rbf(u0[0] + u1[0]) * scale), rbf(rbf(u0[1] + u1[1]) * scale));
                }
            }
            bar_sync(BAR_CTL, 128);
            {
                float v0 = sm.sc[cw][lane], v1 = (lane < 8) ? sm.sc[cw][32 + lane] : -INFINITY;
                float y0 = sm.sc[cw + 4][lane], y1 = (lane < 8) ? sm.sc[cw + 4][32 + lane] : -INFINITY;
                float mx = fmaxf(v0, v1), my = fmaxf(y0, y1);
#pragma unroll
                for (int o = 16; o; o >>= 1) { mx = fmaxf(mx, __shfl_xor_sync(0xffffffffu, mx, o)); my = fmaxf(my, __shfl_xor_sync(0xffffffffu, my, o)); }
                float e0 = __expf(v0 - mx), e1 = (lane < 8) ? __expf(v1 - mx) : 0.f;
                float f0 = __expf(y0 - my), f1 = (lane < 8) ? __expf(y1 - my) : 0.f;
                float sx = e0 + e1, sy = f0 + f1;
#pragma unroll
                for (int o = 16; o; o >>= 1) { sx += __shfl_xor_sync(0xffffffffu, sx, o); sy += __shfl_xor_sync(0xffffffffu, sy, o); }
                float ix = 1.0f / sx, iy = 1.0f / sy;
                sm.p[cw][lane] = __float2bfloat16_rn(e0 * ix);
                sm.p[cw + 4][lane] = __float2bfloat16_rn(f0 * iy);
                if (lane < 8) { sm.p[cw][32 + lane] = __float2bfloat16_rn(e1 * ix); sm.p[cw + 4][32 + lane] = __float2bfloat16_rn(f1 * iy); }
            }
            bar_sync(BAR_CTL, 128);
            PROF(7);
            {
                uint32_t a[2][3][4], b[3][2];
#pragma unroll
                for (int kt = 0; kt < 3; kt++) {
                    asm volatile("ldmatrix.sync.aligned.m8n8.x2.shared.b16 {%0,%1}, [%2];" : "=r"(b[kt][0]), "=r"(b[kt][1]) : "r"(pbaddr + kt * 32));
                    ldsm_x4_t(a[0][kt], va0 + bo + kt * 16 * HL * 2);
                    ldsm_x4_t(a[1][kt], va0 + bo + kt * 16 * HL * 2 + 32);
                }
#pragma unroll
                for (int m = 0; m < 2; m++) {
                    float o[4] = {0.f, 0.f, 0.f, 0.f};
#pragma unroll
                    for (int kt = 0; kt < 3; kt++) mma16816(o, a[m][kt], b[kt][0], b[kt][1]);
                    int d0 = cw * 32 + m * 16 + g;
                    sm.om[2 * t][d0] = __float2bfloat16_rn(o[0]);
                    sm.om[2 * t + 1][d0] = __float2bfloat16_rn(o[1]);
                    sm.om[2 * t][d0 + 8] = __float2bfloat16_rn(o[2]);
                    sm.om[2 * t + 1][d0 + 8] = __float2bfloat16_rn(o[3]);
                }
            }
            bar_sync(BAR_CTL, 128);
            PROF(8);
            {
                float acc[5][4];
#pragma unroll
                for (int mi = 0; mi < 5; mi++) { acc[mi][0] = acc[mi][1] = acc[mi][2] = acc[mi][3] = 0.f; }
                uint32_t b[2][4];
                ldsm_x4(b[0], ob); ldsm_x4(b[1], ob + 64);
#pragma unroll
                for (int ki = 0; ki < 4; ki++)
#pragma unroll
                    for (int mi = 0; mi < 5; mi++) mma16816(acc[mi], wf[mi * 4 + ki], b[ki >> 1][(ki & 1) * 2], b[ki >> 1][(ki & 1) * 2 + 1]);
                if (kh == 1) {
#pragma unroll
                    for (int mi = 0; mi < 5; mi++)
                        *reinterpret_cast<float4*>(&sm.wred[mg][mi][lane * 4]) = make_float4(acc[mi][0], acc[mi][1], acc[mi][2], acc[mi][3]);
                }
                bar_sync(BAR_WO + mg, 64);
                if (kh == 0) {
                    float* dst = acc_dst_g + (size_t)s * (MEM_ * D_);
#pragma unroll
                    for (int mi = 0; mi < 5; mi++) {
                        float4 o2 = *reinterpret_cast<float4*>(&sm.wred[mg][mi][lane * 4]);
                        asm volatile("red.global.add.v2.f32 [%0], {%1,%2};" ::"l"(dst + mi * 128), "f"(acc[mi][0] + o2.x), "f"(acc[mi][1] + o2.y) : "memory");
                        asm volatile("red.global.add.v2.f32 [%0], {%1,%2};" ::"l"(dst + mi * 128 + 64), "f"(acc[mi][2] + o2.z), "f"(acc[mi][3] + o2.w) : "memory");
                    }
                    __threadfence();
                    __syncwarp();
                    if (lane == 0) atomicAdd(&g_cnt[s * 32], 1u);
                }
            }
            PROF(9);
            prefetch_kv(s + 1, buf ^ 1);
            PROF(10);
        }
    }
}

__global__ void __launch_bounds__(128)
attn_x_kernel() {
    __shared__ __align__(16) bf16 sq[32][HL], sk[48][HL], sv[48][HL];
    const int s = blockIdx.x >> 5, h = blockIdx.x & 31;
    const int tid = threadIdx.x, lane = tid & 31, w = tid >> 5, g = lane >> 2, t = lane & 3;
    for (int i = tid; i < (32 + 40 + 40) * 16; i += 128) {
        int r = i >> 4, ch = i & 15;
        const bf16* src; bf16* dst;
        if (r < 32) { src = g_qkv + (size_t)(s * SEG_ + r) * (3 * HD_) + h * DH_; dst = sq[r]; }
        else if (r < 72) { int rr = r - 32; dst = sk[rr];
            src = rr < 8 ? g_kmem + ((size_t)s * MEM_ + rr) * HD_ + h * DH_ : g_qkv + (size_t)(s * SEG_ + rr - 8) * (3 * HD_) + HD_ + h * DH_; }
        else { int rr = r - 72; dst = sv[rr];
            src = rr < 8 ? g_vmem + ((size_t)s * MEM_ + rr) * HD_ + h * DH_ : g_qkv + (size_t)(s * SEG_ + rr - 8) * (3 * HD_) + 2 * HD_ + h * DH_; }
        *reinterpret_cast<uint4*>(dst + ch * 8) = *reinterpret_cast<const uint4*>(src + ch * 8);
    }
    for (int i = tid; i < 8 * 16; i += 128) *reinterpret_cast<uint4*>(&sv[40 + (i >> 4)][(i & 15) * 8]) = make_uint4(0, 0, 0, 0);
    __syncthreads();
    const int rh = w & 1, dhh = w >> 1;
    float sc[5][4];
#pragma unroll
    for (int n = 0; n < 5; n++) sc[n][0] = sc[n][1] = sc[n][2] = sc[n][3] = 0.f;
#pragma unroll
    for (int kk = 0; kk < 8; kk++) {
        uint32_t a[4];
        ldsm_x4(a, smem_u32(&sq[rh * 16 + (lane & 15)][kk * 16 + (lane >> 4) * 8]));
#pragma unroll
        for (int n = 0; n < 5; n++) {
            uint32_t b[2];
            asm volatile("ldmatrix.sync.aligned.m8n8.x2.shared.b16 {%0,%1}, [%2];" : "=r"(b[0]), "=r"(b[1])
                         : "r"(smem_u32(&sk[n * 8 + (lane & 7)][kk * 16 + ((lane >> 3) & 1) * 8])));
            mma16816(sc[n], a, b[0], b[1]);
        }
    }
    const float scale = 0.08838834764831845f;
    float mx[2] = {-INFINITY, -INFINITY};
#pragma unroll
    for (int n = 0; n < 5; n++)
#pragma unroll
        for (int e = 0; e < 4; e++) {
            int row = rh * 16 + g + (e >> 1) * 8, key = n * 8 + 2 * t + (e & 1);
            float v = rbf(rbf(sc[n][e]) * scale);
            if (key > row + MEM_) v = -INFINITY;
            sc[n][e] = v;
            mx[e >> 1] = fmaxf(mx[e >> 1], v);
        }
#pragma unroll
    for (int o = 1; o < 4; o <<= 1) { mx[0] = fmaxf(mx[0], __shfl_xor_sync(0xffffffffu, mx[0], o)); mx[1] = fmaxf(mx[1], __shfl_xor_sync(0xffffffffu, mx[1], o)); }
    float sum[2] = {0.f, 0.f};
#pragma unroll
    for (int n = 0; n < 5; n++)
#pragma unroll
        for (int e = 0; e < 4; e++) { float ev = __expf(sc[n][e] - mx[e >> 1]); sc[n][e] = ev; sum[e >> 1] += ev; }
#pragma unroll
    for (int o = 1; o < 4; o <<= 1) { sum[0] += __shfl_xor_sync(0xffffffffu, sum[0], o); sum[1] += __shfl_xor_sync(0xffffffffu, sum[1], o); }
    float inv[2] = {1.0f / sum[0], 1.0f / sum[1]};
    uint32_t pa[3][4];
#pragma unroll
    for (int kt = 0; kt < 3; kt++) {
        pa[kt][0] = pack_bf16(sc[2 * kt][0] * inv[0], sc[2 * kt][1] * inv[0]);
        pa[kt][1] = pack_bf16(sc[2 * kt][2] * inv[1], sc[2 * kt][3] * inv[1]);
        if (kt < 2) {
            pa[kt][2] = pack_bf16(sc[2 * kt + 1][0] * inv[0], sc[2 * kt + 1][1] * inv[0]);
            pa[kt][3] = pack_bf16(sc[2 * kt + 1][2] * inv[1], sc[2 * kt + 1][3] * inv[1]);
        } else { pa[kt][2] = 0u; pa[kt][3] = 0u; }
    }
#pragma unroll
    for (int n = 0; n < 8; n++) {
        float o[4] = {0.f, 0.f, 0.f, 0.f};
#pragma unroll
        for (int kt = 0; kt < 3; kt++) {
            uint32_t b[2];
            asm volatile("ldmatrix.sync.aligned.m8n8.x2.trans.shared.b16 {%0,%1}, [%2];" : "=r"(b[0]), "=r"(b[1])
                         : "r"(smem_u32(&sv[kt * 16 + (lane & 15)][dhh * 64 + n * 8])));
            mma16816(o, pa[kt], b[0], b[1]);
        }
        int row = s * SEG_ + rh * 16 + g;
        bf16* dst = g_o + (size_t)row * HD_ + h * DH_ + dhh * 64 + n * 8 + 2 * t;
        *reinterpret_cast<uint32_t*>(dst) = pack_bf16(o[0], o[1]);
        *reinterpret_cast<uint32_t*>(dst + 8 * HD_) = pack_bf16(o[2], o[3]);
    }
}

typedef CUresult (*PFN_encodeTiled)(CUtensorMap*, CUtensorMapDataType, cuuint32_t, void*, const cuuint64_t*,
                                    const cuuint64_t*, const cuuint32_t*, const cuuint32_t*, CUtensorMapInterleave,
                                    CUtensorMapSwizzle, CUtensorMapL2promotion, CUtensorMapFloatOOBfill);
static PFN_encodeTiled p_encode = nullptr;

static CUtensorMap make_map(const void* ptr, uint64_t rows, uint64_t cols, uint64_t ld, uint32_t box_rows) {
    CUtensorMap m;
    cuuint64_t dims[2] = {cols, rows};
    cuuint64_t strides[1] = {ld * 2};
    cuuint32_t box[2] = {64, box_rows};
    cuuint32_t es[2] = {1, 1};
    p_encode(&m, CU_TENSOR_MAP_DATA_TYPE_BFLOAT16, 2, const_cast<void*>(ptr), dims, strides, box, es,
             CU_TENSOR_MAP_INTERLEAVE_NONE, CU_TENSOR_MAP_SWIZZLE_128B, CU_TENSOR_MAP_L2_PROMOTION_L2_128B,
             CU_TENSOR_MAP_FLOAT_OOB_FILL_NONE);
    return m;
}

template <int BN, int EPI>
static void launch_gemm(const CUtensorMap& a, const CUtensorMap& b, int M, int N, int K, EpiParams ep, cudaStream_t st) {
    constexpr int STAGE = 16384 + (BN / 64) * 8192;
    constexpr int NST = (200 * 1024) / STAGE;
    constexpr int SMEM = NST * STAGE + 1024;
    cudaFuncSetAttribute(gemm_kernel<BN, EPI>, cudaFuncAttributeMaxDynamicSharedMemorySize, SMEM);
    dim3 grid((N + BN - 1) / BN, M / 128);
    gemm_kernel<BN, EPI><<<grid, 384, SMEM, st>>>(a, b, M, N, K, ep);
}

extern "C" void kernel_launch(void* const* d_in, const int* in_sizes, int n_in, void* d_out, int out_size) {
    const bf16* x    = (const bf16*)d_in[0];
    const bf16* mem0 = (const bf16*)d_in[1];
    const bf16* Wq   = (const bf16*)d_in[2];
    const bf16* Wk   = (const bf16*)d_in[3];
    const bf16* Wv   = (const bf16*)d_in[4];
    const bf16* Wo   = (const bf16*)d_in[5];
    const bf16* w_in  = (const bf16*)d_in[8];
    const bf16* w_sp  = (const bf16*)d_in[9];
    const bf16* b_sp  = (const bf16*)d_in[10];
    const bf16* w_out = (const bf16*)d_in[11];
    bf16* out = (bf16*)d_out;
    cudaStream_t st = cudaStreamPerThread;

    if (!p_encode) {
        cudaDriverEntryPointQueryResult qr;
        cudaGetDriverEntryPoint("cuTensorMapEncodeTiled", (void**)&p_encode, cudaEnableDefault, &qr);
    }
    void *p_xn, *p_qkv, *p_z, *p_zg, *p_gate, *p_o, *p_acc, *p_cnt, *p_hx;
    cudaGetSymbolAddress(&p_xn, g_xn); cudaGetSymbolAddress(&p_qkv, g_qkv); cudaGetSymbolAddress(&p_z, g_z);
    cudaGetSymbolAddress(&p_zg, g_zg); cudaGetSymbolAddress(&p_gate, g_gate); cudaGetSymbolAddress(&p_o, g_o);
    cudaGetSymbolAddress(&p_acc, g_acc); cudaGetSymbolAddress(&p_cnt, g_cnt); cudaGetSymbolAddress(&p_hx, g_hx);

    CUtensorMap mA_xn  = make_map(p_xn, S_, D_, D_, 128);
    CUtensorMap mA_wsp = make_map(w_sp, S_, S_, S_, 128);
    CUtensorMap mA_zg  = make_map(p_zg, S_, FH_, FH_, 128);
    CUtensorMap mA_o   = make_map(p_o, S_, HD_, HD_, 128);
    CUtensorMap mB_wq  = make_map(Wq, D_, HD_, HD_, 64);
    CUtensorMap mB_wk  = make_map(Wk, D_, HD_, HD_, 64);
    CUtensorMap mB_wv  = make_map(Wv, D_, HD_, HD_, 64);
    CUtensorMap mB_win = make_map(w_in, D_, F_, F_, 64);
    CUtensorMap mB_z2  = make_map((bf16*)p_z + FH_, S_, FH_, F_, 64);
    CUtensorMap mB_wout = make_map(w_out, FH_, D_, D_, 64);
    CUtensorMap mB_wo  = make_map(Wo, HD_, D_, D_, 64);

    cudaMemsetAsync(p_acc, 0, sizeof(float) * NSEG_ * MEM_ * D_, st);
    cudaMemsetAsync(p_cnt, 0, sizeof(unsigned) * NSEG_ * 32, st);
    cudaMemsetAsync(p_hx, 0, sizeof(uint2) * H_ * 4 * 256 * 2, st);

    ln_kernel<<<S_ / 8, 256, 0, st>>>(x);
    for (int i = 0; i < 3; i++) {
        EpiParams ep{(bf16*)p_qkv + i * HD_, 3 * HD_, nullptr, nullptr};
        launch_gemm<128, EPI_STORE>(mA_xn, i == 0 ? mB_wq : (i == 1 ? mB_wk : mB_wv), S_, HD_, D_, ep, st);
    }
    { EpiParams ep{(bf16*)p_z, F_, nullptr, nullptr}; launch_gemm<192, EPI_GELU>(mA_xn, mB_win, S_, F_, D_, ep, st); }
    ln2_kernel<<<S_ / 8, 256, 0, st>>>();
    { EpiParams ep{(bf16*)p_zg, FH_, (const bf16*)p_z, b_sp}; launch_gemm<128, EPI_SP>(mA_wsp, mB_z2, S_, FH_, S_, ep, st); }
    { EpiParams ep{(bf16*)p_gate, D_, nullptr, nullptr}; launch_gemm<128, EPI_SILU>(mA_zg, mB_wout, S_, D_, FH_, ep, st); }
    cudaFuncSetAttribute(recur_kernel, cudaFuncAttributeMaxDynamicSharedMemorySize, (int)sizeof(RecurSmem));
    recur_kernel<<<128, RT, sizeof(RecurSmem), st>>>(mem0, Wq, Wk, Wv, Wo);
    attn_x_kernel<<<NSEG_ * H_, 128, 0, st>>>();
    { EpiParams ep{out, D_, x, (const bf16*)p_gate}; launch_gemm<128, EPI_FINAL>(mA_o, mB_wo, S_, D_, HD_, ep, st); }
}
```

```cpp
#include <cuda_runtime.h>
#include <cuda_bf16.h>
#include <cuda.h>
#include <stdint.h>

typedef __nv_bfloat16 bf16;

constexpr int S_   = 2048;
constexpr int D_   = 640;
constexpr int H_   = 32;
constexpr int DH_  = 128;
constexpr int MEM_ = 8;
constexpr int SEG_ = 32;
constexpr int NSEG_ = S_ / SEG_;
constexpr int HD_  = H_ * DH_;
constexpr int F_   = 1728;
constexpr int FH_  = 864;

__device__ bf16 g_xn[S_ * D_];
__device__ bf16 g_qkv[(size_t)S_ * 3 * HD_];
__device__ bf16 g_z[S_ * F_];
__device__ bf16 g_zg[S_ * FH_];
__device__ bf16 g_gate[S_ * D_];
__device__ bf16 g_kmem[NSEG_ * MEM_ * HD_];
__device__ bf16 g_vmem[NSEG_ * MEM_ * HD_];
__device__ bf16 g_o[(size_t)S_ * HD_];
__device__ float g_acc[NSEG_ * MEM_ * D_];
__device__ unsigned g_cnt[NSEG_ * 32];
__device__ uint2 g_hx[H_ * 4 * 256 * 2];

__device__ __forceinline__ uint32_t smem_u32(const void* p) { return (uint32_t)__cvta_generic_to_shared(p); }
__device__ __forceinline__ float bf2f(bf16 v) { return __bfloat162float(v); }
__device__ __forceinline__ float rbf(float v) { return __bfloat162float(__float2bfloat16_rn(v)); }
__device__ __forceinline__ uint32_t pack_bf16(float lo, float hi) {
    __nv_bfloat162 t = __floats2bfloat162_rn(lo, hi);
    return *reinterpret_cast<uint32_t*>(&t);
}
__device__ __forceinline__ float lo_f(uint32_t u) { return __uint_as_float(u << 16); }
__device__ __forceinline__ float hi_f(uint32_t u) { return __uint_as_float(u & 0xffff0000u); }

__device__ __forceinline__ void mbar_init(uint32_t bar, uint32_t cnt) {
    asm volatile("mbarrier.init.shared.b64 [%0], %1;" ::"r"(bar), "r"(cnt));
}
__device__ __forceinline__ void mbar_expect_tx(uint32_t bar, uint32_t bytes) {
    asm volatile("mbarrier.arrive.expect_tx.shared.b64 _, [%0], %1;" ::"r"(bar), "r"(bytes) : "memory");
}
__device__ __forceinline__ void mbar_arrive(uint32_t bar) {
    asm volatile("mbarrier.arrive.shared.b64 _, [%0];" ::"r"(bar) : "memory");
}
__device__ __forceinline__ void mbar_wait(uint32_t bar, uint32_t parity) {
    asm volatile(
        "{\n .reg .pred p;\n"
        "WAIT_%=:\n"
        " mbarrier.try_wait.parity.shared.b64 p, [%0], %1;\n"
        " @p bra DONE_%=;\n"
        " bra WAIT_%=;\n"
        "DONE_%=:\n}\n" ::"r"(bar), "r"(parity) : "memory");
}
__device__ __forceinline__ void tma_load_2d(uint32_t dst, const CUtensorMap* tm, uint32_t bar, int c0, int c1) {
    asm volatile(
        "cp.async.bulk.tensor.2d.shared::cluster.global.mbarrier::complete_tx::bytes [%0], [%1, {%3, %4}], [%2];"
        ::"r"(dst), "l"(tm), "r"(bar), "r"(c0), "r"(c1) : "memory");
}
__device__ __forceinline__ void wgmma_fence() { asm volatile("wgmma.fence.sync.aligned;" ::: "memory"); }
__device__ __forceinline__ void wgmma_commit() { asm volatile("wgmma.commit_group.sync.aligned;" ::: "memory"); }
template <int N> __device__ __forceinline__ void wgmma_wait() { asm volatile("wgmma.wait_group.sync.aligned %0;" ::"n"(N) : "memory"); }

__device__ __forceinline__ uint64_t make_desc(uint32_t addr, uint32_t lbo, uint32_t sbo) {
    return (uint64_t)((addr & 0x3FFFF) >> 4) | ((uint64_t)(lbo >> 4) << 16) | ((uint64_t)(sbo >> 4) << 32) | (1ull << 62);
}

template <int N> struct Wgmma;
template <> struct Wgmma<128> {
    static __device__ __forceinline__ void mma(float* d, uint64_t da, uint64_t db, int sd) {
        asm volatile(
            "{\n.reg .pred p;\nsetp.ne.b32 p, %66, 0;\n"
            "wgmma.mma_async.sync.aligned.m64n128k16.f32.bf16.bf16 "
            "{%0,%1,%2,%3,%4,%5,%6,%7,%8,%9,%10,%11,%12,%13,%14,%15,"
            "%16,%17,%18,%19,%20,%21,%22,%23,%24,%25,%26,%27,%28,%29,%30,%31,"
            "%32,%33,%34,%35,%36,%37,%38,%39,%40,%41,%42,%43,%44,%45,%46,%47,"
            "%48,%49,%50,%51,%52,%53,%54,%55,%56,%57,%58,%59,%60,%61,%62,%63},"
            "%64,%65,p,1,1,0,1;\n}\n"
            : "+f"(d[0]), "+f"(d[1]), "+f"(d[2]), "+f"(d[3]), "+f"(d[4]), "+f"(d[5]), "+f"(d[6]), "+f"(d[7]),
              "+f"(d[8]), "+f"(d[9]), "+f"(d[10]), "+f"(d[11]), "+f"(d[12]), "+f"(d[13]), "+f"(d[14]), "+f"(d[15]),
              "+f"(d[16]), "+f"(d[17]), "+f"(d[18]), "+f"(d[19]), "+f"(d[20]), "+f"(d[21]), "+f"(d[22]), "+f"(d[23]),
              "+f"(d[24]), "+f"(d[25]), "+f"(d[26]), "+f"(d[27]), "+f"(d[28]), "+f"(d[29]), "+f"(d[30]), "+f"(d[31]),
              "+f"(d[32]), "+f"(d[33]), "+f"(d[34]), "+f"(d[35]), "+f"(d[36]), "+f"(d[37]), "+f"(d[38]), "+f"(d[39]),
              "+f"(d[40]), "+f"(d[41]), "+f"(d[42]), "+f"(d[43]), "+f"(d[44]), "+f"(d[45]), "+f"(d[46]), "+f"(d[47]),
              "+f"(d[48]), "+f"(d[49]), "+f"(d[50]), "+f"(d[51]), "+f"(d[52]), "+f"(d[53]), "+f"(d[54]), "+f"(d[55]),
              "+f"(d[56]), "+f"(d[57]), "+f"(d[58]), "+f"(d[59]), "+f"(d[60]), "+f"(d[61]), "+f"(d[62]), "+f"(d[63])
            : "l"(da), "l"(db), "r"(sd));
    }
};
template <> struct Wgmma<192> {
    static __device__ __forceinline__ void mma(float* d, uint64_t da, uint64_t db, int sd) {
        asm volatile(
            "{\n.reg .pred p;\nsetp.ne.b32 p, %98, 0;\n"
            "wgmma.mma_async.sync.aligned.m64n192k16.f32.bf16.bf16 "
            "{%0,%1,%2,%3,%4,%5,%6,%7,%8,%9,%10,%11,%12,%13,%14,%15,"
            "%16,%17,%18,%19,%20,%21,%22,%23,%24,%25,%26,%27,%28,%29,%30,%31,"
            "%32,%33,%34,%35,%36,%37,%38,%39,%40,%41,%42,%43,%44,%45,%46,%47,"
            "%48,%49,%50,%51,%52,%53,%54,%55,%56,%57,%58,%59,%60,%61,%62,%63,"
            "%64,%65,%66,%67,%68,%69,%70,%71,%72,%73,%74,%75,%76,%77,%78,%79,"
            "%80,%81,%82,%83,%84,%85,%86,%87,%88,%89,%90,%91,%92,%93,%94,%95},"
            "%96,%97,p,1,1,0,1;\n}\n"
            : "+f"(d[0]), "+f"(d[1]), "+f"(d[2]), "+f"(d[3]), "+f"(d[4]), "+f"(d[5]), "+f"(d[6]), "+f"(d[7]),
              "+f"(d[8]), "+f"(d[9]), "+f"(d[10]), "+f"(d[11]), "+f"(d[12]), "+f"(d[13]), "+f"(d[14]), "+f"(d[15]),
              "+f"(d[16]), "+f"(d[17]), "+f"(d[18]), "+f"(d[19]), "+f"(d[20]), "+f"(d[21]), "+f"(d[22]), "+f"(d[23]),
              "+f"(d[24]), "+f"(d[25]), "+f"(d[26]), "+f"(d[27]), "+f"(d[28]), "+f"(d[29]), "+f"(d[30]), "+f"(d[31]),
              "+f"(d[32]), "+f"(d[33]), "+f"(d[34]), "+f"(d[35]), "+f"(d[36]), "+f"(d[37]), "+f"(d[38]), "+f"(d[39]),
              "+f"(d[40]), "+f"(d[41]), "+f"(d[42]), "+f"(d[43]), "+f"(d[44]), "+f"(d[45]), "+f"(d[46]), "+f"(d[47]),
              "+f"(d[48]), "+f"(d[49]), "+f"(d[50]), "+f"(d[51]), "+f"(d[52]), "+f"(d[53]), "+f"(d[54]), "+f"(d[55]),
              "+f"(d[56]), "+f"(d[57]), "+f"(d[58]), "+f"(d[59]), "+f"(d[60]), "+f"(d[61]), "+f"(d[62]), "+f"(d[63]),
              "+f"(d[64]), "+f"(d[65]), "+f"(d[66]), "+f"(d[67]), "+f"(d[68]), "+f"(d[69]), "+f"(d[70]), "+f"(d[71]),
              "+f"(d[72]), "+f"(d[73]), "+f"(d[74]), "+f"(d[75]), "+f"(d[76]), "+f"(d[77]), "+f"(d[78]), "+f"(d[79]),
              "+f"(d[80]), "+f"(d[81]), "+f"(d[82]), "+f"(d[83]), "+f"(d[84]), "+f"(d[85]), "+f"(d[86]), "+f"(d[87]),
              "+f"(d[88]), "+f"(d[89]), "+f"(d[90]), "+f"(d[91]), "+f"(d[92]), "+f"(d[93]), "+f"(d[94]), "+f"(d[95])
            : "l"(da), "l"(db), "r"(sd));
    }
};

template <> struct Wgmma<256> {
    static __device__ __forceinline__ void mma(float* d, uint64_t da, uint64_t db, int sd) {
        asm volatile(
            "{\n.reg .pred p;\nsetp.ne.b32 p, %130, 0;\n"
            "wgmma.mma_async.sync.aligned.m64n256k16.f32.bf16.bf16 "
            "{%0,%1,%2,%3,%4,%5,%6,%7,%8,%9,%10,%11,%12,%13,%14,%15,%16,%17,%18,%19,%20,%21,%22,%23,%24,%25,%26,%27,%28,%29,%30,%31,%32,%33,%34,%35,%36,%37,%38,%39,%40,%41,%42,%43,%44,%45,%46,%47,%48,%49,%50,%51,%52,%53,%54,%55,%56,%57,%58,%59,%60,%61,%62,%63,%64,%65,%66,%67,%68,%69,%70,%71,%72,%73,%74,%75,%76,%77,%78,%79,%80,%81,%82,%83,%84,%85,%86,%87,%88,%89,%90,%91,%92,%93,%94,%95,%96,%97,%98,%99,%100,%101,%102,%103,%104,%105,%106,%107,%108,%109,%110,%111,%112,%113,%114,%115,%116,%117,%118,%119,%120,%121,%122,%123,%124,%125,%126,%127},"
            "%128,%129,p,1,1,0,1;\n}\n"
            : "+f"(d[0]), "+f"(d[1]), "+f"(d[2]), "+f"(d[3]), "+f"(d[4]), "+f"(d[5]), "+f"(d[6]), "+f"(d[7]), "+f"(d[8]), "+f"(d[9]), "+f"(d[10]), "+f"(d[11]), "+f"(d[12]), "+f"(d[13]), "+f"(d[14]), "+f"(d[15]), "+f"(d[16]), "+f"(d[17]), "+f"(d[18]), "+f"(d[19]), "+f"(d[20]), "+f"(d[21]), "+f"(d[22]), "+f"(d[23]), "+f"(d[24]), "+f"(d[25]), "+f"(d[26]), "+f"(d[27]), "+f"(d[28]), "+f"(d[29]), "+f"(d[30]), "+f"(d[31]), "+f"(d[32]), "+f"(d[33]), "+f"(d[34]), "+f"(d[35]), "+f"(d[36]), "+f"(d[37]), "+f"(d[38]), "+f"(d[39]), "+f"(d[40]), "+f"(d[41]), "+f"(d[42]), "+f"(d[43]), "+f"(d[44]), "+f"(d[45]), "+f"(d[46]), "+f"(d[47]), "+f"(d[48]), "+f"(d[49]), "+f"(d[50]), "+f"(d[51]), "+f"(d[52]), "+f"(d[53]), "+f"(d[54]), "+f"(d[55]), "+f"(d[56]), "+f"(d[57]), "+f"(d[58]), "+f"(d[59]), "+f"(d[60]), "+f"(d[61]), "+f"(d[62]), "+f"(d[63]), "+f"(d[64]), "+f"(d[65]), "+f"(d[66]), "+f"(d[67]), "+f"(d[68]), "+f"(d[69]), "+f"(d[70]), "+f"(d[71]), "+f"(d[72]), "+f"(d[73]), "+f"(d[74]), "+f"(d[75]), "+f"(d[76]), "+f"(d[77]), "+f"(d[78]), "+f"(d[79]), "+f"(d[80]), "+f"(d[81]), "+f"(d[82]), "+f"(d[83]), "+f"(d[84]), "+f"(d[85]), "+f"(d[86]), "+f"(d[87]), "+f"(d[88]), "+f"(d[89]), "+f"(d[90]), "+f"(d[91]), "+f"(d[92]), "+f"(d[93]), "+f"(d[94]), "+f"(d[95]), "+f"(d[96]), "+f"(d[97]), "+f"(d[98]), "+f"(d[99]), "+f"(d[100]), "+f"(d[101]), "+f"(d[102]), "+f"(d[103]), "+f"(d[104]), "+f"(d[105]), "+f"(d[106]), "+f"(d[107]), "+f"(d[108]), "+f"(d[109]), "+f"(d[110]), "+f"(d[111]), "+f"(d[112]), "+f"(d[113]), "+f"(d[114]), "+f"(d[115]), "+f"(d[116]), "+f"(d[117]), "+f"(d[118]), "+f"(d[119]), "+f"(d[120]), "+f"(d[121]), "+f"(d[122]), "+f"(d[123]), "+f"(d[124]), "+f"(d[125]), "+f"(d[126]), "+f"(d[127])
            : "l"(da), "l"(db), "r"(sd));
    }
};
template <int W>
__device__ __forceinline__ void ln_row(const bf16* __restrict__ src, bf16* __restrict__ dst, int lane) {
    constexpr int NP = W / 64;
    constexpr int REM = (W / 2) % 32;
    uint32_t v[NP + 1];
    const uint32_t* s32 = reinterpret_cast<const uint32_t*>(src);
    float sum = 0.f;
#pragma unroll
    for (int i = 0; i < NP; i++) { v[i] = s32[i * 32 + lane]; sum += lo_f(v[i]) + hi_f(v[i]); }
    if (REM) { v[NP] = (lane < REM) ? s32[NP * 32 + lane] : 0u; if (lane < REM) sum += lo_f(v[NP]) + hi_f(v[NP]); }
#pragma unroll
    for (int o = 16; o; o >>= 1) sum += __shfl_xor_sync(0xffffffffu, sum, o);
    float mean = sum * (1.0f / W);
    float vs = 0.f;
#pragma unroll
    for (int i = 0; i < NP; i++) { float a = lo_f(v[i]) - mean, b = hi_f(v[i]) - mean; vs += a * a + b * b; }
    if (REM && lane < REM) { float a = lo_f(v[NP]) - mean, b = hi_f(v[NP]) - mean; vs += a * a + b * b; }
#pragma unroll
    for (int o = 16; o; o >>= 1) vs += __shfl_xor_sync(0xffffffffu, vs, o);
    float var = rbf(vs * (1.0f / W));
    float mb = rbf(mean);
    float den = rbf(sqrtf(rbf(var + 1e-5f)));
    uint32_t* d32 = reinterpret_cast<uint32_t*>(dst);
#pragma unroll
    for (int i = 0; i < NP; i++) d32[i * 32 + lane] = pack_bf16(rbf(lo_f(v[i]) - mb) / den, rbf(hi_f(v[i]) - mb) / den);
    if (REM && lane < REM) d32[NP * 32 + lane] = pack_bf16(rbf(lo_f(v[NP]) - mb) / den, rbf(hi_f(v[NP]) - mb) / den);
}

__global__ void ln_kernel(const bf16* __restrict__ x) {
    int row = blockIdx.x * 8 + (threadIdx.x >> 5);
    ln_row<D_>(x + (size_t)row * D_, g_xn + (size_t)row * D_, threadIdx.x & 31);
}
__global__ void ln2_kernel() {
    int row = blockIdx.x * 8 + (threadIdx.x >> 5);
    bf16* p = g_z + (size_t)row * F_ + FH_;
    ln_row<FH_>(p, p, threadIdx.x & 31);
}

enum { EPI_STORE = 0, EPI_GELU = 1, EPI_SP = 2, EPI_SILU = 3, EPI_FINAL = 4 };
struct EpiParams {
    bf16* out; int ldo;
    const bf16* aux0;
    const bf16* aux1;
};

__device__ __forceinline__ float gelu_tanh_f(float x) {
    const float k0 = 0.7978845608028654f, k1 = 0.044715f;
    float inner = k0 * (x + k1 * x * x * x);
    return 0.5f * x * (1.0f + tanhf(inner));
}
__device__ __forceinline__ float silu_f(float x) { return x / (1.0f + expf(-x)); }

template <int BN, int EPI>
__global__ void __launch_bounds__(384, 1)
gemm_kernel(const __grid_constant__ CUtensorMap tmA, const __grid_constant__ CUtensorMap tmB0,
            const __grid_constant__ CUtensorMap tmB1, const __grid_constant__ CUtensorMap tmB2,
            int nPerB, int N, int K, EpiParams ep) {
    constexpr int BM = 128, BK = 64;
    constexpr int A_BYTES = BM * BK * 2;
    constexpr int B_BYTES = (BN / 64) * 8192;
    constexpr int STAGE = A_BYTES + B_BYTES;
    constexpr int NST = (200 * 1024) / STAGE;
    constexpr int OLD = BN + 8;
    extern __shared__ __align__(1024) uint8_t smem_raw[];
    uint8_t* smem = (uint8_t*)(((uintptr_t)smem_raw + 1023) & ~(uintptr_t)1023);
    __shared__ __align__(8) uint64_t full_bar[NST], empty_bar[NST];

    const int tid = threadIdx.x, wg = tid >> 7;
    const int m0 = blockIdx.y * BM, n0 = blockIdx.x * BN;
    const int nk = (K + BK - 1) / BK;

    if (tid == 0) {
        for (int i = 0; i < NST; i++) { mbar_init(smem_u32(&full_bar[i]), 1); mbar_init(smem_u32(&empty_bar[i]), 2); }
        asm volatile("fence.mbarrier_init.release.cluster;" ::: "memory");
    }
    __syncthreads();

    if (wg == 0) {
        if (tid == 0) {
            const int bsel = n0 / nPerB;
            const CUtensorMap* tmB = bsel == 0 ? &tmB0 : (bsel == 1 ? &tmB1 : &tmB2);
            const int nb = n0 - bsel * nPerB;
            for (int kt = 0; kt < nk; kt++) {
                int st = kt % NST; uint32_t ph = (kt / NST) & 1;
                mbar_wait(smem_u32(&empty_bar[st]), ph ^ 1);
                uint32_t fb = smem_u32(&full_bar[st]);
                mbar_expect_tx(fb, STAGE);
                uint32_t sa = smem_u32(smem + st * STAGE);
                tma_load_2d(sa, &tmA, fb, kt * BK, m0);
#pragma unroll
                for (int j = 0; j < BN / 64; j++) tma_load_2d(sa + A_BYTES + j * 8192, tmB, fb, nb + j * 64, kt * BK);
            }
        }
    } else {
        const int cw = wg - 1;
        float acc[BN / 2];
        for (int kt = 0; kt < nk; kt++) {
            int st = kt % NST; uint32_t ph = (kt / NST) & 1;
            mbar_wait(smem_u32(&full_bar[st]), ph);
            uint32_t sa = smem_u32(smem + st * STAGE) + cw * 64 * 128;
            uint32_t sb = smem_u32(smem + st * STAGE) + A_BYTES;
            wgmma_fence();
#pragma unroll
            for (int k = 0; k < BK / 16; k++) {
                uint64_t da = make_desc(sa + k * 32, 16, 1024);
                uint64_t db = make_desc(sb + k * 2048, 8192, 1024);
                Wgmma<BN>::mma(acc, da, db, (kt | k) != 0);
            }
            wgmma_commit();
            wgmma_wait<1>();
            if (kt > 0 && (tid & 127) == 0) mbar_arrive(smem_u32(&empty_bar[(kt - 1) % NST]));
        }
        wgmma_wait<0>();
        asm volatile("bar.sync 1, 256;" ::: "memory");
        const int lane = tid & 31, wi = (tid >> 5) & 3, g = lane >> 2, t = lane & 3;
        bf16* stg = reinterpret_cast<bf16*>(smem) + cw * 64 * OLD;
#pragma unroll
        for (int j = 0; j < BN / 8; j++) {
            *reinterpret_cast<uint32_t*>(&stg[(wi * 16 + g) * OLD + j * 8 + 2 * t]) = pack_bf16(acc[4 * j], acc[4 * j + 1]);
            *reinterpret_cast<uint32_t*>(&stg[(wi * 16 + g + 8) * OLD + j * 8 + 2 * t]) = pack_bf16(acc[4 * j + 2], acc[4 * j + 3]);
        }
        asm volatile("bar.sync %0, 128;" ::"r"(2 + cw) : "memory");
        constexpr int CPR = BN / 8;
        const int ltid = tid & 127;
#pragma unroll 4
        for (int i = ltid; i < 64 * CPR; i += 128) {
            int r = i / CPR, ch = i % CPR;
            int row = m0 + cw * 64 + r, col = n0 + ch * 8;
            if (col >= N) continue;
            uint4 v = *reinterpret_cast<const uint4*>(&stg[r * OLD + ch * 8]);
            uint32_t u[4] = {v.x, v.y, v.z, v.w}, o[4];
            if (EPI == EPI_STORE) {
#pragma unroll
                for (int q = 0; q < 4; q++) o[q] = u[q];
            } else if (EPI == EPI_GELU) {
#pragma unroll
                for (int q = 0; q < 4; q++) o[q] = pack_bf16(gelu_tanh_f(lo_f(u[q])), gelu_tanh_f(hi_f(u[q])));
            } else if (EPI == EPI_SP) {
                float bb = bf2f(ep.aux1[row]);
                uint4 z = *reinterpret_cast<const uint4*>(ep.aux0 + (size_t)row * F_ + col);
                uint32_t zz[4] = {z.x, z.y, z.z, z.w};
#pragma unroll
                for (int q = 0; q < 4; q++) o[q] = pack_bf16(lo_f(zz[q]) * rbf(lo_f(u[q]) + bb), hi_f(zz[q]) * rbf(hi_f(u[q]) + bb));
            } else if (EPI == EPI_SILU) {
#pragma unroll
                for (int q = 0; q < 4; q++) o[q] = pack_bf16(silu_f(lo_f(u[q])), silu_f(hi_f(u[q])));
            } else {
                uint4 xv = *reinterpret_cast<const uint4*>(ep.aux0 + (size_t)row * D_ + col);
                uint4 gv = *reinterpret_cast<const uint4*>(ep.aux1 + (size_t)row * D_ + col);
                uint32_t xx[4] = {xv.x, xv.y, xv.z, xv.w}, gg[4] = {gv.x, gv.y, gv.z, gv.w};
#pragma unroll
                for (int q = 0; q < 4; q++)
                    o[q] = pack_bf16(lo_f(xx[q]) + rbf(lo_f(u[q]) * lo_f(gg[q])), hi_f(xx[q]) + rbf(hi_f(u[q]) * hi_f(gg[q])));
            }
            *reinterpret_cast<uint4*>(ep.out + (size_t)row * ep.ldo + col) = make_uint4(o[0], o[1], o[2], o[3]);
        }
    }
}

__device__ __forceinline__ void mma16816(float* c, const uint32_t* a, uint32_t b0, uint32_t b1) {
    asm volatile(
        "mma.sync.aligned.m16n8k16.row.col.f32.bf16.bf16.f32 {%0,%1,%2,%3}, {%4,%5,%6,%7}, {%8,%9}, {%0,%1,%2,%3};"
        : "+f"(c[0]), "+f"(c[1]), "+f"(c[2]), "+f"(c[3])
        : "r"(a[0]), "r"(a[1]), "r"(a[2]), "r"(a[3]), "r"(b0), "r"(b1));
}
__device__ __forceinline__ void ldsm_x4(uint32_t* r, uint32_t addr) {
    asm volatile("ldmatrix.sync.aligned.m8n8.x4.shared.b16 {%0,%1,%2,%3}, [%4];"
                 : "=r"(r[0]), "=r"(r[1]), "=r"(r[2]), "=r"(r[3]) : "r"(addr));
}
__device__ __forceinline__ void ldsm_x4_t(uint32_t* r, uint32_t addr) {
    asm volatile("ldmatrix.sync.aligned.m8n8.x4.trans.shared.b16 {%0,%1,%2,%3}, [%4];"
                 : "=r"(r[0]), "=r"(r[1]), "=r"(r[2]), "=r"(r[3]) : "r"(addr));
}
__device__ __forceinline__ uint4 ld_relaxed_v4(const void* p) {
    uint4 v;
    asm volatile("ld.relaxed.gpu.global.v4.u32 {%0,%1,%2,%3}, [%4];" : "=r"(v.x), "=r"(v.y), "=r"(v.z), "=r"(v.w) : "l"(p) : "memory");
    return v;
}
__device__ __forceinline__ void st_relaxed_v4(void* p, uint32_t a, uint32_t b, uint32_t c, uint32_t d) {
    asm volatile("st.relaxed.gpu.global.v4.u32 [%0], {%1,%2,%3,%4};" ::"l"(p), "r"(a), "r"(b), "r"(c), "r"(d) : "memory");
}
__device__ __forceinline__ void st_relaxed_v2(void* p, uint32_t a, uint32_t b) {
    asm volatile("st.relaxed.gpu.global.v2.u32 [%0], {%1,%2};" ::"l"(p), "r"(a), "r"(b) : "memory");
}
__device__ __forceinline__ void cp_async16(uint32_t dst, const void* src) {
    asm volatile("cp.async.cg.shared.global [%0], [%1], 16;" ::"r"(dst), "l"(src) : "memory");
}
__device__ __forceinline__ void cp_async_commit() { asm volatile("cp.async.commit_group;" ::: "memory"); }
template <int N> __device__ __forceinline__ void cp_async_wait() { asm volatile("cp.async.wait_group %0;" ::"n"(N) : "memory"); }

#define PROF(i) do {} while (0)
constexpr int SPIN_LIMIT = 4000000;

__device__ __forceinline__ uint4 poll_ll(const void* p, uint32_t flag) {
    uint4 v = ld_relaxed_v4(p);
    int n = 0;
    while ((v.y != flag || v.w != flag) && ++n < SPIN_LIMIT) {
        v = ld_relaxed_v4(p);
    }
    return v;
}

constexpr int RT = 512;
constexpr int MEMS_LD = D_ + 8;
constexpr int HL = DH_ + 8;
struct RecurSmem {
    bf16 mem[MEM_][MEMS_LD];
    bf16 kall[2][48][HL];
    bf16 vall[2][48][HL];
    bf16 qm[16][HL];
    float sc[MEM_][40];
    bf16 p[MEM_][48 + 8];
    bf16 om[MEM_][HL];
    float red[12][16 * 8];
    float wred[2][5][16 * 8];
};

__device__ __forceinline__ void bar_sync(int id, int n) { asm volatile("bar.sync %0, %1;" ::"r"(id), "r"(n) : "memory"); }
__device__ __forceinline__ void bar_arrive(int id, int n) { asm volatile("bar.arrive %0, %1;" ::"r"(id), "r"(n) : "memory"); }
__device__ __forceinline__ void sts64(uint32_t a, uint32_t x, uint32_t y) { asm volatile("st.shared.v2.u32 [%0], {%1,%2};" ::"r"(a), "r"(x), "r"(y) : "memory"); }
__device__ __forceinline__ uint32_t ldg_u16x2(const bf16* p0, const bf16* p1) {
    return (uint32_t)*(const uint16_t*)p0 | ((uint32_t)*(const uint16_t*)p1 << 16);
}
enum { BAR_MEM = 1, BAR_RED = 2, BAR_CTL = 3, BAR_WO = 4 };

__global__ void __launch_bounds__(RT, 1)
recur_kernel(const bf16* __restrict__ mem0, const bf16* __restrict__ Wq, const bf16* __restrict__ Wk,
             const bf16* __restrict__ Wv, const bf16* __restrict__ Wo) {
    extern __shared__ __align__(16) uint8_t smem_raw[];
    RecurSmem& sm = *reinterpret_cast<RecurSmem*>(smem_raw);
    const int tid = threadIdx.x, lane = tid & 31, w = tid >> 5;
    const int g = lane >> 2, t = lane & 3;
    const int h = blockIdx.x >> 2, c = blockIdx.x & 3;

    for (int i = tid; i < 2 * 8 * HL; i += RT) {
        int b = i / (8 * HL), r = (i / HL) % 8, cc = i % HL;
        sm.kall[b][40 + r][cc] = __float2bfloat16(0.f);
        sm.vall[b][40 + r][cc] = __float2bfloat16(0.f);
    }
    for (int i = tid; i < 8 * HL; i += RT) sm.qm[8 + i / HL][i % HL] = __float2bfloat16(0.f);
    for (int i = tid; i < 8 * 56; i += RT) sm.p[i / 56][i % 56] = __float2bfloat16(0.f);
    __syncthreads();

    if (w < 12) {
        asm volatile("setmaxnreg.dec.sync.aligned.u32 104;");
        uint32_t wf[20][4];
        const int mt = w % 6, kh = w / 6;
        {
            const bf16* W = (mt < 2) ? Wq : (mt < 4 ? Wk : Wv);
            int f0 = h * DH_ + c * 32 + (mt & 1) * 16;
#pragma unroll
            for (int i = 0; i < 20; i++) {
                int k0 = (kh * 20 + i) * 16;
                const bf16* p0 = W + (size_t)(k0 + 2 * t) * HD_ + f0 + g;
                wf[i][0] = ldg_u16x2(p0, p0 + HD_);
                wf[i][1] = ldg_u16x2(p0 + 8, p0 + HD_ + 8);
                wf[i][2] = ldg_u16x2(p0 + 8 * HD_, p0 + 9 * HD_);
                wf[i][3] = ldg_u16x2(p0 + 8 * HD_ + 8, p0 + 9 * HD_ + 8);
            }
        }
        const uint32_t base = smem_u32(&sm.mem[lane & 7][kh * 320 + (lane >> 3) * 8]);
        const uint32_t rp = smem_u32(&sm.red[w][g * 8 + 2 * t]);
        for (int s = 0; s < NSEG_; s++) {
            bar_sync(BAR_MEM, RT);
            float a0[4] = {0.f, 0.f, 0.f, 0.f}, a1[4] = {0.f, 0.f, 0.f, 0.f};
#pragma unroll
            for (int i = 0; i < 10; i++) {
                uint32_t b[4];
                ldsm_x4(b, base + i * 64);
                mma16816(a0, wf[2 * i], b[0], b[1]);
                mma16816(a1, wf[2 * i + 1], b[2], b[3]);
            }
            sts64(rp, __float_as_uint(a0[0] + a1[0]), __float_as_uint(a0[1] + a1[1]));
            sts64(rp + 256, __float_as_uint(a0[2] + a1[2]), __float_as_uint(a0[3] + a1[3]));
            bar_arrive(BAR_RED, RT);
        }
    } else {
        asm volatile("setmaxnreg.inc.sync.aligned.u32 200;");
        const int ct = tid - 384, cw = w - 12;
        const int mg = cw >> 1, kh = cw & 1;
        uint32_t wf[20][4];
#pragma unroll
        for (int mi = 0; mi < 5; mi++)
#pragma unroll
            for (int ki = 0; ki < 4; ki++) {
                int col0 = c * 160 + (mg * 5 + mi) * 16;
                int e0 = h * DH_ + (kh * 4 + ki) * 16;
                const bf16* p0 = Wo + (size_t)(e0 + 2 * t) * D_ + col0 + g;
                int i = mi * 4 + ki;
                wf[i][0] = ldg_u16x2(p0, p0 + D_);
                wf[i][1] = ldg_u16x2(p0 + 8, p0 + D_ + 8);
                wf[i][2] = ldg_u16x2(p0 + 8 * D_, p0 + 9 * D_);
                wf[i][3] = ldg_u16x2(p0 + 8 * D_ + 8, p0 + 9 * D_ + 8);
            }
        constexpr uint32_t KV_BUF = 48 * HL * 2;
        const bf16* kv_src = g_qkv + (size_t)(ct >> 4) * (3 * HD_) + HD_ + h * DH_ + (ct & 15) * 8;
        const uint32_t kv_dst0 = smem_u32(&sm.kall[0][MEM_ + (ct >> 4)][(ct & 15) * 8]);
        const uint32_t kv_dst1 = smem_u32(&sm.vall[0][MEM_ + (ct >> 4)][(ct & 15) * 8]);
        auto prefetch_kv = [&](int s, int buf) {
            const bf16* src = kv_src + (size_t)s * SEG_ * (3 * HD_);
#pragma unroll
            for (int j = 0; j < 4; j++) {
                cp_async16(kv_dst0 + buf * KV_BUF + j * (8 * HL * 2), src + (size_t)j * 8 * (3 * HD_));
                cp_async16(kv_dst1 + buf * KV_BUF + j * (8 * HL * 2), src + (size_t)j * 8 * (3 * HD_) + HD_);
            }
            cp_async_commit();
        };
        const float4* acc_src = reinterpret_cast<const float4*>(g_acc) + ct;
        const uint32_t acc_dst = smem_u32(&sm.mem[(ct & 1) * 4][ct >> 1]);
        const uint4* hx_base = reinterpret_cast<const uint4*>(g_hx) + h * 1024;
        const int hx_rq = ct & 63, hx_half = ct >> 6;
        const uint4* hx_src = hx_base + hx_half * 64 + hx_rq;
        const uint32_t hx_col = (hx_rq & 7) * 8, hx_r = hx_rq >> 3;
        const uint32_t hx_dstA = (hx_half == 0 ? smem_u32(&sm.qm[hx_r][0]) : smem_u32(&sm.kall[0][hx_r][0])) + hx_col;
        const uint32_t hx_dstB = smem_u32(&sm.vall[0][hx_r][0]) + hx_col;
        const uint4* hx_probe = hx_base + (lane >> 3) * 256 + ((lane & 7) % 3) * 64 + (lane & 7) * 8 + 3;
        const int pb_r = ct >> 4, pb_pr = ct & 15;
        uint2* pb_dst = g_hx + (h * 1024 + c * 256 + pb_r * 8) * 2 + pb_pr;
        const float* pb_src = &sm.red[pb_pr >> 3][(pb_pr & 7) * 16 + pb_r];
        bf16* pb_k = g_kmem + (size_t)pb_r * HD_ + h * DH_ + c * 32 + pb_pr * 2;
        bf16* pb_v = g_vmem + (size_t)pb_r * HD_ + h * DH_ + c * 32 + pb_pr * 2;
        const uint32_t qa = smem_u32(&sm.qm[lane & 15][(lane >> 4) * 8]);
        const uint32_t kb0 = smem_u32(&sm.kall[0][cw * 8 + (lane & 7)][(lane >> 3) * 8]);
        const uint32_t va0 = smem_u32(&sm.vall[0][(lane & 7) + ((lane >> 4) & 1) * 8][cw * 32 + ((lane >> 3) & 1) * 8]);
        const uint32_t pbaddr = smem_u32(&sm.p[lane & 7][((lane >> 3) & 1) * 8]);
        const uint32_t ob = smem_u32(&sm.om[lane & 7][kh * 64 + (lane >> 3) * 8]);
        float* acc_dst_g = g_acc + (c * 160 + mg * 80 + g) * 8 + 2 * t;

        prefetch_kv(0, 0);
        for (int s = 0; s < NSEG_; s++) {
            const int buf = s & 1;
            const uint32_t flag = s + 1;
            const uint32_t bo = buf * KV_BUF;
            PROF(0);
            if (s == 0) {
                for (int i = ct; i < MEM_ * D_ / 8; i += 128) {
                    int r = i / (D_ / 8), cc = (i % (D_ / 8)) * 8;
                    *reinterpret_cast<uint4*>(&sm.mem[r][cc]) = *reinterpret_cast<const uint4*>(mem0 + r * D_ + cc);
                }
            } else {
                if (ct == 0) {
                    const unsigned* cp = g_cnt + (s - 1) * 32;
                    unsigned v; int n = 0;
                    do { asm volatile("ld.acquire.gpu.global.u32 %0, [%1];" : "=r"(v) : "l"(cp) : "memory"); } while (v < 256u && ++n < SPIN_LIMIT);
                }
                bar_sync(BAR_CTL, 128);
                PROF(1);
                const float4* src = acc_src + (size_t)(s - 1) * (MEM_ * D_ / 4);
                float4 v[10];
#pragma unroll
                for (int j = 0; j < 10; j++)
                    asm volatile("ld.relaxed.gpu.global.v4.f32 {%0,%1,%2,%3}, [%4];" : "=f"(v[j].x), "=f"(v[j].y), "=f"(v[j].z), "=f"(v[j].w) : "l"(src + 128 * j) : "memory");
#pragma unroll
                for (int j = 0; j < 10; j++) {
                    uint32_t lo = pack_bf16(v[j].x, v[j].y), hi = pack_bf16(v[j].z, v[j].w);
                    uint32_t d = acc_dst + j * 128;
                    asm volatile("st.shared.u16 [%0], %1;" ::"r"(d), "h"((uint16_t)(lo & 0xffff)) : "memory");
                    asm volatile("st.shared.u16 [%0], %1;" ::"r"(d + MEMS_LD * 2), "h"((uint16_t)(lo >> 16)) : "memory");
                    asm volatile("st.shared.u16 [%0], %1;" ::"r"(d + MEMS_LD * 4), "h"((uint16_t)(hi & 0xffff)) : "memory");
                    asm volatile("st.shared.u16 [%0], %1;" ::"r"(d + MEMS_LD * 6), "h"((uint16_t)(hi >> 16)) : "memory");
                }
            }
            bar_arrive(BAR_MEM, RT);
            PROF(2);
            bar_sync(BAR_RED, RT);
            PROF(3);
            {
                uint32_t pk0 = pack_bf16(pb_src[0] + pb_src[768], pb_src[8] + pb_src[768 + 8]);
                uint32_t pk1 = pack_bf16(pb_src[256] + pb_src[1024], pb_src[256 + 8] + pb_src[1024 + 8]);
                uint32_t pk2 = pack_bf16(pb_src[512] + pb_src[1280], pb_src[512 + 8] + pb_src[1280 + 8]);
                st_relaxed_v2(pb_dst, pk0, flag);
                st_relaxed_v2(pb_dst + 128, pk1, flag);
                st_relaxed_v2(pb_dst + 256, pk2, flag);
                *reinterpret_cast<uint32_t*>(pb_k + (size_t)s * (MEM_ * HD_)) = pk1;
                *reinterpret_cast<uint32_t*>(pb_v + (size_t)s * (MEM_ * HD_)) = pk2;
            }
            if (s == NSEG_ - 1) break;
            PROF(4);
            if (cw == 0) (void)poll_ll(hx_probe, flag);
            bar_sync(BAR_CTL, 128);
            PROF(5);
            {
                uint4 v[8];
#pragma unroll
                for (int j = 0; j < 4; j++) v[j] = ld_relaxed_v4(hx_src + j * 256);
                if (hx_half == 0) {
#pragma unroll
                    for (int j = 0; j < 4; j++) v[4 + j] = ld_relaxed_v4(hx_src + j * 256 + 128);
                }
#pragma unroll
                for (int j = 0; j < 4; j++) {
                    if (v[j].y != flag || v[j].w != flag) v[j] = poll_ll(hx_src + j * 256, flag);
                    sts64(hx_dstA + j * 64 + (hx_half ? bo : 0), v[j].x, v[j].z);
                }
                if (hx_half == 0) {
#pragma unroll
                    for (int j = 0; j < 4; j++) {
                        if (v[4 + j].y != flag || v[4 + j].w != flag) v[4 + j] = poll_ll(hx_src + j * 256 + 128, flag);
                        sts64(hx_dstB + j * 64 + bo, v[4 + j].x, v[4 + j].z);
                    }
                }
            }
            cp_async_wait<0>();
            bar_sync(BAR_CTL, 128);
            PROF(6);
            {
                uint32_t a[8][4], b[4][4], b2[4][4];
#pragma unroll
                for (int kk = 0; kk < 4; kk++) ldsm_x4(b[kk], kb0 + bo + kk * 64);
                if (cw == 0) {
#pragma unroll
                    for (int kk = 0; kk < 4; kk++) ldsm_x4(b2[kk], kb0 + bo + 32 * HL * 2 + kk * 64);
                }
#pragma unroll
                for (int kk = 0; kk < 8; kk++) ldsm_x4(a[kk], qa + kk * 32);
                float s0[4] = {0.f, 0.f, 0.f, 0.f}, s1[4] = {0.f, 0.f, 0.f, 0.f};
#pragma unroll
                for (int kk = 0; kk < 4; kk++) { mma16816(s0, a[2 * kk], b[kk][0], b[kk][1]); mma16816(s1, a[2 * kk + 1], b[kk][2], b[kk][3]); }
                const float scale = 0.08838834764831845f;
                *reinterpret_cast<float2*>(&sm.sc[g][cw * 8 + 2 * t]) =
                    make_float2(rbf(rbf(s0[0] + s1[0]) * scale), rbf(rbf(s0[1] + s1[1]) * scale));
                if (cw == 0) {
                    float u0[4] = {0.f, 0.f, 0.f, 0.f}, u1[4] = {0.f, 0.f, 0.f, 0.f};
#pragma unroll
                    for (int kk = 0; kk < 4; kk++) { mma16816(u0, a[2 * kk], b2[kk][0], b2[kk][1]); mma16816(u1, a[2 * kk + 1], b2[kk][2], b2[kk][3]); }
                    *reinterpret_cast<float2*>(&sm.sc[g][32 + 2 * t]) =
                        make_float2(rbf(rbf(u0[0] + u1[0]) * scale), rbf(rbf(u0[1] + u1[1]) * scale));
                }
            }
            bar_sync(BAR_CTL, 128);
            {
                float v0 = sm.sc[cw][lane], v1 = (lane < 8) ? sm.sc[cw][32 + lane] : -INFINITY;
                float y0 = sm.sc[cw + 4][lane], y1 = (lane < 8) ? sm.sc[cw + 4][32 + lane] : -INFINITY;
                float mx = fmaxf(v0, v1), my = fmaxf(y0, y1);
#pragma unroll
                for (int o = 16; o; o >>= 1) { mx = fmaxf(mx, __shfl_xor_sync(0xffffffffu, mx, o)); my = fmaxf(my, __shfl_xor_sync(0xffffffffu, my, o)); }
                float e0 = __expf(v0 - mx), e1 = (lane < 8) ? __expf(v1 - mx) : 0.f;
                float f0 = __expf(y0 - my), f1 = (lane < 8) ? __expf(y1 - my) : 0.f;
                float sx = e0 + e1, sy = f0 + f1;
#pragma unroll
                for (int o = 16; o; o >>= 1) { sx += __shfl_xor_sync(0xffffffffu, sx, o); sy += __shfl_xor_sync(0xffffffffu, sy, o); }
                float ix = 1.0f / sx, iy = 1.0f / sy;
                sm.p[cw][lane] = __float2bfloat16_rn(e0 * ix);
                sm.p[cw + 4][lane] = __float2bfloat16_rn(f0 * iy);
                if (lane < 8) { sm.p[cw][32 + lane] = __float2bfloat16_rn(e1 * ix); sm.p[cw + 4][32 + lane] = __float2bfloat16_rn(f1 * iy); }
            }
            bar_sync(BAR_CTL, 128);
            PROF(7);
            {
                uint32_t a[2][3][4], b[3][2];
#pragma unroll
                for (int kt = 0; kt < 3; kt++) {
                    asm volatile("ldmatrix.sync.aligned.m8n8.x2.shared.b16 {%0,%1}, [%2];" : "=r"(b[kt][0]), "=r"(b[kt][1]) : "r"(pbaddr + kt * 32));
                    ldsm_x4_t(a[0][kt], va0 + bo + kt * 16 * HL * 2);
                    ldsm_x4_t(a[1][kt], va0 + bo + kt * 16 * HL * 2 + 32);
                }
#pragma unroll
                for (int m = 0; m < 2; m++) {
                    float o[4] = {0.f, 0.f, 0.f, 0.f};
#pragma unroll
                    for (int kt = 0; kt < 3; kt++) mma16816(o, a[m][kt], b[kt][0], b[kt][1]);
                    int d0 = cw * 32 + m * 16 + g;
                    sm.om[2 * t][d0] = __float2bfloat16_rn(o[0]);
                    sm.om[2 * t + 1][d0] = __float2bfloat16_rn(o[1]);
                    sm.om[2 * t][d0 + 8] = __float2bfloat16_rn(o[2]);
                    sm.om[2 * t + 1][d0 + 8] = __float2bfloat16_rn(o[3]);
                }
            }
            bar_sync(BAR_CTL, 128);
            PROF(8);
            {
                float acc[5][4];
#pragma unroll
                for (int mi = 0; mi < 5; mi++) { acc[mi][0] = acc[mi][1] = acc[mi][2] = acc[mi][3] = 0.f; }
                uint32_t b[2][4];
                ldsm_x4(b[0], ob); ldsm_x4(b[1], ob + 64);
#pragma unroll
                for (int ki = 0; ki < 4; ki++)
#pragma unroll
                    for (int mi = 0; mi < 5; mi++) mma16816(acc[mi], wf[mi * 4 + ki], b[ki >> 1][(ki & 1) * 2], b[ki >> 1][(ki & 1) * 2 + 1]);
                if (kh == 1) {
#pragma unroll
                    for (int mi = 0; mi < 5; mi++)
                        *reinterpret_cast<float4*>(&sm.wred[mg][mi][lane * 4]) = make_float4(acc[mi][0], acc[mi][1], acc[mi][2], acc[mi][3]);
                }
                bar_sync(BAR_WO + mg, 64);
                if (kh == 0) {
                    float* dst = acc_dst_g + (size_t)s * (MEM_ * D_);
#pragma unroll
                    for (int mi = 0; mi < 5; mi++) {
                        float4 o2 = *reinterpret_cast<float4*>(&sm.wred[mg][mi][lane * 4]);
                        asm volatile("red.global.add.v2.f32 [%0], {%1,%2};" ::"l"(dst + mi * 128), "f"(acc[mi][0] + o2.x), "f"(acc[mi][1] + o2.y) : "memory");
                        asm volatile("red.global.add.v2.f32 [%0], {%1,%2};" ::"l"(dst + mi * 128 + 64), "f"(acc[mi][2] + o2.z), "f"(acc[mi][3] + o2.w) : "memory");
                    }
                    __threadfence();
                    __syncwarp();
                    if (lane == 0) atomicAdd(&g_cnt[s * 32], 1u);
                }
            }
            PROF(9);
            prefetch_kv(s + 1, buf ^ 1);
            PROF(10);
        }
    }
}

__global__ void __launch_bounds__(128)
attn_x_kernel() {
    __shared__ __align__(16) bf16 sq[32][HL], sk[48][HL], sv[48][HL];
    const int s = blockIdx.x >> 5, h = blockIdx.x & 31;
    const int tid = threadIdx.x, lane = tid & 31, w = tid >> 5, g = lane >> 2, t = lane & 3;
    for (int i = tid; i < (32 + 40 + 40) * 16; i += 128) {
        int r = i >> 4, ch = i & 15;
        const bf16* src; bf16* dst;
        if (r < 32) { src = g_qkv + (size_t)(s * SEG_ + r) * (3 * HD_) + h * DH_; dst = sq[r]; }
        else if (r < 72) { int rr = r - 32; dst = sk[rr];
            src = rr < 8 ? g_kmem + ((size_t)s * MEM_ + rr) * HD_ + h * DH_ : g_qkv + (size_t)(s * SEG_ + rr - 8) * (3 * HD_) + HD_ + h * DH_; }
        else { int rr = r - 72; dst = sv[rr];
            src = rr < 8 ? g_vmem + ((size_t)s * MEM_ + rr) * HD_ + h * DH_ : g_qkv + (size_t)(s * SEG_ + rr - 8) * (3 * HD_) + 2 * HD_ + h * DH_; }
        *reinterpret_cast<uint4*>(dst + ch * 8) = *reinterpret_cast<const uint4*>(src + ch * 8);
    }
    for (int i = tid; i < 8 * 16; i += 128) *reinterpret_cast<uint4*>(&sv[40 + (i >> 4)][(i & 15) * 8]) = make_uint4(0, 0, 0, 0);
    __syncthreads();
    const int rh = w & 1, dhh = w >> 1;
    float sc[5][4];
#pragma unroll
    for (int n = 0; n < 5; n++) sc[n][0] = sc[n][1] = sc[n][2] = sc[n][3] = 0.f;
#pragma unroll
    for (int kk = 0; kk < 8; kk++) {
        uint32_t a[4];
        ldsm_x4(a, smem_u32(&sq[rh * 16 + (lane & 15)][kk * 16 + (lane >> 4) * 8]));
#pragma unroll
        for (int n = 0; n < 5; n++) {
            uint32_t b[2];
            asm volatile("ldmatrix.sync.aligned.m8n8.x2.shared.b16 {%0,%1}, [%2];" : "=r"(b[0]), "=r"(b[1])
                         : "r"(smem_u32(&sk[n * 8 + (lane & 7)][kk * 16 + ((lane >> 3) & 1) * 8])));
            mma16816(sc[n], a, b[0], b[1]);
        }
    }
    const float scale = 0.08838834764831845f;
    float mx[2] = {-INFINITY, -INFINITY};
#pragma unroll
    for (int n = 0; n < 5; n++)
#pragma unroll
        for (int e = 0; e < 4; e++) {
            int row = rh * 16 + g + (e >> 1) * 8, key = n * 8 + 2 * t + (e & 1);
            float v = rbf(rbf(sc[n][e]) * scale);
            if (key > row + MEM_) v = -INFINITY;
            sc[n][e] = v;
            mx[e >> 1] = fmaxf(mx[e >> 1], v);
        }
#pragma unroll
    for (int o = 1; o < 4; o <<= 1) { mx[0] = fmaxf(mx[0], __shfl_xor_sync(0xffffffffu, mx[0], o)); mx[1] = fmaxf(mx[1], __shfl_xor_sync(0xffffffffu, mx[1], o)); }
    float sum[2] = {0.f, 0.f};
#pragma unroll
    for (int n = 0; n < 5; n++)
#pragma unroll
        for (int e = 0; e < 4; e++) { float ev = __expf(sc[n][e] - mx[e >> 1]); sc[n][e] = ev; sum[e >> 1] += ev; }
#pragma unroll
    for (int o = 1; o < 4; o <<= 1) { sum[0] += __shfl_xor_sync(0xffffffffu, sum[0], o); sum[1] += __shfl_xor_sync(0xffffffffu, sum[1], o); }
    float inv[2] = {1.0f / sum[0], 1.0f / sum[1]};
    uint32_t pa[3][4];
#pragma unroll
    for (int kt = 0; kt < 3; kt++) {
        pa[kt][0] = pack_bf16(sc[2 * kt][0] * inv[0], sc[2 * kt][1] * inv[0]);
        pa[kt][1] = pack_bf16(sc[2 * kt][2] * inv[1], sc[2 * kt][3] * inv[1]);
        if (kt < 2) {
            pa[kt][2] = pack_bf16(sc[2 * kt + 1][0] * inv[0], sc[2 * kt + 1][1] * inv[0]);
            pa[kt][3] = pack_bf16(sc[2 * kt + 1][2] * inv[1], sc[2 * kt + 1][3] * inv[1]);
        } else { pa[kt][2] = 0u; pa[kt][3] = 0u; }
    }
#pragma unroll
    for (int n = 0; n < 8; n++) {
        float o[4] = {0.f, 0.f, 0.f, 0.f};
#pragma unroll
        for (int kt = 0; kt < 3; kt++) {
            uint32_t b[2];
            asm volatile("ldmatrix.sync.aligned.m8n8.x2.trans.shared.b16 {%0,%1}, [%2];" : "=r"(b[0]), "=r"(b[1])
                         : "r"(smem_u32(&sv[kt * 16 + (lane & 15)][dhh * 64 + n * 8])));
            mma16816(o, pa[kt], b[0], b[1]);
        }
        int row = s * SEG_ + rh * 16 + g;
        bf16* dst = g_o + (size_t)row * HD_ + h * DH_ + dhh * 64 + n * 8 + 2 * t;
        *reinterpret_cast<uint32_t*>(dst) = pack_bf16(o[0], o[1]);
        *reinterpret_cast<uint32_t*>(dst + 8 * HD_) = pack_bf16(o[2], o[3]);
    }
}

typedef CUresult (*PFN_encodeTiled)(CUtensorMap*, CUtensorMapDataType, cuuint32_t, void*, const cuuint64_t*,
                                    const cuuint64_t*, const cuuint32_t*, const cuuint32_t*, CUtensorMapInterleave,
                                    CUtensorMapSwizzle, CUtensorMapL2promotion, CUtensorMapFloatOOBfill);
static PFN_encodeTiled p_encode = nullptr;

static CUtensorMap make_map(const void* ptr, uint64_t rows, uint64_t cols, uint64_t ld, uint32_t box_rows) {
    CUtensorMap m;
    cuuint64_t dims[2] = {cols, rows};
    cuuint64_t strides[1] = {ld * 2};
    cuuint32_t box[2] = {64, box_rows};
    cuuint32_t es[2] = {1, 1};
    p_encode(&m, CU_TENSOR_MAP_DATA_TYPE_BFLOAT16, 2, const_cast<void*>(ptr), dims, strides, box, es,
             CU_TENSOR_MAP_INTERLEAVE_NONE, CU_TENSOR_MAP_SWIZZLE_128B, CU_TENSOR_MAP_L2_PROMOTION_L2_128B,
             CU_TENSOR_MAP_FLOAT_OOB_FILL_NONE);
    return m;
}

template <int BN, int EPI>
static void launch_gemm(const CUtensorMap& a, const CUtensorMap& b0, const CUtensorMap& b1, const CUtensorMap& b2,
                        int nPerB, int M, int N, int K, EpiParams ep, cudaStream_t st) {
    constexpr int STAGE = 16384 + (BN / 64) * 8192;
    constexpr int NST = (200 * 1024) / STAGE;
    constexpr int SMEM = NST * STAGE + 1024;
    cudaFuncSetAttribute(gemm_kernel<BN, EPI>, cudaFuncAttributeMaxDynamicSharedMemorySize, SMEM);
    dim3 grid((N + BN - 1) / BN, M / 128);
    gemm_kernel<BN, EPI><<<grid, 384, SMEM, st>>>(a, b0, b1, b2, nPerB, N, K, ep);
}

extern "C" void kernel_launch(void* const* d_in, const int* in_sizes, int n_in, void* d_out, int out_size) {
    const bf16* x    = (const bf16*)d_in[0];
    const bf16* mem0 = (const bf16*)d_in[1];
    const bf16* Wq   = (const bf16*)d_in[2];
    const bf16* Wk   = (const bf16*)d_in[3];
    const bf16* Wv   = (const bf16*)d_in[4];
    const bf16* Wo   = (const bf16*)d_in[5];
    const bf16* w_in  = (const bf16*)d_in[8];
    const bf16* w_sp  = (const bf16*)d_in[9];
    const bf16* b_sp  = (const bf16*)d_in[10];
    const bf16* w_out = (const bf16*)d_in[11];
    bf16* out = (bf16*)d_out;
    cudaStream_t st = cudaStreamPerThread;

    if (!p_encode) {
        cudaDriverEntryPointQueryResult qr;
        cudaGetDriverEntryPoint("cuTensorMapEncodeTiled", (void**)&p_encode, cudaEnableDefault, &qr);
    }
    void *p_xn, *p_qkv, *p_z, *p_zg, *p_gate, *p_o, *p_acc, *p_cnt, *p_hx;
    cudaGetSymbolAddress(&p_xn, g_xn); cudaGetSymbolAddress(&p_qkv, g_qkv); cudaGetSymbolAddress(&p_z, g_z);
    cudaGetSymbolAddress(&p_zg, g_zg); cudaGetSymbolAddress(&p_gate, g_gate); cudaGetSymbolAddress(&p_o, g_o);
    cudaGetSymbolAddress(&p_acc, g_acc); cudaGetSymbolAddress(&p_cnt, g_cnt); cudaGetSymbolAddress(&p_hx, g_hx);

    CUtensorMap mA_xn  = make_map(p_xn, S_, D_, D_, 128);
    CUtensorMap mA_wsp = make_map(w_sp, S_, S_, S_, 128);
    CUtensorMap mA_zg  = make_map(p_zg, S_, FH_, FH_, 128);
    CUtensorMap mA_o   = make_map(p_o, S_, HD_, HD_, 128);
    CUtensorMap mB_wq  = make_map(Wq, D_, HD_, HD_, 64);
    CUtensorMap mB_wk  = make_map(Wk, D_, HD_, HD_, 64);
    CUtensorMap mB_wv  = make_map(Wv, D_, HD_, HD_, 64);
    CUtensorMap mB_win = make_map(w_in, D_, F_, F_, 64);
    CUtensorMap mB_z2  = make_map((bf16*)p_z + FH_, S_, FH_, F_, 64);
    CUtensorMap mB_wout = make_map(w_out, FH_, D_, D_, 64);
    CUtensorMap mB_wo  = make_map(Wo, HD_, D_, D_, 64);

    cudaMemsetAsync(p_acc, 0, sizeof(float) * NSEG_ * MEM_ * D_, st);
    cudaMemsetAsync(p_cnt, 0, sizeof(unsigned) * NSEG_ * 32, st);
    cudaMemsetAsync(p_hx, 0, sizeof(uint2) * H_ * 4 * 256 * 2, st);

    ln_kernel<<<S_ / 8, 256, 0, st>>>(x);
    { EpiParams ep{(bf16*)p_qkv, 3 * HD_, nullptr, nullptr}; launch_gemm<256, EPI_STORE>(mA_xn, mB_wq, mB_wk, mB_wv, HD_, S_, 3 * HD_, D_, ep, st); }
    { EpiParams ep{(bf16*)p_z, F_, nullptr, nullptr}; launch_gemm<128, EPI_GELU>(mA_xn, mB_win, mB_win, mB_win, 1 << 20, S_, F_, D_, ep, st); }
    ln2_kernel<<<S_ / 8, 256, 0, st>>>();
    { EpiParams ep{(bf16*)p_zg, FH_, (const bf16*)p_z, b_sp}; launch_gemm<128, EPI_SP>(mA_wsp, mB_z2, mB_z2, mB_z2, 1 << 20, S_, FH_, S_, ep, st); }
    { EpiParams ep{(bf16*)p_gate, D_, nullptr, nullptr}; launch_gemm<128, EPI_SILU>(mA_zg, mB_wout, mB_wout, mB_wout, 1 << 20, S_, D_, FH_, ep, st); }
    cudaFuncSetAttribute(recur_kernel, cudaFuncAttributeMaxDynamicSharedMemorySize, (int)sizeof(RecurSmem));
    recur_kernel<<<128, RT, sizeof(RecurSmem), st>>>(mem0, Wq, Wk, Wv, Wo);
    attn_x_kernel<<<NSEG_ * H_, 128, 0, st>>>();
    { EpiParams ep{out, D_, x, (const bf16*)p_gate}; launch_gemm<128, EPI_FINAL>(mA_o, mB_wo, mB_wo, mB_wo, 1 << 20, S_, D_, HD_, ep, st); }
}
```

```cpp
#include <cuda_runtime.h>
#include <cuda_bf16.h>
#include <cuda.h>
#include <stdint.h>

typedef __nv_bfloat16 bf16;

constexpr int S_   = 2048;
constexpr int D_   = 640;
constexpr int H_   = 32;
constexpr int DH_  = 128;
constexpr int MEM_ = 8;
constexpr int SEG_ = 32;
constexpr int NSEG_ = S_ / SEG_;
constexpr int HD_  = H_ * DH_;
constexpr int F_   = 1728;
constexpr int FH_  = 864;

__device__ bf16 g_xn[S_ * D_];
__device__ bf16 g_qkv[(size_t)S_ * 3 * HD_];
__device__ bf16 g_z[S_ * F_];
__device__ bf16 g_zg[S_ * FH_];
__device__ bf16 g_gate[S_ * D_];
__device__ bf16 g_kmem[NSEG_ * MEM_ * HD_];
__device__ bf16 g_vmem[NSEG_ * MEM_ * HD_];
__device__ bf16 g_o[(size_t)S_ * HD_];
__device__ float g_acc[NSEG_ * MEM_ * D_];
__device__ unsigned g_cnt[NSEG_ * 32];
__device__ uint2 g_hx[H_ * 4 * 256 * 2];

__device__ __forceinline__ uint32_t smem_u32(const void* p) { return (uint32_t)__cvta_generic_to_shared(p); }
__device__ __forceinline__ float bf2f(bf16 v) { return __bfloat162float(v); }
__device__ __forceinline__ float rbf(float v) { return __bfloat162float(__float2bfloat16_rn(v)); }
__device__ __forceinline__ uint32_t pack_bf16(float lo, float hi) {
    __nv_bfloat162 t = __floats2bfloat162_rn(lo, hi);
    return *reinterpret_cast<uint32_t*>(&t);
}
__device__ __forceinline__ float lo_f(uint32_t u) { return __uint_as_float(u << 16); }
__device__ __forceinline__ float hi_f(uint32_t u) { return __uint_as_float(u & 0xffff0000u); }

__device__ __forceinline__ void mbar_init(uint32_t bar, uint32_t cnt) {
    asm volatile("mbarrier.init.shared.b64 [%0], %1;" ::"r"(bar), "r"(cnt));
}
__device__ __forceinline__ void mbar_expect_tx(uint32_t bar, uint32_t bytes) {
    asm volatile("mbarrier.arrive.expect_tx.shared.b64 _, [%0], %1;" ::"r"(bar), "r"(bytes) : "memory");
}
__device__ __forceinline__ void mbar_arrive(uint32_t bar) {
    asm volatile("mbarrier.arrive.shared.b64 _, [%0];" ::"r"(bar) : "memory");
}
__device__ __forceinline__ void mbar_wait(uint32_t bar, uint32_t parity) {
    asm volatile(
        "{\n .reg .pred p;\n"
        "WAIT_%=:\n"
        " mbarrier.try_wait.parity.shared.b64 p, [%0], %1;\n"
        " @p bra DONE_%=;\n"
        " bra WAIT_%=;\n"
        "DONE_%=:\n}\n" ::"r"(bar), "r"(parity) : "memory");
}
__device__ __forceinline__ void tma_load_2d(uint32_t dst, const CUtensorMap* tm, uint32_t bar, int c0, int c1) {
    asm volatile(
        "cp.async.bulk.tensor.2d.shared::cluster.global.mbarrier::complete_tx::bytes [%0], [%1, {%3, %4}], [%2];"
        ::"r"(dst), "l"(tm), "r"(bar), "r"(c0), "r"(c1) : "memory");
}
__device__ __forceinline__ void wgmma_fence() { asm volatile("wgmma.fence.sync.aligned;" ::: "memory"); }
__device__ __forceinline__ void wgmma_commit() { asm volatile("wgmma.commit_group.sync.aligned;" ::: "memory"); }
template <int N> __device__ __forceinline__ void wgmma_wait() { asm volatile("wgmma.wait_group.sync.aligned %0;" ::"n"(N) : "memory"); }

__device__ __forceinline__ uint64_t make_desc(uint32_t addr, uint32_t lbo, uint32_t sbo) {
    return (uint64_t)((addr & 0x3FFFF) >> 4) | ((uint64_t)(lbo >> 4) << 16) | ((uint64_t)(sbo >> 4) << 32) | (1ull << 62);
}

template <int N> struct Wgmma;
template <> struct Wgmma<128> {
    static __device__ __forceinline__ void mma(float* d, uint64_t da, uint64_t db, int sd) {
        asm volatile(
            "{\n.reg .pred p;\nsetp.ne.b32 p, %66, 0;\n"
            "wgmma.mma_async.sync.aligned.m64n128k16.f32.bf16.bf16 "
            "{%0,%1,%2,%3,%4,%5,%6,%7,%8,%9,%10,%11,%12,%13,%14,%15,"
            "%16,%17,%18,%19,%20,%21,%22,%23,%24,%25,%26,%27,%28,%29,%30,%31,"
            "%32,%33,%34,%35,%36,%37,%38,%39,%40,%41,%42,%43,%44,%45,%46,%47,"
            "%48,%49,%50,%51,%52,%53,%54,%55,%56,%57,%58,%59,%60,%61,%62,%63},"
            "%64,%65,p,1,1,0,1;\n}\n"
            : "+f"(d[0]), "+f"(d[1]), "+f"(d[2]), "+f"(d[3]), "+f"(d[4]), "+f"(d[5]), "+f"(d[6]), "+f"(d[7]),
              "+f"(d[8]), "+f"(d[9]), "+f"(d[10]), "+f"(d[11]), "+f"(d[12]), "+f"(d[13]), "+f"(d[14]), "+f"(d[15]),
              "+f"(d[16]), "+f"(d[17]), "+f"(d[18]), "+f"(d[19]), "+f"(d[20]), "+f"(d[21]), "+f"(d[22]), "+f"(d[23]),
              "+f"(d[24]), "+f"(d[25]), "+f"(d[26]), "+f"(d[27]), "+f"(d[28]), "+f"(d[29]), "+f"(d[30]), "+f"(d[31]),
              "+f"(d[32]), "+f"(d[33]), "+f"(d[34]), "+f"(d[35]), "+f"(d[36]), "+f"(d[37]), "+f"(d[38]), "+f"(d[39]),
              "+f"(d[40]), "+f"(d[41]), "+f"(d[42]), "+f"(d[43]), "+f"(d[44]), "+f"(d[45]), "+f"(d[46]), "+f"(d[47]),
              "+f"(d[48]), "+f"(d[49]), "+f"(d[50]), "+f"(d[51]), "+f"(d[52]), "+f"(d[53]), "+f"(d[54]), "+f"(d[55]),
              "+f"(d[56]), "+f"(d[57]), "+f"(d[58]), "+f"(d[59]), "+f"(d[60]), "+f"(d[61]), "+f"(d[62]), "+f"(d[63])
            : "l"(da), "l"(db), "r"(sd));
    }
};
template <> struct Wgmma<192> {
    static __device__ __forceinline__ void mma(float* d, uint64_t da, uint64_t db, int sd) {
        asm volatile(
            "{\n.reg .pred p;\nsetp.ne.b32 p, %98, 0;\n"
            "wgmma.mma_async.sync.aligned.m64n192k16.f32.bf16.bf16 "
            "{%0,%1,%2,%3,%4,%5,%6,%7,%8,%9,%10,%11,%12,%13,%14,%15,"
            "%16,%17,%18,%19,%20,%21,%22,%23,%24,%25,%26,%27,%28,%29,%30,%31,"
            "%32,%33,%34,%35,%36,%37,%38,%39,%40,%41,%42,%43,%44,%45,%46,%47,"
            "%48,%49,%50,%51,%52,%53,%54,%55,%56,%57,%58,%59,%60,%61,%62,%63,"
            "%64,%65,%66,%67,%68,%69,%70,%71,%72,%73,%74,%75,%76,%77,%78,%79,"
            "%80,%81,%82,%83,%84,%85,%86,%87,%88,%89,%90,%91,%92,%93,%94,%95},"
            "%96,%97,p,1,1,0,1;\n}\n"
            : "+f"(d[0]), "+f"(d[1]), "+f"(d[2]), "+f"(d[3]), "+f"(d[4]), "+f"(d[5]), "+f"(d[6]), "+f"(d[7]),
              "+f"(d[8]), "+f"(d[9]), "+f"(d[10]), "+f"(d[11]), "+f"(d[12]), "+f"(d[13]), "+f"(d[14]), "+f"(d[15]),
              "+f"(d[16]), "+f"(d[17]), "+f"(d[18]), "+f"(d[19]), "+f"(d[20]), "+f"(d[21]), "+f"(d[22]), "+f"(d[23]),
              "+f"(d[24]), "+f"(d[25]), "+f"(d[26]), "+f"(d[27]), "+f"(d[28]), "+f"(d[29]), "+f"(d[30]), "+f"(d[31]),
              "+f"(d[32]), "+f"(d[33]), "+f"(d[34]), "+f"(d[35]), "+f"(d[36]), "+f"(d[37]), "+f"(d[38]), "+f"(d[39]),
              "+f"(d[40]), "+f"(d[41]), "+f"(d[42]), "+f"(d[43]), "+f"(d[44]), "+f"(d[45]), "+f"(d[46]), "+f"(d[47]),
              "+f"(d[48]), "+f"(d[49]), "+f"(d[50]), "+f"(d[51]), "+f"(d[52]), "+f"(d[53]), "+f"(d[54]), "+f"(d[55]),
              "+f"(d[56]), "+f"(d[57]), "+f"(d[58]), "+f"(d[59]), "+f"(d[60]), "+f"(d[61]), "+f"(d[62]), "+f"(d[63]),
              "+f"(d[64]), "+f"(d[65]), "+f"(d[66]), "+f"(d[67]), "+f"(d[68]), "+f"(d[69]), "+f"(d[70]), "+f"(d[71]),
              "+f"(d[72]), "+f"(d[73]), "+f"(d[74]), "+f"(d[75]), "+f"(d[76]), "+f"(d[77]), "+f"(d[78]), "+f"(d[79]),
              "+f"(d[80]), "+f"(d[81]), "+f"(d[82]), "+f"(d[83]), "+f"(d[84]), "+f"(d[85]), "+f"(d[86]), "+f"(d[87]),
              "+f"(d[88]), "+f"(d[89]), "+f"(d[90]), "+f"(d[91]), "+f"(d[92]), "+f"(d[93]), "+f"(d[94]), "+f"(d[95])
            : "l"(da), "l"(db), "r"(sd));
    }
};

template <> struct Wgmma<256> {
    static __device__ __forceinline__ void mma(float* d, uint64_t da, uint64_t db, int sd) {
        asm volatile(
            "{\n.reg .pred p;\nsetp.ne.b32 p, %130, 0;\n"
            "wgmma.mma_async.sync.aligned.m64n256k16.f32.bf16.bf16 "
            "{%0,%1,%2,%3,%4,%5,%6,%7,%8,%9,%10,%11,%12,%13,%14,%15,%16,%17,%18,%19,%20,%21,%22,%23,%24,%25,%26,%27,%28,%29,%30,%31,%32,%33,%34,%35,%36,%37,%38,%39,%40,%41,%42,%43,%44,%45,%46,%47,%48,%49,%50,%51,%52,%53,%54,%55,%56,%57,%58,%59,%60,%61,%62,%63,%64,%65,%66,%67,%68,%69,%70,%71,%72,%73,%74,%75,%76,%77,%78,%79,%80,%81,%82,%83,%84,%85,%86,%87,%88,%89,%90,%91,%92,%93,%94,%95,%96,%97,%98,%99,%100,%101,%102,%103,%104,%105,%106,%107,%108,%109,%110,%111,%112,%113,%114,%115,%116,%117,%118,%119,%120,%121,%122,%123,%124,%125,%126,%127},"
            "%128,%129,p,1,1,0,1;\n}\n"
            : "+f"(d[0]), "+f"(d[1]), "+f"(d[2]), "+f"(d[3]), "+f"(d[4]), "+f"(d[5]), "+f"(d[6]), "+f"(d[7]), "+f"(d[8]), "+f"(d[9]), "+f"(d[10]), "+f"(d[11]), "+f"(d[12]), "+f"(d[13]), "+f"(d[14]), "+f"(d[15]), "+f"(d[16]), "+f"(d[17]), "+f"(d[18]), "+f"(d[19]), "+f"(d[20]), "+f"(d[21]), "+f"(d[22]), "+f"(d[23]), "+f"(d[24]), "+f"(d[25]), "+f"(d[26]), "+f"(d[27]), "+f"(d[28]), "+f"(d[29]), "+f"(d[30]), "+f"(d[31]), "+f"(d[32]), "+f"(d[33]), "+f"(d[34]), "+f"(d[35]), "+f"(d[36]), "+f"(d[37]), "+f"(d[38]), "+f"(d[39]), "+f"(d[40]), "+f"(d[41]), "+f"(d[42]), "+f"(d[43]), "+f"(d[44]), "+f"(d[45]), "+f"(d[46]), "+f"(d[47]), "+f"(d[48]), "+f"(d[49]), "+f"(d[50]), "+f"(d[51]), "+f"(d[52]), "+f"(d[53]), "+f"(d[54]), "+f"(d[55]), "+f"(d[56]), "+f"(d[57]), "+f"(d[58]), "+f"(d[59]), "+f"(d[60]), "+f"(d[61]), "+f"(d[62]), "+f"(d[63]), "+f"(d[64]), "+f"(d[65]), "+f"(d[66]), "+f"(d[67]), "+f"(d[68]), "+f"(d[69]), "+f"(d[70]), "+f"(d[71]), "+f"(d[72]), "+f"(d[73]), "+f"(d[74]), "+f"(d[75]), "+f"(d[76]), "+f"(d[77]), "+f"(d[78]), "+f"(d[79]), "+f"(d[80]), "+f"(d[81]), "+f"(d[82]), "+f"(d[83]), "+f"(d[84]), "+f"(d[85]), "+f"(d[86]), "+f"(d[87]), "+f"(d[88]), "+f"(d[89]), "+f"(d[90]), "+f"(d[91]), "+f"(d[92]), "+f"(d[93]), "+f"(d[94]), "+f"(d[95]), "+f"(d[96]), "+f"(d[97]), "+f"(d[98]), "+f"(d[99]), "+f"(d[100]), "+f"(d[101]), "+f"(d[102]), "+f"(d[103]), "+f"(d[104]), "+f"(d[105]), "+f"(d[106]), "+f"(d[107]), "+f"(d[108]), "+f"(d[109]), "+f"(d[110]), "+f"(d[111]), "+f"(d[112]), "+f"(d[113]), "+f"(d[114]), "+f"(d[115]), "+f"(d[116]), "+f"(d[117]), "+f"(d[118]), "+f"(d[119]), "+f"(d[120]), "+f"(d[121]), "+f"(d[122]), "+f"(d[123]), "+f"(d[124]), "+f"(d[125]), "+f"(d[126]), "+f"(d[127])
            : "l"(da), "l"(db), "r"(sd));
    }
};
template <int W>
__device__ __forceinline__ void ln_row(const bf16* __restrict__ src, bf16* __restrict__ dst, int lane) {
    constexpr int NP = W / 64;
    constexpr int REM = (W / 2) % 32;
    uint32_t v[NP + 1];
    const uint32_t* s32 = reinterpret_cast<const uint32_t*>(src);
    float sum = 0.f;
#pragma unroll
    for (int i = 0; i < NP; i++) { v[i] = s32[i * 32 + lane]; sum += lo_f(v[i]) + hi_f(v[i]); }
    if (REM) { v[NP] = (lane < REM) ? s32[NP * 32 + lane] : 0u; if (lane < REM) sum += lo_f(v[NP]) + hi_f(v[NP]); }
#pragma unroll
    for (int o = 16; o; o >>= 1) sum += __shfl_xor_sync(0xffffffffu, sum, o);
    float mean = sum * (1.0f / W);
    float vs = 0.f;
#pragma unroll
    for (int i = 0; i < NP; i++) { float a = lo_f(v[i]) - mean, b = hi_f(v[i]) - mean; vs += a * a + b * b; }
    if (REM && lane < REM) { float a = lo_f(v[NP]) - mean, b = hi_f(v[NP]) - mean; vs += a * a + b * b; }
#pragma unroll
    for (int o = 16; o; o >>= 1) vs += __shfl_xor_sync(0xffffffffu, vs, o);
    float var = rbf(vs * (1.0f / W));
    float mb = rbf(mean);
    float den = rbf(sqrtf(rbf(var + 1e-5f)));
    uint32_t* d32 = reinterpret_cast<uint32_t*>(dst);
#pragma unroll
    for (int i = 0; i < NP; i++) d32[i * 32 + lane] = pack_bf16(rbf(lo_f(v[i]) - mb) / den, rbf(hi_f(v[i]) - mb) / den);
    if (REM && lane < REM) d32[NP * 32 + lane] = pack_bf16(rbf(lo_f(v[NP]) - mb) / den, rbf(hi_f(v[NP]) - mb) / den);
}

__global__ void ln_kernel(const bf16* __restrict__ x) {
    int row = blockIdx.x * 8 + (threadIdx.x >> 5);
    ln_row<D_>(x + (size_t)row * D_, g_xn + (size_t)row * D_, threadIdx.x & 31);
}
__global__ void ln2_kernel() {
    int row = blockIdx.x * 8 + (threadIdx.x >> 5);
    bf16* p = g_z + (size_t)row * F_ + FH_;
    ln_row<FH_>(p, p, threadIdx.x & 31);
}

enum { EPI_STORE = 0, EPI_GELU = 1, EPI_SP = 2, EPI_SILU = 3, EPI_FINAL = 4 };
struct EpiParams {
    bf16* out; int ldo;
    const bf16* aux0;
    const bf16* aux1;
};

__device__ __forceinline__ float gelu_tanh_f(float x) {
    const float k0 = 0.7978845608028654f, k1 = 0.044715f;
    float inner = k0 * (x + k1 * x * x * x);
    return 0.5f * x * (1.0f + tanhf(inner));
}
__device__ __forceinline__ float silu_f(float x) { return x / (1.0f + expf(-x)); }

template <int BN, int EPI>
__global__ void __launch_bounds__(384, 1)
gemm_kernel(const __grid_constant__ CUtensorMap tmA, const __grid_constant__ CUtensorMap tmB0,
            const __grid_constant__ CUtensorMap tmB1, const __grid_constant__ CUtensorMap tmB2,
            int nPerB, int N, int K, EpiParams ep) {
    constexpr int BM = 128, BK = 64;
    constexpr int A_BYTES = BM * BK * 2;
    constexpr int B_BYTES = (BN / 64) * 8192;
    constexpr int STAGE = A_BYTES + B_BYTES;
    constexpr int NST = (200 * 1024) / STAGE;
    constexpr int OLD = BN + 8;
    extern __shared__ __align__(1024) uint8_t smem_raw[];
    uint8_t* smem = (uint8_t*)(((uintptr_t)smem_raw + 1023) & ~(uintptr_t)1023);
    __shared__ __align__(8) uint64_t full_bar[NST], empty_bar[NST];

    const int tid = threadIdx.x, wg = tid >> 7;
    const int m0 = blockIdx.y * BM, n0 = blockIdx.x * BN;
    const int nk = (K + BK - 1) / BK;

    if (tid == 0) {
        for (int i = 0; i < NST; i++) { mbar_init(smem_u32(&full_bar[i]), 1); mbar_init(smem_u32(&empty_bar[i]), 2); }
        asm volatile("fence.mbarrier_init.release.cluster;" ::: "memory");
    }
    __syncthreads();

    if (wg == 0) {
        if (tid == 0) {
            const int bsel = n0 / nPerB;
            const CUtensorMap* tmB = bsel == 0 ? &tmB0 : (bsel == 1 ? &tmB1 : &tmB2);
            const int nb = n0 - bsel * nPerB;
            for (int kt = 0; kt < nk; kt++) {
                int st = kt % NST; uint32_t ph = (kt / NST) & 1;
                mbar_wait(smem_u32(&empty_bar[st]), ph ^ 1);
                uint32_t fb = smem_u32(&full_bar[st]);
                mbar_expect_tx(fb, STAGE);
                uint32_t sa = smem_u32(smem + st * STAGE);
                tma_load_2d(sa, &tmA, fb, kt * BK, m0);
#pragma unroll
                for (int j = 0; j < BN / 64; j++) tma_load_2d(sa + A_BYTES + j * 8192, tmB, fb, nb + j * 64, kt * BK);
            }
        }
    } else {
        const int cw = wg - 1;
        float acc[BN / 2];
        for (int kt = 0; kt < nk; kt++) {
            int st = kt % NST; uint32_t ph = (kt / NST) & 1;
            mbar_wait(smem_u32(&full_bar[st]), ph);
            uint32_t sa = smem_u32(smem + st * STAGE) + cw * 64 * 128;
            uint32_t sb = smem_u32(smem + st * STAGE) + A_BYTES;
            wgmma_fence();
#pragma unroll
            for (int k = 0; k < BK / 16; k++) {
                uint64_t da = make_desc(sa + k * 32, 16, 1024);
                uint64_t db = make_desc(sb + k * 2048, 8192, 1024);
                Wgmma<BN>::mma(acc, da, db, (kt | k) != 0);
            }
            wgmma_commit();
            wgmma_wait<1>();
            if (kt > 0 && (tid & 127) == 0) mbar_arrive(smem_u32(&empty_bar[(kt - 1) % NST]));
        }
        wgmma_wait<0>();
        asm volatile("bar.sync 1, 256;" ::: "memory");
        const int lane = tid & 31, wi = (tid >> 5) & 3, g = lane >> 2, t = lane & 3;
        bf16* stg = reinterpret_cast<bf16*>(smem) + cw * 64 * OLD;
#pragma unroll
        for (int j = 0; j < BN / 8; j++) {
            *reinterpret_cast<uint32_t*>(&stg[(wi * 16 + g) * OLD + j * 8 + 2 * t]) = pack_bf16(acc[4 * j], acc[4 * j + 1]);
            *reinterpret_cast<uint32_t*>(&stg[(wi * 16 + g + 8) * OLD + j * 8 + 2 * t]) = pack_bf16(acc[4 * j + 2], acc[4 * j + 3]);
        }
        asm volatile("bar.sync %0, 128;" ::"r"(2 + cw) : "memory");
        constexpr int CPR = BN / 8;
        const int ltid = tid & 127;
#pragma unroll 4
        for (int i = ltid; i < 64 * CPR; i += 128) {
            int r = i / CPR, ch = i % CPR;
            int row = m0 + cw * 64 + r, col = n0 + ch * 8;
            if (col >= N) continue;
            uint4 v = *reinterpret_cast<const uint4*>(&stg[r * OLD + ch * 8]);
            uint32_t u[4] = {v.x, v.y, v.z, v.w}, o[4];
            if (EPI == EPI_STORE) {
#pragma unroll
                for (int q = 0; q < 4; q++) o[q] = u[q];
            } else if (EPI == EPI_GELU) {
#pragma unroll
                for (int q = 0; q < 4; q++) o[q] = pack_bf16(gelu_tanh_f(lo_f(u[q])), gelu_tanh_f(hi_f(u[q])));
            } else if (EPI == EPI_SP) {
                float bb = bf2f(ep.aux1[row]);
                uint4 z = *reinterpret_cast<const uint4*>(ep.aux0 + (size_t)row * F_ + col);
                uint32_t zz[4] = {z.x, z.y, z.z, z.w};
#pragma unroll
                for (int q = 0; q < 4; q++) o[q] = pack_bf16(lo_f(zz[q]) * rbf(lo_f(u[q]) + bb), hi_f(zz[q]) * rbf(hi_f(u[q]) + bb));
            } else if (EPI == EPI_SILU) {
#pragma unroll
                for (int q = 0; q < 4; q++) o[q] = pack_bf16(silu_f(lo_f(u[q])), silu_f(hi_f(u[q])));
            } else {
                uint4 xv = *reinterpret_cast<const uint4*>(ep.aux0 + (size_t)row * D_ + col);
                uint4 gv = *reinterpret_cast<const uint4*>(ep.aux1 + (size_t)row * D_ + col);
                uint32_t xx[4] = {xv.x, xv.y, xv.z, xv.w}, gg[4] = {gv.x, gv.y, gv.z, gv.w};
#pragma unroll
                for (int q = 0; q < 4; q++)
                    o[q] = pack_bf16(lo_f(xx[q]) + rbf(lo_f(u[q]) * lo_f(gg[q])), hi_f(xx[q]) + rbf(hi_f(u[q]) * hi_f(gg[q])));
            }
            *reinterpret_cast<uint4*>(ep.out + (size_t)row * ep.ldo + col) = make_uint4(o[0], o[1], o[2], o[3]);
        }
    }
}

__device__ __forceinline__ void mma16816(float* c, const uint32_t* a, uint32_t b0, uint32_t b1) {
    asm volatile(
        "mma.sync.aligned.m16n8k16.row.col.f32.bf16.bf16.f32 {%0,%1,%2,%3}, {%4,%5,%6,%7}, {%8,%9}, {%0,%1,%2,%3};"
        : "+f"(c[0]), "+f"(c[1]), "+f"(c[2]), "+f"(c[3])
        : "r"(a[0]), "r"(a[1]), "r"(a[2]), "r"(a[3]), "r"(b0), "r"(b1));
}
__device__ __forceinline__ void ldsm_x4(uint32_t* r, uint32_t addr) {
    asm volatile("ldmatrix.sync.aligned.m8n8.x4.shared.b16 {%0,%1,%2,%3}, [%4];"
                 : "=r"(r[0]), "=r"(r[1]), "=r"(r[2]), "=r"(r[3]) : "r"(addr));
}
__device__ __forceinline__ void ldsm_x4_t(uint32_t* r, uint32_t addr) {
    asm volatile("ldmatrix.sync.aligned.m8n8.x4.trans.shared.b16 {%0,%1,%2,%3}, [%4];"
                 : "=r"(r[0]), "=r"(r[1]), "=r"(r[2]), "=r"(r[3]) : "r"(addr));
}
__device__ __forceinline__ uint4 ld_relaxed_v4(const void* p) {
    uint4 v;
    asm volatile("ld.relaxed.gpu.global.v4.u32 {%0,%1,%2,%3}, [%4];" : "=r"(v.x), "=r"(v.y), "=r"(v.z), "=r"(v.w) : "l"(p) : "memory");
    return v;
}
__device__ __forceinline__ void st_relaxed_v4(void* p, uint32_t a, uint32_t b, uint32_t c, uint32_t d) {
    asm volatile("st.relaxed.gpu.global.v4.u32 [%0], {%1,%2,%3,%4};" ::"l"(p), "r"(a), "r"(b), "r"(c), "r"(d) : "memory");
}
__device__ __forceinline__ void st_relaxed_v2(void* p, uint32_t a, uint32_t b) {
    asm volatile("st.relaxed.gpu.global.v2.u32 [%0], {%1,%2};" ::"l"(p), "r"(a), "r"(b) : "memory");
}
__device__ __forceinline__ void cp_async16(uint32_t dst, const void* src) {
    asm volatile("cp.async.cg.shared.global [%0], [%1], 16;" ::"r"(dst), "l"(src) : "memory");
}
__device__ __forceinline__ void cp_async_commit() { asm volatile("cp.async.commit_group;" ::: "memory"); }
template <int N> __device__ __forceinline__ void cp_async_wait() { asm volatile("cp.async.wait_group %0;" ::"n"(N) : "memory"); }

#define PROF(i) do {} while (0)
constexpr int SPIN_LIMIT = 4000000;

__device__ __forceinline__ uint4 poll_ll(const void* p, uint32_t flag) {
    uint4 v = ld_relaxed_v4(p);
    int n = 0;
    while ((v.y != flag || v.w != flag) && ++n < SPIN_LIMIT) {
        v = ld_relaxed_v4(p);
    }
    return v;
}

constexpr int RT = 512;
constexpr int MEMS_LD = D_ + 8;
constexpr int HL = DH_ + 8;
struct RecurSmem {
    bf16 mem[MEM_][MEMS_LD];
    bf16 kall[2][48][HL];
    bf16 vall[2][48][HL];
    bf16 qm[16][HL];
    float sc[MEM_][40];
    bf16 p[MEM_][48 + 8];
    bf16 om[MEM_][HL];
    float red[12][16 * 8];
    float wred[2][5][16 * 8];
};

__device__ __forceinline__ void bar_sync(int id, int n) { asm volatile("bar.sync %0, %1;" ::"r"(id), "r"(n) : "memory"); }
__device__ __forceinline__ void bar_arrive(int id, int n) { asm volatile("bar.arrive %0, %1;" ::"r"(id), "r"(n) : "memory"); }
__device__ __forceinline__ void sts64(uint32_t a, uint32_t x, uint32_t y) { asm volatile("st.shared.v2.u32 [%0], {%1,%2};" ::"r"(a), "r"(x), "r"(y) : "memory"); }
__device__ __forceinline__ uint32_t ldg_u16x2(const bf16* p0, const bf16* p1) {
    return (uint32_t)*(const uint16_t*)p0 | ((uint32_t)*(const uint16_t*)p1 << 16);
}
enum { BAR_MEM = 1, BAR_RED = 2, BAR_CTL = 3, BAR_WO = 4, BAR_INIT = 6 };

__global__ void __launch_bounds__(RT, 1)
recur_kernel(const bf16* __restrict__ mem0, const bf16* __restrict__ Wq, const bf16* __restrict__ Wk,
             const bf16* __restrict__ Wv, const bf16* __restrict__ Wo) {
    extern __shared__ __align__(16) uint8_t smem_raw[];
    RecurSmem& sm = *reinterpret_cast<RecurSmem*>(smem_raw);
    const int tid = threadIdx.x, lane = tid & 31, w = tid >> 5;
    const int g = lane >> 2, t = lane & 3;
    const int h = blockIdx.x >> 2, c = blockIdx.x & 3;

    if (w < 12) {
        asm volatile("setmaxnreg.dec.sync.aligned.u32 104;");
        uint32_t wf[20][4];
        const int mt = w % 6, kh = w / 6;
        {
            const bf16* W = (mt < 2) ? Wq : (mt < 4 ? Wk : Wv);
            int f0 = h * DH_ + c * 32 + (mt & 1) * 16;
            uint32_t stg = smem_u32(smem_raw) + w * 10240;
#pragma unroll 4
            for (int i = lane; i < 640; i += 32)
                cp_async16(stg + i * 16, W + (size_t)(kh * 320 + (i >> 1)) * HD_ + f0 + (i & 1) * 8);
            cp_async_commit(); cp_async_wait<0>(); __syncwarp();
            uint32_t la = stg + ((lane & 7) + ((lane >> 4) & 1) * 8) * 32 + ((lane >> 3) & 1) * 16;
#pragma unroll
            for (int i = 0; i < 20; i++) ldsm_x4_t(wf[i], la + i * 512);
        }
        bar_sync(BAR_INIT, RT);
        const uint32_t base = smem_u32(&sm.mem[lane & 7][kh * 320 + (lane >> 3) * 8]);
        const uint32_t rp = smem_u32(&sm.red[w][g * 8 + 2 * t]);
        for (int s = 0; s < NSEG_; s++) {
            bar_sync(BAR_MEM, RT);
            float a0[4] = {0.f, 0.f, 0.f, 0.f}, a1[4] = {0.f, 0.f, 0.f, 0.f};
#pragma unroll
            for (int i = 0; i < 10; i++) {
                uint32_t b[4];
                ldsm_x4(b, base + i * 64);
                mma16816(a0, wf[2 * i], b[0], b[1]);
                mma16816(a1, wf[2 * i + 1], b[2], b[3]);
            }
            sts64(rp, __float_as_uint(a0[0] + a1[0]), __float_as_uint(a0[1] + a1[1]));
            sts64(rp + 256, __float_as_uint(a0[2] + a1[2]), __float_as_uint(a0[3] + a1[3]));
            bar_arrive(BAR_RED, RT);
        }
    } else {
        asm volatile("setmaxnreg.inc.sync.aligned.u32 200;");
        const int ct = tid - 384, cw = w - 12;
        const int mg = cw >> 1, kh = cw & 1;
        uint32_t wf[20][4];
        {
            uint32_t stg = smem_u32(smem_raw) + 12 * 10240 + cw * 10240;
#pragma unroll 4
            for (int i = lane; i < 640; i += 32) {
                int r = i / 10, ch = i % 10;
                cp_async16(stg + r * 160 + ch * 16, Wo + (size_t)(h * DH_ + kh * 64 + r) * D_ + c * 160 + mg * 80 + ch * 8);
            }
            cp_async_commit(); cp_async_wait<0>(); __syncwarp();
            uint32_t la = stg + ((lane & 7) + ((lane >> 4) & 1) * 8) * 160 + ((lane >> 3) & 1) * 16;
#pragma unroll
            for (int mi = 0; mi < 5; mi++)
#pragma unroll
                for (int ki = 0; ki < 4; ki++) ldsm_x4_t(wf[mi * 4 + ki], la + ki * 16 * 160 + mi * 32);
        }
        bar_sync(BAR_INIT, RT);
        for (int i = ct; i < 2 * 8 * HL; i += 128) {
            int b = i / (8 * HL), r = (i / HL) % 8, cc = i % HL;
            sm.kall[b][40 + r][cc] = __float2bfloat16(0.f);
            sm.vall[b][40 + r][cc] = __float2bfloat16(0.f);
        }
        for (int i = ct; i < 8 * HL; i += 128) sm.qm[8 + i / HL][i % HL] = __float2bfloat16(0.f);
        for (int i = ct; i < 8 * 56; i += 128) sm.p[i / 56][i % 56] = __float2bfloat16(0.f);
        bar_sync(BAR_CTL, 128);
        constexpr uint32_t KV_BUF = 48 * HL * 2;
        const bf16* kv_src = g_qkv + (size_t)(ct >> 4) * (3 * HD_) + HD_ + h * DH_ + (ct & 15) * 8;
        const uint32_t kv_dst0 = smem_u32(&sm.kall[0][MEM_ + (ct >> 4)][(ct & 15) * 8]);
        const uint32_t kv_dst1 = smem_u32(&sm.vall[0][MEM_ + (ct >> 4)][(ct & 15) * 8]);
        auto prefetch_kv = [&](int s, int buf) {
            const bf16* src = kv_src + (size_t)s * SEG_ * (3 * HD_);
#pragma unroll
            for (int j = 0; j < 4; j++) {
                cp_async16(kv_dst0 + buf * KV_BUF + j * (8 * HL * 2), src + (size_t)j * 8 * (3 * HD_));
                cp_async16(kv_dst1 + buf * KV_BUF + j * (8 * HL * 2), src + (size_t)j * 8 * (3 * HD_) + HD_);
            }
            cp_async_commit();
        };
        const float4* acc_src = reinterpret_cast<const float4*>(g_acc) + ct;
        const uint32_t acc_dst = smem_u32(&sm.mem[(ct & 1) * 4][ct >> 1]);
        const uint4* hx_base = reinterpret_cast<const uint4*>(g_hx) + h * 1024;
        const int hx_rq = ct & 63, hx_half = ct >> 6;
        const uint4* hx_src = hx_base + hx_half * 64 + hx_rq;
        const uint32_t hx_col = (hx_rq & 7) * 8, hx_r = hx_rq >> 3;
        const uint32_t hx_dstA = (hx_half == 0 ? smem_u32(&sm.qm[hx_r][0]) : smem_u32(&sm.kall[0][hx_r][0])) + hx_col;
        const uint32_t hx_dstB = smem_u32(&sm.vall[0][hx_r][0]) + hx_col;
        const uint4* hx_probe = hx_base + (lane >> 3) * 256 + ((lane & 7) % 3) * 64 + (lane & 7) * 8 + 3;
        const int pb_r = ct >> 4, pb_pr = ct & 15;
        uint2* pb_dst = g_hx + (h * 1024 + c * 256 + pb_r * 8) * 2 + pb_pr;
        const float* pb_src = &sm.red[pb_pr >> 3][(pb_pr & 7) * 16 + pb_r];
        bf16* pb_k = g_kmem + (size_t)pb_r * HD_ + h * DH_ + c * 32 + pb_pr * 2;
        bf16* pb_v = g_vmem + (size_t)pb_r * HD_ + h * DH_ + c * 32 + pb_pr * 2;
        const uint32_t qa = smem_u32(&sm.qm[lane & 15][(lane >> 4) * 8]);
        const uint32_t kb0 = smem_u32(&sm.kall[0][cw * 8 + (lane & 7)][(lane >> 3) * 8]);
        const uint32_t va0 = smem_u32(&sm.vall[0][(lane & 7) + ((lane >> 4) & 1) * 8][cw * 32 + ((lane >> 3) & 1) * 8]);
        const uint32_t pbaddr = smem_u32(&sm.p[lane & 7][((lane >> 3) & 1) * 8]);
        const uint32_t ob = smem_u32(&sm.om[lane & 7][kh * 64 + (lane >> 3) * 8]);
        float* acc_dst_g = g_acc + (c * 160 + mg * 80 + g) * 8 + 2 * t;

        prefetch_kv(0, 0);
        for (int s = 0; s < NSEG_; s++) {
            const int buf = s & 1;
            const uint32_t flag = s + 1;
            const uint32_t bo = buf * KV_BUF;
            PROF(0);
            if (s == 0) {
                for (int i = ct; i < MEM_ * D_ / 8; i += 128) {
                    int r = i / (D_ / 8), cc = (i % (D_ / 8)) * 8;
                    *reinterpret_cast<uint4*>(&sm.mem[r][cc]) = *reinterpret_cast<const uint4*>(mem0 + r * D_ + cc);
                }
            } else {
                if (ct == 0) {
                    const unsigned* cp = g_cnt + (s - 1) * 32;
                    unsigned v; int n = 0;
                    do { asm volatile("ld.acquire.gpu.global.u32 %0, [%1];" : "=r"(v) : "l"(cp) : "memory"); } while (v < 256u && ++n < SPIN_LIMIT);
                }
                bar_sync(BAR_CTL, 128);
                PROF(1);
                const float4* src = acc_src + (size_t)(s - 1) * (MEM_ * D_ / 4);
                float4 v[10];
#pragma unroll
                for (int j = 0; j < 10; j++)
                    asm volatile("ld.relaxed.gpu.global.v4.f32 {%0,%1,%2,%3}, [%4];" : "=f"(v[j].x), "=f"(v[j].y), "=f"(v[j].z), "=f"(v[j].w) : "l"(src + 128 * j) : "memory");
#pragma unroll
                for (int j = 0; j < 10; j++) {
                    uint32_t lo = pack_bf16(v[j].x, v[j].y), hi = pack_bf16(v[j].z, v[j].w);
                    uint32_t d = acc_dst + j * 128;
                    asm volatile("st.shared.u16 [%0], %1;" ::"r"(d), "h"((uint16_t)(lo & 0xffff)) : "memory");
                    asm volatile("st.shared.u16 [%0], %1;" ::"r"(d + MEMS_LD * 2), "h"((uint16_t)(lo >> 16)) : "memory");
                    asm volatile("st.shared.u16 [%0], %1;" ::"r"(d + MEMS_LD * 4), "h"((uint16_t)(hi & 0xffff)) : "memory");
                    asm volatile("st.shared.u16 [%0], %1;" ::"r"(d + MEMS_LD * 6), "h"((uint16_t)(hi >> 16)) : "memory");
                }
            }
            bar_arrive(BAR_MEM, RT);
            PROF(2);
            bar_sync(BAR_RED, RT);
            PROF(3);
            {
                uint32_t pk0 = pack_bf16(pb_src[0] + pb_src[768], pb_src[8] + pb_src[768 + 8]);
                uint32_t pk1 = pack_bf16(pb_src[256] + pb_src[1024], pb_src[256 + 8] + pb_src[1024 + 8]);
                uint32_t pk2 = pack_bf16(pb_src[512] + pb_src[1280], pb_src[512 + 8] + pb_src[1280 + 8]);
                st_relaxed_v2(pb_dst, pk0, flag);
                st_relaxed_v2(pb_dst + 128, pk1, flag);
                st_relaxed_v2(pb_dst + 256, pk2, flag);
                *reinterpret_cast<uint32_t*>(pb_k + (size_t)s * (MEM_ * HD_)) = pk1;
                *reinterpret_cast<uint32_t*>(pb_v + (size_t)s * (MEM_ * HD_)) = pk2;
            }
            if (s == NSEG_ - 1) break;
            PROF(4);
            if (cw == 0) (void)poll_ll(hx_probe, flag);
            bar_sync(BAR_CTL, 128);
            PROF(5);
            {
                uint4 v[8];
#pragma unroll
                for (int j = 0; j < 4; j++) v[j] = ld_relaxed_v4(hx_src + j * 256);
                if (hx_half == 0) {
#pragma unroll
                    for (int j = 0; j < 4; j++) v[4 + j] = ld_relaxed_v4(hx_src + j * 256 + 128);
                }
#pragma unroll
                for (int j = 0; j < 4; j++) {
                    if (v[j].y != flag || v[j].w != flag) v[j] = poll_ll(hx_src + j * 256, flag);
                    sts64(hx_dstA + j * 64 + (hx_half ? bo : 0), v[j].x, v[j].z);
                }
                if (hx_half == 0) {
#pragma unroll
                    for (int j = 0; j < 4; j++) {
                        if (v[4 + j].y != flag || v[4 + j].w != flag) v[4 + j] = poll_ll(hx_src + j * 256 + 128, flag);
                        sts64(hx_dstB + j * 64 + bo, v[4 + j].x, v[4 + j].z);
                    }
                }
            }
            cp_async_wait<0>();
            bar_sync(BAR_CTL, 128);
            PROF(6);
            {
                uint32_t a[8][4], b[4][4], b2[4][4];
#pragma unroll
                for (int kk = 0; kk < 4; kk++) ldsm_x4(b[kk], kb0 + bo + kk * 64);
                if (cw == 0) {
#pragma unroll
                    for (int kk = 0; kk < 4; kk++) ldsm_x4(b2[kk], kb0 + bo + 32 * HL * 2 + kk * 64);
                }
#pragma unroll
                for (int kk = 0; kk < 8; kk++) ldsm_x4(a[kk], qa + kk * 32);
                float s0[4] = {0.f, 0.f, 0.f, 0.f}, s1[4] = {0.f, 0.f, 0.f, 0.f};
#pragma unroll
                for (int kk = 0; kk < 4; kk++) { mma16816(s0, a[2 * kk], b[kk][0], b[kk][1]); mma16816(s1, a[2 * kk + 1], b[kk][2], b[kk][3]); }
                const float scale = 0.08838834764831845f;
                *reinterpret_cast<float2*>(&sm.sc[g][cw * 8 + 2 * t]) =
                    make_float2(rbf(rbf(s0[0] + s1[0]) * scale), rbf(rbf(s0[1] + s1[1]) * scale));
                if (cw == 0) {
                    float u0[4] = {0.f, 0.f, 0.f, 0.f}, u1[4] = {0.f, 0.f, 0.f, 0.f};
#pragma unroll
                    for (int kk = 0; kk < 4; kk++) { mma16816(u0, a[2 * kk], b2[kk][0], b2[kk][1]); mma16816(u1, a[2 * kk + 1], b2[kk][2], b2[kk][3]); }
                    *reinterpret_cast<float2*>(&sm.sc[g][32 + 2 * t]) =
                        make_float2(rbf(rbf(u0[0] + u1[0]) * scale), rbf(rbf(u0[1] + u1[1]) * scale));
                }
            }
            bar_sync(BAR_CTL, 128);
            {
                float v0 = sm.sc[cw][lane], v1 = (lane < 8) ? sm.sc[cw][32 + lane] : -INFINITY;
                float y0 = sm.sc[cw + 4][lane], y1 = (lane < 8) ? sm.sc[cw + 4][32 + lane] : -INFINITY;
                float mx = fmaxf(v0, v1), my = fmaxf(y0, y1);
#pragma unroll
                for (int o = 16; o; o >>= 1) { mx = fmaxf(mx, __shfl_xor_sync(0xffffffffu, mx, o)); my = fmaxf(my, __shfl_xor_sync(0xffffffffu, my, o)); }
                float e0 = __expf(v0 - mx), e1 = (lane < 8) ? __expf(v1 - mx) : 0.f;
                float f0 = __expf(y0 - my), f1 = (lane < 8) ? __expf(y1 - my) : 0.f;
                float sx = e0 + e1, sy = f0 + f1;
#pragma unroll
                for (int o = 16; o; o >>= 1) { sx += __shfl_xor_sync(0xffffffffu, sx, o); sy += __shfl_xor_sync(0xffffffffu, sy, o); }
                float ix = 1.0f / sx, iy = 1.0f / sy;
                sm.p[cw][lane] = __float2bfloat16_rn(e0 * ix);
                sm.p[cw + 4][lane] = __float2bfloat16_rn(f0 * iy);
                if (lane < 8) { sm.p[cw][32 + lane] = __float2bfloat16_rn(e1 * ix); sm.p[cw + 4][32 + lane] = __float2bfloat16_rn(f1 * iy); }
            }
            bar_sync(BAR_CTL, 128);
            PROF(7);
            {
                uint32_t a[2][3][4], b[3][2];
#pragma unroll
                for (int kt = 0; kt < 3; kt++) {
                    asm volatile("ldmatrix.sync.aligned.m8n8.x2.shared.b16 {%0,%1}, [%2];" : "=r"(b[kt][0]), "=r"(b[kt][1]) : "r"(pbaddr + kt * 32));
                    ldsm_x4_t(a[0][kt], va0 + bo + kt * 16 * HL * 2);
                    ldsm_x4_t(a[1][kt], va0 + bo + kt * 16 * HL * 2 + 32);
                }
#pragma unroll
                for (int m = 0; m < 2; m++) {
                    float o[4] = {0.f, 0.f, 0.f, 0.f};
#pragma unroll
                    for (int kt = 0; kt < 3; kt++) mma16816(o, a[m][kt], b[kt][0], b[kt][1]);
                    int d0 = cw * 32 + m * 16 + g;
                    sm.om[2 * t][d0] = __float2bfloat16_rn(o[0]);
                    sm.om[2 * t + 1][d0] = __float2bfloat16_rn(o[1]);
                    sm.om[2 * t][d0 + 8] = __float2bfloat16_rn(o[2]);
                    sm.om[2 * t + 1][d0 + 8] = __float2bfloat16_rn(o[3]);
                }
            }
            bar_sync(BAR_CTL, 128);
            PROF(8);
            {
                float acc[5][4];
#pragma unroll
                for (int mi = 0; mi < 5; mi++) { acc[mi][0] = acc[mi][1] = acc[mi][2] = acc[mi][3] = 0.f; }
                uint32_t b[2][4];
                ldsm_x4(b[0], ob); ldsm_x4(b[1], ob + 64);
#pragma unroll
                for (int ki = 0; ki < 4; ki++)
#pragma unroll
                    for (int mi = 0; mi < 5; mi++) mma16816(acc[mi], wf[mi * 4 + ki], b[ki >> 1][(ki & 1) * 2], b[ki >> 1][(ki & 1) * 2 + 1]);
                if (kh == 1) {
#pragma unroll
                    for (int mi = 0; mi < 5; mi++)
                        *reinterpret_cast<float4*>(&sm.wred[mg][mi][lane * 4]) = make_float4(acc[mi][0], acc[mi][1], acc[mi][2], acc[mi][3]);
                }
                bar_sync(BAR_WO + mg, 64);
                if (kh == 0) {
                    float* dst = acc_dst_g + (size_t)s * (MEM_ * D_);
#pragma unroll
                    for (int mi = 0; mi < 5; mi++) {
                        float4 o2 = *reinterpret_cast<float4*>(&sm.wred[mg][mi][lane * 4]);
                        asm volatile("red.global.add.v2.f32 [%0], {%1,%2};" ::"l"(dst + mi * 128), "f"(acc[mi][0] + o2.x), "f"(acc[mi][1] + o2.y) : "memory");
                        asm volatile("red.global.add.v2.f32 [%0], {%1,%2};" ::"l"(dst + mi * 128 + 64), "f"(acc[mi][2] + o2.z), "f"(acc[mi][3] + o2.w) : "memory");
                    }
                    __threadfence();
                    __syncwarp();
                    if (lane == 0) atomicAdd(&g_cnt[s * 32], 1u);
                }
            }
            PROF(9);
            prefetch_kv(s + 1, buf ^ 1);
            PROF(10);
        }
    }
}

__global__ void __launch_bounds__(128)
attn_x_kernel() {
    __shared__ __align__(16) bf16 sq[32][HL], sk[48][HL], sv[48][HL];
    const int s = blockIdx.x >> 5, h = blockIdx.x & 31;
    const int tid = threadIdx.x, lane = tid & 31, w = tid >> 5, g = lane >> 2, t = lane & 3;
    for (int i = tid; i < (32 + 40 + 40) * 16; i += 128) {
        int r = i >> 4, ch = i & 15;
        const bf16* src; bf16* dst;
        if (r < 32) { src = g_qkv + (size_t)(s * SEG_ + r) * (3 * HD_) + h * DH_; dst = sq[r]; }
        else if (r < 72) { int rr = r - 32; dst = sk[rr];
            src = rr < 8 ? g_kmem + ((size_t)s * MEM_ + rr) * HD_ + h * DH_ : g_qkv + (size_t)(s * SEG_ + rr - 8) * (3 * HD_) + HD_ + h * DH_; }
        else { int rr = r - 72; dst = sv[rr];
            src = rr < 8 ? g_vmem + ((size_t)s * MEM_ + rr) * HD_ + h * DH_ : g_qkv + (size_t)(s * SEG_ + rr - 8) * (3 * HD_) + 2 * HD_ + h * DH_; }
        cp_async16(smem_u32(dst + ch * 8), src + ch * 8);
    }
    cp_async_commit();
    for (int i = tid; i < 8 * 16; i += 128) *reinterpret_cast<uint4*>(&sv[40 + (i >> 4)][(i & 15) * 8]) = make_uint4(0, 0, 0, 0);
    cp_async_wait<0>();
    __syncthreads();
    const int rh = w & 1, dhh = w >> 1;
    float sc[5][4];
#pragma unroll
    for (int n = 0; n < 5; n++) sc[n][0] = sc[n][1] = sc[n][2] = sc[n][3] = 0.f;
#pragma unroll
    for (int kk = 0; kk < 8; kk++) {
        uint32_t a[4];
        ldsm_x4(a, smem_u32(&sq[rh * 16 + (lane & 15)][kk * 16 + (lane >> 4) * 8]));
#pragma unroll
        for (int n = 0; n < 5; n++) {
            uint32_t b[2];
            asm volatile("ldmatrix.sync.aligned.m8n8.x2.shared.b16 {%0,%1}, [%2];" : "=r"(b[0]), "=r"(b[1])
                         : "r"(smem_u32(&sk[n * 8 + (lane & 7)][kk * 16 + ((lane >> 3) & 1) * 8])));
            mma16816(sc[n], a, b[0], b[1]);
        }
    }
    const float scale = 0.08838834764831845f;
    float mx[2] = {-INFINITY, -INFINITY};
#pragma unroll
    for (int n = 0; n < 5; n++)
#pragma unroll
        for (int e = 0; e < 4; e++) {
            int row = rh * 16 + g + (e >> 1) * 8, key = n * 8 + 2 * t + (e & 1);
            float v = rbf(rbf(sc[n][e]) * scale);
            if (key > row + MEM_) v = -INFINITY;
            sc[n][e] = v;
            mx[e >> 1] = fmaxf(mx[e >> 1], v);
        }
#pragma unroll
    for (int o = 1; o < 4; o <<= 1) { mx[0] = fmaxf(mx[0], __shfl_xor_sync(0xffffffffu, mx[0], o)); mx[1] = fmaxf(mx[1], __shfl_xor_sync(0xffffffffu, mx[1], o)); }
    float sum[2] = {0.f, 0.f};
#pragma unroll
    for (int n = 0; n < 5; n++)
#pragma unroll
        for (int e = 0; e < 4; e++) { float ev = __expf(sc[n][e] - mx[e >> 1]); sc[n][e] = ev; sum[e >> 1] += ev; }
#pragma unroll
    for (int o = 1; o < 4; o <<= 1) { sum[0] += __shfl_xor_sync(0xffffffffu, sum[0], o); sum[1] += __shfl_xor_sync(0xffffffffu, sum[1], o); }
    float inv[2] = {1.0f / sum[0], 1.0f / sum[1]};
    uint32_t pa[3][4];
#pragma unroll
    for (int kt = 0; kt < 3; kt++) {
        pa[kt][0] = pack_bf16(sc[2 * kt][0] * inv[0], sc[2 * kt][1] * inv[0]);
        pa[kt][1] = pack_bf16(sc[2 * kt][2] * inv[1], sc[2 * kt][3] * inv[1]);
        if (kt < 2) {
            pa[kt][2] = pack_bf16(sc[2 * kt + 1][0] * inv[0], sc[2 * kt + 1][1] * inv[0]);
            pa[kt][3] = pack_bf16(sc[2 * kt + 1][2] * inv[1], sc[2 * kt + 1][3] * inv[1]);
        } else { pa[kt][2] = 0u; pa[kt][3] = 0u; }
    }
#pragma unroll
    for (int n = 0; n < 8; n++) {
        float o[4] = {0.f, 0.f, 0.f, 0.f};
#pragma unroll
        for (int kt = 0; kt < 3; kt++) {
            uint32_t b[2];
            asm volatile("ldmatrix.sync.aligned.m8n8.x2.trans.shared.b16 {%0,%1}, [%2];" : "=r"(b[0]), "=r"(b[1])
                         : "r"(smem_u32(&sv[kt * 16 + (lane & 15)][dhh * 64 + n * 8])));
            mma16816(o, pa[kt], b[0], b[1]);
        }
        int row = s * SEG_ + rh * 16 + g;
        bf16* dst = g_o + (size_t)row * HD_ + h * DH_ + dhh * 64 + n * 8 + 2 * t;
        *reinterpret_cast<uint32_t*>(dst) = pack_bf16(o[0], o[1]);
        *reinterpret_cast<uint32_t*>(dst + 8 * HD_) = pack_bf16(o[2], o[3]);
    }
}

typedef CUresult (*PFN_encodeTiled)(CUtensorMap*, CUtensorMapDataType, cuuint32_t, void*, const cuuint64_t*,
                                    const cuuint64_t*, const cuuint32_t*, const cuuint32_t*, CUtensorMapInterleave,
                                    CUtensorMapSwizzle, CUtensorMapL2promotion, CUtensorMapFloatOOBfill);
static PFN_encodeTiled p_encode = nullptr;

static CUtensorMap make_map(const void* ptr, uint64_t rows, uint64_t cols, uint64_t ld, uint32_t box_rows) {
    CUtensorMap m;
    cuuint64_t dims[2] = {cols, rows};
    cuuint64_t strides[1] = {ld * 2};
    cuuint32_t box[2] = {64, box_rows};
    cuuint32_t es[2] = {1, 1};
    p_encode(&m, CU_TENSOR_MAP_DATA_TYPE_BFLOAT16, 2, const_cast<void*>(ptr), dims, strides, box, es,
             CU_TENSOR_MAP_INTERLEAVE_NONE, CU_TENSOR_MAP_SWIZZLE_128B, CU_TENSOR_MAP_L2_PROMOTION_L2_128B,
             CU_TENSOR_MAP_FLOAT_OOB_FILL_NONE);
    return m;
}

template <int BN, int EPI>
static void launch_gemm(const CUtensorMap& a, const CUtensorMap& b0, const CUtensorMap& b1, const CUtensorMap& b2,
                        int nPerB, int M, int N, int K, EpiParams ep, cudaStream_t st) {
    constexpr int STAGE = 16384 + (BN / 64) * 8192;
    constexpr int NST = (200 * 1024) / STAGE;
    constexpr int SMEM = NST * STAGE + 1024;
    cudaFuncSetAttribute(gemm_kernel<BN, EPI>, cudaFuncAttributeMaxDynamicSharedMemorySize, SMEM);
    dim3 grid((N + BN - 1) / BN, M / 128);
    gemm_kernel<BN, EPI><<<grid, 384, SMEM, st>>>(a, b0, b1, b2, nPerB, N, K, ep);
}

extern "C" void kernel_launch(void* const* d_in, const int* in_sizes, int n_in, void* d_out, int out_size) {
    const bf16* x    = (const bf16*)d_in[0];
    const bf16* mem0 = (const bf16*)d_in[1];
    const bf16* Wq   = (const bf16*)d_in[2];
    const bf16* Wk   = (const bf16*)d_in[3];
    const bf16* Wv   = (const bf16*)d_in[4];
    const bf16* Wo   = (const bf16*)d_in[5];
    const bf16* w_in  = (const bf16*)d_in[8];
    const bf16* w_sp  = (const bf16*)d_in[9];
    const bf16* b_sp  = (const bf16*)d_in[10];
    const bf16* w_out = (const bf16*)d_in[11];
    bf16* out = (bf16*)d_out;
    cudaStream_t st = cudaStreamPerThread;

    if (!p_encode) {
        cudaDriverEntryPointQueryResult qr;
        cudaGetDriverEntryPoint("cuTensorMapEncodeTiled", (void**)&p_encode, cudaEnableDefault, &qr);
    }
    void *p_xn, *p_qkv, *p_z, *p_zg, *p_gate, *p_o, *p_acc, *p_cnt, *p_hx;
    cudaGetSymbolAddress(&p_xn, g_xn); cudaGetSymbolAddress(&p_qkv, g_qkv); cudaGetSymbolAddress(&p_z, g_z);
    cudaGetSymbolAddress(&p_zg, g_zg); cudaGetSymbolAddress(&p_gate, g_gate); cudaGetSymbolAddress(&p_o, g_o);
    cudaGetSymbolAddress(&p_acc, g_acc); cudaGetSymbolAddress(&p_cnt, g_cnt); cudaGetSymbolAddress(&p_hx, g_hx);

    CUtensorMap mA_xn  = make_map(p_xn, S_, D_, D_, 128);
    CUtensorMap mA_wsp = make_map(w_sp, S_, S_, S_, 128);
    CUtensorMap mA_zg  = make_map(p_zg, S_, FH_, FH_, 128);
    CUtensorMap mA_o   = make_map(p_o, S_, HD_, HD_, 128);
    CUtensorMap mB_wq  = make_map(Wq, D_, HD_, HD_, 64);
    CUtensorMap mB_wk  = make_map(Wk, D_, HD_, HD_, 64);
    CUtensorMap mB_wv  = make_map(Wv, D_, HD_, HD_, 64);
    CUtensorMap mB_win = make_map(w_in, D_, F_, F_, 64);
    CUtensorMap mB_z2  = make_map((bf16*)p_z + FH_, S_, FH_, F_, 64);
    CUtensorMap mB_wout = make_map(w_out, FH_, D_, D_, 64);
    CUtensorMap mB_wo  = make_map(Wo, HD_, D_, D_, 64);

    cudaMemsetAsync(p_acc, 0, sizeof(float) * NSEG_ * MEM_ * D_, st);
    cudaMemsetAsync(p_cnt, 0, sizeof(unsigned) * NSEG_ * 32, st);
    cudaMemsetAsync(p_hx, 0, sizeof(uint2) * H_ * 4 * 256 * 2, st);

    ln_kernel<<<S_ / 8, 256, 0, st>>>(x);
    { EpiParams ep{(bf16*)p_qkv, 3 * HD_, nullptr, nullptr}; launch_gemm<256, EPI_STORE>(mA_xn, mB_wq, mB_wk, mB_wv, HD_, S_, 3 * HD_, D_, ep, st); }
    { EpiParams ep{(bf16*)p_z, F_, nullptr, nullptr}; launch_gemm<128, EPI_GELU>(mA_xn, mB_win, mB_win, mB_win, 1 << 20, S_, F_, D_, ep, st); }
    ln2_kernel<<<S_ / 8, 256, 0, st>>>();
    { EpiParams ep{(bf16*)p_zg, FH_, (const bf16*)p_z, b_sp}; launch_gemm<128, EPI_SP>(mA_wsp, mB_z2, mB_z2, mB_z2, 1 << 20, S_, FH_, S_, ep, st); }
    { EpiParams ep{(bf16*)p_gate, D_, nullptr, nullptr}; launch_gemm<128, EPI_SILU>(mA_zg, mB_wout, mB_wout, mB_wout, 1 << 20, S_, D_, FH_, ep, st); }
    constexpr int RSM = (int)sizeof(RecurSmem) > 16 * 10240 ? (int)sizeof(RecurSmem) : 16 * 10240;
    cudaFuncSetAttribute(recur_kernel, cudaFuncAttributeMaxDynamicSharedMemorySize, RSM);
    recur_kernel<<<128, RT, RSM, st>>>(mem0, Wq, Wk, Wv, Wo);
    attn_x_kernel<<<NSEG_ * H_, 128, 0, st>>>();
    { EpiParams ep{out, D_, x, (const bf16*)p_gate}; launch_gemm<128, EPI_FINAL>(mA_o, mB_wo, mB_wo, mB_wo, 1 << 20, S_, D_, HD_, ep, st); }
}
```

```cpp
#include <cuda_runtime.h>
#include <cuda_bf16.h>
#include <cuda.h>
#include <stdint.h>

typedef __nv_bfloat16 bf16;

constexpr int S_   = 2048;
constexpr int D_   = 640;
constexpr int H_   = 32;
constexpr int DH_  = 128;
constexpr int MEM_ = 8;
constexpr int SEG_ = 32;
constexpr int NSEG_ = S_ / SEG_;
constexpr int HD_  = H_ * DH_;
constexpr int F_   = 1728;
constexpr int FH_  = 864;

__device__ bf16 g_xn[S_ * D_];
__device__ bf16 g_qkv[(size_t)S_ * 3 * HD_];
__device__ bf16 g_z[S_ * F_];
__device__ bf16 g_zg[S_ * FH_];
__device__ bf16 g_gate[S_ * D_];
__device__ bf16 g_kmem[NSEG_ * MEM_ * HD_];
__device__ bf16 g_vmem[NSEG_ * MEM_ * HD_];
__device__ bf16 g_o[(size_t)S_ * HD_];
__device__ float g_acc[NSEG_ * MEM_ * D_];
__device__ unsigned g_cnt[NSEG_ * 32];
__device__ unsigned g_xcnt[H_ * NSEG_];
__device__ uint2 g_hx[H_ * 4 * 256 * 2];

__device__ __forceinline__ uint32_t smem_u32(const void* p) { return (uint32_t)__cvta_generic_to_shared(p); }
__device__ __forceinline__ float bf2f(bf16 v) { return __bfloat162float(v); }
__device__ __forceinline__ float rbf(float v) { return __bfloat162float(__float2bfloat16_rn(v)); }
__device__ __forceinline__ uint32_t pack_bf16(float lo, float hi) {
    __nv_bfloat162 t = __floats2bfloat162_rn(lo, hi);
    return *reinterpret_cast<uint32_t*>(&t);
}
__device__ __forceinline__ float lo_f(uint32_t u) { return __uint_as_float(u << 16); }
__device__ __forceinline__ float hi_f(uint32_t u) { return __uint_as_float(u & 0xffff0000u); }

__device__ __forceinline__ void mbar_init(uint32_t bar, uint32_t cnt) {
    asm volatile("mbarrier.init.shared.b64 [%0], %1;" ::"r"(bar), "r"(cnt));
}
__device__ __forceinline__ void mbar_expect_tx(uint32_t bar, uint32_t bytes) {
    asm volatile("mbarrier.arrive.expect_tx.shared.b64 _, [%0], %1;" ::"r"(bar), "r"(bytes) : "memory");
}
__device__ __forceinline__ void mbar_arrive(uint32_t bar) {
    asm volatile("mbarrier.arrive.shared.b64 _, [%0];" ::"r"(bar) : "memory");
}
__device__ __forceinline__ void mbar_wait(uint32_t bar, uint32_t parity) {
    asm volatile(
        "{\n .reg .pred p;\n"
        "WAIT_%=:\n"
        " mbarrier.try_wait.parity.shared.b64 p, [%0], %1;\n"
        " @p bra DONE_%=;\n"
        " bra WAIT_%=;\n"
        "DONE_%=:\n}\n" ::"r"(bar), "r"(parity) : "memory");
}
__device__ __forceinline__ void tma_load_2d(uint32_t dst, const CUtensorMap* tm, uint32_t bar, int c0, int c1) {
    asm volatile(
        "cp.async.bulk.tensor.2d.shared::cluster.global.mbarrier::complete_tx::bytes [%0], [%1, {%3, %4}], [%2];"
        ::"r"(dst), "l"(tm), "r"(bar), "r"(c0), "r"(c1) : "memory");
}
__device__ __forceinline__ void wgmma_fence() { asm volatile("wgmma.fence.sync.aligned;" ::: "memory"); }
__device__ __forceinline__ void wgmma_commit() { asm volatile("wgmma.commit_group.sync.aligned;" ::: "memory"); }
template <int N> __device__ __forceinline__ void wgmma_wait() { asm volatile("wgmma.wait_group.sync.aligned %0;" ::"n"(N) : "memory"); }

__device__ __forceinline__ uint64_t make_desc(uint32_t addr, uint32_t lbo, uint32_t sbo) {
    return (uint64_t)((addr & 0x3FFFF) >> 4) | ((uint64_t)(lbo >> 4) << 16) | ((uint64_t)(sbo >> 4) << 32) | (1ull << 62);
}

template <int N> struct Wgmma;
template <> struct Wgmma<128> {
    static __device__ __forceinline__ void mma(float* d, uint64_t da, uint64_t db, int sd) {
        asm volatile(
            "{\n.reg .pred p;\nsetp.ne.b32 p, %66, 0;\n"
            "wgmma.mma_async.sync.aligned.m64n128k16.f32.bf16.bf16 "
            "{%0,%1,%2,%3,%4,%5,%6,%7,%8,%9,%10,%11,%12,%13,%14,%15,"
            "%16,%17,%18,%19,%20,%21,%22,%23,%24,%25,%26,%27,%28,%29,%30,%31,"
            "%32,%33,%34,%35,%36,%37,%38,%39,%40,%41,%42,%43,%44,%45,%46,%47,"
            "%48,%49,%50,%51,%52,%53,%54,%55,%56,%57,%58,%59,%60,%61,%62,%63},"
            "%64,%65,p,1,1,0,1;\n}\n"
            : "+f"(d[0]), "+f"(d[1]), "+f"(d[2]), "+f"(d[3]), "+f"(d[4]), "+f"(d[5]), "+f"(d[6]), "+f"(d[7]),
              "+f"(d[8]), "+f"(d[9]), "+f"(d[10]), "+f"(d[11]), "+f"(d[12]), "+f"(d[13]), "+f"(d[14]), "+f"(d[15]),
              "+f"(d[16]), "+f"(d[17]), "+f"(d[18]), "+f"(d[19]), "+f"(d[20]), "+f"(d[21]), "+f"(d[22]), "+f"(d[23]),
              "+f"(d[24]), "+f"(d[25]), "+f"(d[26]), "+f"(d[27]), "+f"(d[28]), "+f"(d[29]), "+f"(d[30]), "+f"(d[31]),
              "+f"(d[32]), "+f"(d[33]), "+f"(d[34]), "+f"(d[35]), "+f"(d[36]), "+f"(d[37]), "+f"(d[38]), "+f"(d[39]),
              "+f"(d[40]), "+f"(d[41]), "+f"(d[42]), "+f"(d[43]), "+f"(d[44]), "+f"(d[45]), "+f"(d[46]), "+f"(d[47]),
              "+f"(d[48]), "+f"(d[49]), "+f"(d[50]), "+f"(d[51]), "+f"(d[52]), "+f"(d[53]), "+f"(d[54]), "+f"(d[55]),
              "+f"(d[56]), "+f"(d[57]), "+f"(d[58]), "+f"(d[59]), "+f"(d[60]), "+f"(d[61]), "+f"(d[62]), "+f"(d[63])
            : "l"(da), "l"(db), "r"(sd));
    }
};
template <> struct Wgmma<192> {
    static __device__ __forceinline__ void mma(float* d, uint64_t da, uint64_t db, int sd) {
        asm volatile(
            "{\n.reg .pred p;\nsetp.ne.b32 p, %98, 0;\n"
            "wgmma.mma_async.sync.aligned.m64n192k16.f32.bf16.bf16 "
            "{%0,%1,%2,%3,%4,%5,%6,%7,%8,%9,%10,%11,%12,%13,%14,%15,"
            "%16,%17,%18,%19,%20,%21,%22,%23,%24,%25,%26,%27,%28,%29,%30,%31,"
            "%32,%33,%34,%35,%36,%37,%38,%39,%40,%41,%42,%43,%44,%45,%46,%47,"
            "%48,%49,%50,%51,%52,%53,%54,%55,%56,%57,%58,%59,%60,%61,%62,%63,"
            "%64,%65,%66,%67,%68,%69,%70,%71,%72,%73,%74,%75,%76,%77,%78,%79,"
            "%80,%81,%82,%83,%84,%85,%86,%87,%88,%89,%90,%91,%92,%93,%94,%95},"
            "%96,%97,p,1,1,0,1;\n}\n"
            : "+f"(d[0]), "+f"(d[1]), "+f"(d[2]), "+f"(d[3]), "+f"(d[4]), "+f"(d[5]), "+f"(d[6]), "+f"(d[7]),
              "+f"(d[8]), "+f"(d[9]), "+f"(d[10]), "+f"(d[11]), "+f"(d[12]), "+f"(d[13]), "+f"(d[14]), "+f"(d[15]),
              "+f"(d[16]), "+f"(d[17]), "+f"(d[18]), "+f"(d[19]), "+f"(d[20]), "+f"(d[21]), "+f"(d[22]), "+f"(d[23]),
              "+f"(d[24]), "+f"(d[25]), "+f"(d[26]), "+f"(d[27]), "+f"(d[28]), "+f"(d[29]), "+f"(d[30]), "+f"(d[31]),
              "+f"(d[32]), "+f"(d[33]), "+f"(d[34]), "+f"(d[35]), "+f"(d[36]), "+f"(d[37]), "+f"(d[38]), "+f"(d[39]),
              "+f"(d[40]), "+f"(d[41]), "+f"(d[42]), "+f"(d[43]), "+f"(d[44]), "+f"(d[45]), "+f"(d[46]), "+f"(d[47]),
              "+f"(d[48]), "+f"(d[49]), "+f"(d[50]), "+f"(d[51]), "+f"(d[52]), "+f"(d[53]), "+f"(d[54]), "+f"(d[55]),
              "+f"(d[56]), "+f"(d[57]), "+f"(d[58]), "+f"(d[59]), "+f"(d[60]), "+f"(d[61]), "+f"(d[62]), "+f"(d[63]),
              "+f"(d[64]), "+f"(d[65]), "+f"(d[66]), "+f"(d[67]), "+f"(d[68]), "+f"(d[69]), "+f"(d[70]), "+f"(d[71]),
              "+f"(d[72]), "+f"(d[73]), "+f"(d[74]), "+f"(d[75]), "+f"(d[76]), "+f"(d[77]), "+f"(d[78]), "+f"(d[79]),
              "+f"(d[80]), "+f"(d[81]), "+f"(d[82]), "+f"(d[83]), "+f"(d[84]), "+f"(d[85]), "+f"(d[86]), "+f"(d[87]),
              "+f"(d[88]), "+f"(d[89]), "+f"(d[90]), "+f"(d[91]), "+f"(d[92]), "+f"(d[93]), "+f"(d[94]), "+f"(d[95])
            : "l"(da), "l"(db), "r"(sd));
    }
};

template <> struct Wgmma<256> {
    static __device__ __forceinline__ void mma(float* d, uint64_t da, uint64_t db, int sd) {
        asm volatile(
            "{\n.reg .pred p;\nsetp.ne.b32 p, %130, 0;\n"
            "wgmma.mma_async.sync.aligned.m64n256k16.f32.bf16.bf16 "
            "{%0,%1,%2,%3,%4,%5,%6,%7,%8,%9,%10,%11,%12,%13,%14,%15,%16,%17,%18,%19,%20,%21,%22,%23,%24,%25,%26,%27,%28,%29,%30,%31,%32,%33,%34,%35,%36,%37,%38,%39,%40,%41,%42,%43,%44,%45,%46,%47,%48,%49,%50,%51,%52,%53,%54,%55,%56,%57,%58,%59,%60,%61,%62,%63,%64,%65,%66,%67,%68,%69,%70,%71,%72,%73,%74,%75,%76,%77,%78,%79,%80,%81,%82,%83,%84,%85,%86,%87,%88,%89,%90,%91,%92,%93,%94,%95,%96,%97,%98,%99,%100,%101,%102,%103,%104,%105,%106,%107,%108,%109,%110,%111,%112,%113,%114,%115,%116,%117,%118,%119,%120,%121,%122,%123,%124,%125,%126,%127},"
            "%128,%129,p,1,1,0,1;\n}\n"
            : "+f"(d[0]), "+f"(d[1]), "+f"(d[2]), "+f"(d[3]), "+f"(d[4]), "+f"(d[5]), "+f"(d[6]), "+f"(d[7]), "+f"(d[8]), "+f"(d[9]), "+f"(d[10]), "+f"(d[11]), "+f"(d[12]), "+f"(d[13]), "+f"(d[14]), "+f"(d[15]), "+f"(d[16]), "+f"(d[17]), "+f"(d[18]), "+f"(d[19]), "+f"(d[20]), "+f"(d[21]), "+f"(d[22]), "+f"(d[23]), "+f"(d[24]), "+f"(d[25]), "+f"(d[26]), "+f"(d[27]), "+f"(d[28]), "+f"(d[29]), "+f"(d[30]), "+f"(d[31]), "+f"(d[32]), "+f"(d[33]), "+f"(d[34]), "+f"(d[35]), "+f"(d[36]), "+f"(d[37]), "+f"(d[38]), "+f"(d[39]), "+f"(d[40]), "+f"(d[41]), "+f"(d[42]), "+f"(d[43]), "+f"(d[44]), "+f"(d[45]), "+f"(d[46]), "+f"(d[47]), "+f"(d[48]), "+f"(d[49]), "+f"(d[50]), "+f"(d[51]), "+f"(d[52]), "+f"(d[53]), "+f"(d[54]), "+f"(d[55]), "+f"(d[56]), "+f"(d[57]), "+f"(d[58]), "+f"(d[59]), "+f"(d[60]), "+f"(d[61]), "+f"(d[62]), "+f"(d[63]), "+f"(d[64]), "+f"(d[65]), "+f"(d[66]), "+f"(d[67]), "+f"(d[68]), "+f"(d[69]), "+f"(d[70]), "+f"(d[71]), "+f"(d[72]), "+f"(d[73]), "+f"(d[74]), "+f"(d[75]), "+f"(d[76]), "+f"(d[77]), "+f"(d[78]), "+f"(d[79]), "+f"(d[80]), "+f"(d[81]), "+f"(d[82]), "+f"(d[83]), "+f"(d[84]), "+f"(d[85]), "+f"(d[86]), "+f"(d[87]), "+f"(d[88]), "+f"(d[89]), "+f"(d[90]), "+f"(d[91]), "+f"(d[92]), "+f"(d[93]), "+f"(d[94]), "+f"(d[95]), "+f"(d[96]), "+f"(d[97]), "+f"(d[98]), "+f"(d[99]), "+f"(d[100]), "+f"(d[101]), "+f"(d[102]), "+f"(d[103]), "+f"(d[104]), "+f"(d[105]), "+f"(d[106]), "+f"(d[107]), "+f"(d[108]), "+f"(d[109]), "+f"(d[110]), "+f"(d[111]), "+f"(d[112]), "+f"(d[113]), "+f"(d[114]), "+f"(d[115]), "+f"(d[116]), "+f"(d[117]), "+f"(d[118]), "+f"(d[119]), "+f"(d[120]), "+f"(d[121]), "+f"(d[122]), "+f"(d[123]), "+f"(d[124]), "+f"(d[125]), "+f"(d[126]), "+f"(d[127])
            : "l"(da), "l"(db), "r"(sd));
    }
};
template <int W>
__device__ __forceinline__ void ln_row(const bf16* __restrict__ src, bf16* __restrict__ dst, int lane) {
    constexpr int NP = W / 64;
    constexpr int REM = (W / 2) % 32;
    uint32_t v[NP + 1];
    const uint32_t* s32 = reinterpret_cast<const uint32_t*>(src);
    float sum = 0.f;
#pragma unroll
    for (int i = 0; i < NP; i++) { v[i] = s32[i * 32 + lane]; sum += lo_f(v[i]) + hi_f(v[i]); }
    if (REM) { v[NP] = (lane < REM) ? s32[NP * 32 + lane] : 0u; if (lane < REM) sum += lo_f(v[NP]) + hi_f(v[NP]); }
#pragma unroll
    for (int o = 16; o; o >>= 1) sum += __shfl_xor_sync(0xffffffffu, sum, o);
    float mean = sum * (1.0f / W);
    float vs = 0.f;
#pragma unroll
    for (int i = 0; i < NP; i++) { float a = lo_f(v[i]) - mean, b = hi_f(v[i]) - mean; vs += a * a + b * b; }
    if (REM && lane < REM) { float a = lo_f(v[NP]) - mean, b = hi_f(v[NP]) - mean; vs += a * a + b * b; }
#pragma unroll
    for (int o = 16; o; o >>= 1) vs += __shfl_xor_sync(0xffffffffu, vs, o);
    float var = rbf(vs * (1.0f / W));
    float mb = rbf(mean);
    float den = rbf(sqrtf(rbf(var + 1e-5f)));
    uint32_t* d32 = reinterpret_cast<uint32_t*>(dst);
#pragma unroll
    for (int i = 0; i < NP; i++) d32[i * 32 + lane] = pack_bf16(rbf(lo_f(v[i]) - mb) / den, rbf(hi_f(v[i]) - mb) / den);
    if (REM && lane < REM) d32[NP * 32 + lane] = pack_bf16(rbf(lo_f(v[NP]) - mb) / den, rbf(hi_f(v[NP]) - mb) / den);
}

__global__ void ln_kernel(const bf16* __restrict__ x) {
    int row = blockIdx.x * 8 + (threadIdx.x >> 5);
    ln_row<D_>(x + (size_t)row * D_, g_xn + (size_t)row * D_, threadIdx.x & 31);
}
__global__ void ln2_kernel() {
    int row = blockIdx.x * 8 + (threadIdx.x >> 5);
    bf16* p = g_z + (size_t)row * F_ + FH_;
    ln_row<FH_>(p, p, threadIdx.x & 31);
}

enum { EPI_STORE = 0, EPI_GELU = 1, EPI_SP = 2, EPI_SILU = 3, EPI_FINAL = 4 };
struct EpiParams {
    bf16* out; int ldo;
    const bf16* aux0;
    const bf16* aux1;
};

__device__ __forceinline__ float gelu_tanh_f(float x) {
    const float k0 = 0.7978845608028654f, k1 = 0.044715f;
    float inner = k0 * (x + k1 * x * x * x);
    return 0.5f * x * (1.0f + tanhf(inner));
}
__device__ __forceinline__ float silu_f(float x) { return x / (1.0f + expf(-x)); }

template <int BN, int EPI>
__global__ void __launch_bounds__(384, 1)
gemm_kernel(const __grid_constant__ CUtensorMap tmA, const __grid_constant__ CUtensorMap tmB0,
            const __grid_constant__ CUtensorMap tmB1, const __grid_constant__ CUtensorMap tmB2,
            int nPerB, int N, int K, EpiParams ep) {
    constexpr int BM = 128, BK = 64;
    constexpr int A_BYTES = BM * BK * 2;
    constexpr int B_BYTES = (BN / 64) * 8192;
    constexpr int STAGE = A_BYTES + B_BYTES;
    constexpr int NST = (200 * 1024) / STAGE;
    constexpr int OLD = BN + 8;
    extern __shared__ __align__(1024) uint8_t smem_raw[];
    uint8_t* smem = (uint8_t*)(((uintptr_t)smem_raw + 1023) & ~(uintptr_t)1023);
    __shared__ __align__(8) uint64_t full_bar[NST], empty_bar[NST];

    const int tid = threadIdx.x, wg = tid >> 7;
    const int m0 = blockIdx.y * BM, n0 = blockIdx.x * BN;
    const int nk = (K + BK - 1) / BK;

    if (tid == 0) {
        for (int i = 0; i < NST; i++) { mbar_init(smem_u32(&full_bar[i]), 1); mbar_init(smem_u32(&empty_bar[i]), 2); }
        asm volatile("fence.mbarrier_init.release.cluster;" ::: "memory");
    }
    __syncthreads();

    if (wg == 0) {
        if (tid == 0) {
            const int bsel = n0 / nPerB;
            const CUtensorMap* tmB = bsel == 0 ? &tmB0 : (bsel == 1 ? &tmB1 : &tmB2);
            const int nb = n0 - bsel * nPerB;
            for (int kt = 0; kt < nk; kt++) {
                int st = kt % NST; uint32_t ph = (kt / NST) & 1;
                mbar_wait(smem_u32(&empty_bar[st]), ph ^ 1);
                uint32_t fb = smem_u32(&full_bar[st]);
                mbar_expect_tx(fb, STAGE);
                uint32_t sa = smem_u32(smem + st * STAGE);
                tma_load_2d(sa, &tmA, fb, kt * BK, m0);
#pragma unroll
                for (int j = 0; j < BN / 64; j++) tma_load_2d(sa + A_BYTES + j * 8192, tmB, fb, nb + j * 64, kt * BK);
            }
        }
    } else {
        const int cw = wg - 1;
        float acc[BN / 2];
        for (int kt = 0; kt < nk; kt++) {
            int st = kt % NST; uint32_t ph = (kt / NST) & 1;
            mbar_wait(smem_u32(&full_bar[st]), ph);
            uint32_t sa = smem_u32(smem + st * STAGE) + cw * 64 * 128;
            uint32_t sb = smem_u32(smem + st * STAGE) + A_BYTES;
            wgmma_fence();
#pragma unroll
            for (int k = 0; k < BK / 16; k++) {
                uint64_t da = make_desc(sa + k * 32, 16, 1024);
                uint64_t db = make_desc(sb + k * 2048, 8192, 1024);
                Wgmma<BN>::mma(acc, da, db, (kt | k) != 0);
            }
            wgmma_commit();
            wgmma_wait<1>();
            if (kt > 0 && (tid & 127) == 0) mbar_arrive(smem_u32(&empty_bar[(kt - 1) % NST]));
        }
        wgmma_wait<0>();
        asm volatile("bar.sync 1, 256;" ::: "memory");
        const int lane = tid & 31, wi = (tid >> 5) & 3, g = lane >> 2, t = lane & 3;
        bf16* stg = reinterpret_cast<bf16*>(smem) + cw * 64 * OLD;
#pragma unroll
        for (int j = 0; j < BN / 8; j++) {
            *reinterpret_cast<uint32_t*>(&stg[(wi * 16 + g) * OLD + j * 8 + 2 * t]) = pack_bf16(acc[4 * j], acc[4 * j + 1]);
            *reinterpret_cast<uint32_t*>(&stg[(wi * 16 + g + 8) * OLD + j * 8 + 2 * t]) = pack_bf16(acc[4 * j + 2], acc[4 * j + 3]);
        }
        asm volatile("bar.sync %0, 128;" ::"r"(2 + cw) : "memory");
        constexpr int CPR = BN / 8;
        const int ltid = tid & 127;
#pragma unroll 4
        for (int i = ltid; i < 64 * CPR; i += 128) {
            int r = i / CPR, ch = i % CPR;
            int row = m0 + cw * 64 + r, col = n0 + ch * 8;
            if (col >= N) continue;
            uint4 v = *reinterpret_cast<const uint4*>(&stg[r * OLD + ch * 8]);
            uint32_t u[4] = {v.x, v.y, v.z, v.w}, o[4];
            if (EPI == EPI_STORE) {
#pragma unroll
                for (int q = 0; q < 4; q++) o[q] = u[q];
            } else if (EPI == EPI_GELU) {
#pragma unroll
                for (int q = 0; q < 4; q++) o[q] = pack_bf16(gelu_tanh_f(lo_f(u[q])), gelu_tanh_f(hi_f(u[q])));
            } else if (EPI == EPI_SP) {
                float bb = bf2f(ep.aux1[row]);
                uint4 z = *reinterpret_cast<const uint4*>(ep.aux0 + (size_t)row * F_ + col);
                uint32_t zz[4] = {z.x, z.y, z.z, z.w};
#pragma unroll
                for (int q = 0; q < 4; q++) o[q] = pack_bf16(lo_f(zz[q]) * rbf(lo_f(u[q]) + bb), hi_f(zz[q]) * rbf(hi_f(u[q]) + bb));
            } else if (EPI == EPI_SILU) {
#pragma unroll
                for (int q = 0; q < 4; q++) o[q] = pack_bf16(silu_f(lo_f(u[q])), silu_f(hi_f(u[q])));
            } else {
                uint4 xv = *reinterpret_cast<const uint4*>(ep.aux0 + (size_t)row * D_ + col);
                uint4 gv = *reinterpret_cast<const uint4*>(ep.aux1 + (size_t)row * D_ + col);
                uint32_t xx[4] = {xv.x, xv.y, xv.z, xv.w}, gg[4] = {gv.x, gv.y, gv.z, gv.w};
#pragma unroll
                for (int q = 0; q < 4; q++)
                    o[q] = pack_bf16(lo_f(xx[q]) + rbf(lo_f(u[q]) * lo_f(gg[q])), hi_f(xx[q]) + rbf(hi_f(u[q]) * hi_f(gg[q])));
            }
            *reinterpret_cast<uint4*>(ep.out + (size_t)row * ep.ldo + col) = make_uint4(o[0], o[1], o[2], o[3]);
        }
    }
}

__device__ __forceinline__ void mma16816(float* c, const uint32_t* a, uint32_t b0, uint32_t b1) {
    asm volatile(
        "mma.sync.aligned.m16n8k16.row.col.f32.bf16.bf16.f32 {%0,%1,%2,%3}, {%4,%5,%6,%7}, {%8,%9}, {%0,%1,%2,%3};"
        : "+f"(c[0]), "+f"(c[1]), "+f"(c[2]), "+f"(c[3])
        : "r"(a[0]), "r"(a[1]), "r"(a[2]), "r"(a[3]), "r"(b0), "r"(b1));
}
__device__ __forceinline__ void ldsm_x4(uint32_t* r, uint32_t addr) {
    asm volatile("ldmatrix.sync.aligned.m8n8.x4.shared.b16 {%0,%1,%2,%3}, [%4];"
                 : "=r"(r[0]), "=r"(r[1]), "=r"(r[2]), "=r"(r[3]) : "r"(addr));
}
__device__ __forceinline__ void ldsm_x4_t(uint32_t* r, uint32_t addr) {
    asm volatile("ldmatrix.sync.aligned.m8n8.x4.trans.shared.b16 {%0,%1,%2,%3}, [%4];"
                 : "=r"(r[0]), "=r"(r[1]), "=r"(r[2]), "=r"(r[3]) : "r"(addr));
}
__device__ __forceinline__ uint4 ld_relaxed_v4(const void* p) {
    uint4 v;
    asm volatile("ld.relaxed.gpu.global.v4.u32 {%0,%1,%2,%3}, [%4];" : "=r"(v.x), "=r"(v.y), "=r"(v.z), "=r"(v.w) : "l"(p) : "memory");
    return v;
}
__device__ __forceinline__ void st_relaxed_v4(void* p, uint32_t a, uint32_t b, uint32_t c, uint32_t d) {
    asm volatile("st.relaxed.gpu.global.v4.u32 [%0], {%1,%2,%3,%4};" ::"l"(p), "r"(a), "r"(b), "r"(c), "r"(d) : "memory");
}
__device__ __forceinline__ void st_relaxed_v2(void* p, uint32_t a, uint32_t b) {
    asm volatile("st.relaxed.gpu.global.v2.u32 [%0], {%1,%2};" ::"l"(p), "r"(a), "r"(b) : "memory");
}
__device__ __forceinline__ void cp_async16(uint32_t dst, const void* src) {
    asm volatile("cp.async.cg.shared.global [%0], [%1], 16;" ::"r"(dst), "l"(src) : "memory");
}
__device__ __forceinline__ void cp_async_commit() { asm volatile("cp.async.commit_group;" ::: "memory"); }
template <int N> __device__ __forceinline__ void cp_async_wait() { asm volatile("cp.async.wait_group %0;" ::"n"(N) : "memory"); }

#define PROF(i) do {} while (0)
constexpr int SPIN_LIMIT = 4000000;

__device__ __forceinline__ uint4 poll_ll(const void* p, uint32_t flag) {
    uint4 v = ld_relaxed_v4(p);
    int n = 0;
    while ((v.y != flag || v.w != flag) && ++n < SPIN_LIMIT) {
        v = ld_relaxed_v4(p);
    }
    return v;
}

constexpr int RT = 512;
constexpr int MEMS_LD = D_ + 8;
constexpr int HL = DH_ + 8;
struct RecurSmem {
    bf16 mem[MEM_][MEMS_LD];
    bf16 kall[2][48][HL];
    bf16 vall[2][48][HL];
    bf16 qm[16][HL];
    float sc[MEM_][40];
    bf16 p[MEM_][48 + 8];
    bf16 om[MEM_][HL];
    float red[12][16 * 8];
    float wred[2][5][16 * 8];
    bf16 xs[SEG_][MEMS_LD];
    float redx[6][4][16 * 8];
};

__device__ __forceinline__ void bar_sync(int id, int n) { asm volatile("bar.sync %0, %1;" ::"r"(id), "r"(n) : "memory"); }
__device__ __forceinline__ void bar_arrive(int id, int n) { asm volatile("bar.arrive %0, %1;" ::"r"(id), "r"(n) : "memory"); }
__device__ __forceinline__ void sts64(uint32_t a, uint32_t x, uint32_t y) { asm volatile("st.shared.v2.u32 [%0], {%1,%2};" ::"r"(a), "r"(x), "r"(y) : "memory"); }
__device__ __forceinline__ uint32_t ldg_u16x2(const bf16* p0, const bf16* p1) {
    return (uint32_t)*(const uint16_t*)p0 | ((uint32_t)*(const uint16_t*)p1 << 16);
}
enum { BAR_MEM = 1, BAR_RED = 2, BAR_CTL = 3, BAR_WO = 4, BAR_INIT = 6, BAR_X = 7 };

__global__ void __launch_bounds__(RT, 1)
recur_kernel(const bf16* __restrict__ mem0, const bf16* __restrict__ Wq, const bf16* __restrict__ Wk,
             const bf16* __restrict__ Wv, const bf16* __restrict__ Wo) {
    extern __shared__ __align__(16) uint8_t smem_raw[];
    RecurSmem& sm = *reinterpret_cast<RecurSmem*>(smem_raw);
    const int tid = threadIdx.x, lane = tid & 31, w = tid >> 5;
    const int g = lane >> 2, t = lane & 3;
    const int h = blockIdx.x >> 2, c = blockIdx.x & 3;

    if (w < 12) {
        asm volatile("setmaxnreg.dec.sync.aligned.u32 112;");
        uint32_t wf[20][4];
        const int mt = w % 6, kh = w / 6;
        {
            const bf16* W = (mt < 2) ? Wq : (mt < 4 ? Wk : Wv);
            int f0 = h * DH_ + c * 32 + (mt & 1) * 16;
            uint32_t stg = smem_u32(smem_raw) + w * 10240;
#pragma unroll 4
            for (int i = lane; i < 640; i += 32)
                cp_async16(stg + i * 16, W + (size_t)(kh * 320 + (i >> 1)) * HD_ + f0 + (i & 1) * 8);
            cp_async_commit(); cp_async_wait<0>(); __syncwarp();
            uint32_t la = stg + ((lane & 7) + ((lane >> 4) & 1) * 8) * 32 + ((lane >> 3) & 1) * 16;
#pragma unroll
            for (int i = 0; i < 20; i++) ldsm_x4_t(wf[i], la + i * 512);
        }
        bar_sync(BAR_INIT, RT);
        const uint32_t base = smem_u32(&sm.mem[lane & 7][kh * 320 + (lane >> 3) * 8]);
        const uint32_t rp = smem_u32(&sm.red[w][g * 8 + 2 * t]);
        const uint32_t xbase = smem_u32(&sm.xs[lane & 7][kh * 320 + (lane >> 3) * 8]);
        const uint32_t rxp = smem_u32(&sm.redx[mt][0][lane * 4]);
        auto load_x = [&](int seg) {
            for (int i = tid; i < SEG_ * (D_ / 8); i += 384) {
                int r = i / (D_ / 8), ch = i % (D_ / 8);
                cp_async16(smem_u32(&sm.xs[r][ch * 8]), g_xn + (size_t)(seg * SEG_ + r) * D_ + ch * 8);
            }
            cp_async_commit();
        };
        auto xwork = [&](int seg) {
            cp_async_wait<0>();
            bar_sync(BAR_X, 384);
            float acc[4][4];
#pragma unroll
            for (int nt = 0; nt < 4; nt++) {
                float a0[4] = {0.f, 0.f, 0.f, 0.f}, a1[4] = {0.f, 0.f, 0.f, 0.f};
#pragma unroll
                for (int i = 0; i < 10; i++) {
                    uint32_t b[4];
                    ldsm_x4(b, xbase + nt * (8 * MEMS_LD * 2) + i * 64);
                    mma16816(a0, wf[2 * i], b[0], b[1]);
                    mma16816(a1, wf[2 * i + 1], b[2], b[3]);
                }
#pragma unroll
                for (int e = 0; e < 4; e++) acc[nt][e] = a0[e] + a1[e];
            }
            if (kh == 1) {
#pragma unroll
                for (int nt = 0; nt < 4; nt++)
                    asm volatile("st.shared.v4.f32 [%0], {%1,%2,%3,%4};" ::"r"(rxp + nt * 512), "f"(acc[nt][0]), "f"(acc[nt][1]), "f"(acc[nt][2]), "f"(acc[nt][3]) : "memory");
            }
            bar_sync(BAR_X, 384);
            if (seg + 1 < NSEG_) load_x(seg + 1);
            if (kh == 0) {
                bf16* dst = g_qkv + (size_t)(seg * SEG_ + 2 * t) * (3 * HD_) + (mt >> 1) * HD_ + h * DH_ + c * 32 + (mt & 1) * 16 + g;
#pragma unroll
                for (int nt = 0; nt < 4; nt++) {
                    float4 o;
                    asm volatile("ld.shared.v4.f32 {%0,%1,%2,%3}, [%4];" : "=f"(o.x), "=f"(o.y), "=f"(o.z), "=f"(o.w) : "r"(rxp + nt * 512) : "memory");
                    bf16* d = dst + (size_t)nt * 8 * (3 * HD_);
                    d[0] = __float2bfloat16_rn(acc[nt][0] + o.x);
                    d[3 * HD_] = __float2bfloat16_rn(acc[nt][1] + o.y);
                    d[8] = __float2bfloat16_rn(acc[nt][2] + o.z);
                    d[3 * HD_ + 8] = __float2bfloat16_rn(acc[nt][3] + o.w);
                }
                __threadfence();
                __syncwarp();
                if (lane == 0) atomicAdd(&g_xcnt[h * NSEG_ + seg], 1u);
            }
        };
        load_x(0);
        xwork(0);
        xwork(1);
        for (int s = 0; s < NSEG_; s++) {
            bar_sync(BAR_MEM, RT);
            float a0[4] = {0.f, 0.f, 0.f, 0.f}, a1[4] = {0.f, 0.f, 0.f, 0.f};
#pragma unroll
            for (int i = 0; i < 10; i++) {
                uint32_t b[4];
                ldsm_x4(b, base + i * 64);
                mma16816(a0, wf[2 * i], b[0], b[1]);
                mma16816(a1, wf[2 * i + 1], b[2], b[3]);
            }
            sts64(rp, __float_as_uint(a0[0] + a1[0]), __float_as_uint(a0[1] + a1[1]));
            sts64(rp + 256, __float_as_uint(a0[2] + a1[2]), __float_as_uint(a0[3] + a1[3]));
            bar_arrive(BAR_RED, RT);
            if (s + 2 < NSEG_) xwork(s + 2);
        }
    } else {
        asm volatile("setmaxnreg.inc.sync.aligned.u32 176;");
        const int ct = tid - 384, cw = w - 12;
        const int mg = cw >> 1, kh = cw & 1;
        uint32_t wf[20][4];
        {
            uint32_t stg = smem_u32(smem_raw) + 12 * 10240 + cw * 10240;
#pragma unroll 4
            for (int i = lane; i < 640; i += 32) {
                int r = i / 10, ch = i % 10;
                cp_async16(stg + r * 160 + ch * 16, Wo + (size_t)(h * DH_ + kh * 64 + r) * D_ + c * 160 + mg * 80 + ch * 8);
            }
            cp_async_commit(); cp_async_wait<0>(); __syncwarp();
            uint32_t la = stg + ((lane & 7) + ((lane >> 4) & 1) * 8) * 160 + ((lane >> 3) & 1) * 16;
#pragma unroll
            for (int mi = 0; mi < 5; mi++)
#pragma unroll
                for (int ki = 0; ki < 4; ki++) ldsm_x4_t(wf[mi * 4 + ki], la + ki * 16 * 160 + mi * 32);
        }
        bar_sync(BAR_INIT, RT);
        for (int i = ct; i < 2 * 8 * HL; i += 128) {
            int b = i / (8 * HL), r = (i / HL) % 8, cc = i % HL;
            sm.kall[b][40 + r][cc] = __float2bfloat16(0.f);
            sm.vall[b][40 + r][cc] = __float2bfloat16(0.f);
        }
        for (int i = ct; i < 8 * HL; i += 128) sm.qm[8 + i / HL][i % HL] = __float2bfloat16(0.f);
        for (int i = ct; i < 8 * 56; i += 128) sm.p[i / 56][i % 56] = __float2bfloat16(0.f);
        bar_sync(BAR_CTL, 128);
        constexpr uint32_t KV_BUF = 48 * HL * 2;
        const bf16* kv_src = g_qkv + (size_t)(ct >> 4) * (3 * HD_) + HD_ + h * DH_ + (ct & 15) * 8;
        const uint32_t kv_dst0 = smem_u32(&sm.kall[0][MEM_ + (ct >> 4)][(ct & 15) * 8]);
        const uint32_t kv_dst1 = smem_u32(&sm.vall[0][MEM_ + (ct >> 4)][(ct & 15) * 8]);
        auto prefetch_kv = [&](int s, int buf) {
            if (ct == 0) {
                const unsigned* cp = g_xcnt + h * NSEG_ + s;
                unsigned v; int n = 0;
                do { asm volatile("ld.acquire.gpu.global.u32 %0, [%1];" : "=r"(v) : "l"(cp) : "memory"); } while (v < 24u && ++n < SPIN_LIMIT);
            }
            bar_sync(BAR_CTL, 128);
            const bf16* src = kv_src + (size_t)s * SEG_ * (3 * HD_);
#pragma unroll
            for (int j = 0; j < 4; j++) {
                cp_async16(kv_dst0 + buf * KV_BUF + j * (8 * HL * 2), src + (size_t)j * 8 * (3 * HD_));
                cp_async16(kv_dst1 + buf * KV_BUF + j * (8 * HL * 2), src + (size_t)j * 8 * (3 * HD_) + HD_);
            }
            cp_async_commit();
        };
        const float4* acc_src = reinterpret_cast<const float4*>(g_acc) + ct;
        const uint32_t acc_dst = smem_u32(&sm.mem[(ct & 1) * 4][ct >> 1]);
        const uint4* hx_base = reinterpret_cast<const uint4*>(g_hx) + h * 1024;
        const int hx_rq = ct & 63, hx_half = ct >> 6;
        const uint4* hx_src = hx_base + hx_half * 64 + hx_rq;
        const uint32_t hx_col = (hx_rq & 7) * 8, hx_r = hx_rq >> 3;
        const uint32_t hx_dstA = (hx_half == 0 ? smem_u32(&sm.qm[hx_r][0]) : smem_u32(&sm.kall[0][hx_r][0])) + hx_col;
        const uint32_t hx_dstB = smem_u32(&sm.vall[0][hx_r][0]) + hx_col;
        const uint4* hx_probe = hx_base + (lane >> 3) * 256 + ((lane & 7) % 3) * 64 + (lane & 7) * 8 + 3;
        const int pb_r = ct >> 4, pb_pr = ct & 15;
        uint2* pb_dst = g_hx + (h * 1024 + c * 256 + pb_r * 8) * 2 + pb_pr;
        const float* pb_src = &sm.red[pb_pr >> 3][(pb_pr & 7) * 16 + pb_r];
        bf16* pb_k = g_kmem + (size_t)pb_r * HD_ + h * DH_ + c * 32 + pb_pr * 2;
        bf16* pb_v = g_vmem + (size_t)pb_r * HD_ + h * DH_ + c * 32 + pb_pr * 2;
        const uint32_t qa = smem_u32(&sm.qm[lane & 15][(lane >> 4) * 8]);
        const uint32_t kb0 = smem_u32(&sm.kall[0][cw * 8 + (lane & 7)][(lane >> 3) * 8]);
        const uint32_t va0 = smem_u32(&sm.vall[0][(lane & 7) + ((lane >> 4) & 1) * 8][cw * 32 + ((lane >> 3) & 1) * 8]);
        const uint32_t pbaddr = smem_u32(&sm.p[lane & 7][((lane >> 3) & 1) * 8]);
        const uint32_t ob = smem_u32(&sm.om[lane & 7][kh * 64 + (lane >> 3) * 8]);
        float* acc_dst_g = g_acc + (c * 160 + mg * 80 + g) * 8 + 2 * t;

        prefetch_kv(0, 0);
        for (int s = 0; s < NSEG_; s++) {
            const int buf = s & 1;
            const uint32_t flag = s + 1;
            const uint32_t bo = buf * KV_BUF;
            PROF(0);
            if (s == 0) {
                for (int i = ct; i < MEM_ * D_ / 8; i += 128) {
                    int r = i / (D_ / 8), cc = (i % (D_ / 8)) * 8;
                    *reinterpret_cast<uint4*>(&sm.mem[r][cc]) = *reinterpret_cast<const uint4*>(mem0 + r * D_ + cc);
                }
            } else {
                if (ct == 0) {
                    const unsigned* cp = g_cnt + (s - 1) * 32;
                    unsigned v; int n = 0;
                    do { asm volatile("ld.acquire.gpu.global.u32 %0, [%1];" : "=r"(v) : "l"(cp) : "memory"); } while (v < 256u && ++n < SPIN_LIMIT);
                }
                bar_sync(BAR_CTL, 128);
                PROF(1);
                const float4* src = acc_src + (size_t)(s - 1) * (MEM_ * D_ / 4);
                float4 v[10];
#pragma unroll
                for (int j = 0; j < 10; j++)
                    asm volatile("ld.relaxed.gpu.global.v4.f32 {%0,%1,%2,%3}, [%4];" : "=f"(v[j].x), "=f"(v[j].y), "=f"(v[j].z), "=f"(v[j].w) : "l"(src + 128 * j) : "memory");
#pragma unroll
                for (int j = 0; j < 10; j++) {
                    uint32_t lo = pack_bf16(v[j].x, v[j].y), hi = pack_bf16(v[j].z, v[j].w);
                    uint32_t d = acc_dst + j * 128;
                    asm volatile("st.shared.u16 [%0], %1;" ::"r"(d), "h"((uint16_t)(lo & 0xffff)) : "memory");
                    asm volatile("st.shared.u16 [%0], %1;" ::"r"(d + MEMS_LD * 2), "h"((uint16_t)(lo >> 16)) : "memory");
                    asm volatile("st.shared.u16 [%0], %1;" ::"r"(d + MEMS_LD * 4), "h"((uint16_t)(hi & 0xffff)) : "memory");
                    asm volatile("st.shared.u16 [%0], %1;" ::"r"(d + MEMS_LD * 6), "h"((uint16_t)(hi >> 16)) : "memory");
                }
            }
            bar_arrive(BAR_MEM, RT);
            PROF(2);
            bar_sync(BAR_RED, RT);
            PROF(3);
            {
                uint32_t pk0 = pack_bf16(pb_src[0] + pb_src[768], pb_src[8] + pb_src[768 + 8]);
                uint32_t pk1 = pack_bf16(pb_src[256] + pb_src[1024], pb_src[256 + 8] + pb_src[1024 + 8]);
                uint32_t pk2 = pack_bf16(pb_src[512] + pb_src[1280], pb_src[512 + 8] + pb_src[1280 + 8]);
                st_relaxed_v2(pb_dst, pk0, flag);
                st_relaxed_v2(pb_dst + 128, pk1, flag);
                st_relaxed_v2(pb_dst + 256, pk2, flag);
                *reinterpret_cast<uint32_t*>(pb_k + (size_t)s * (MEM_ * HD_)) = pk1;
                *reinterpret_cast<uint32_t*>(pb_v + (size_t)s * (MEM_ * HD_)) = pk2;
            }
            if (s == NSEG_ - 1) break;
            PROF(4);
            if (cw == 0) (void)poll_ll(hx_probe, flag);
            bar_sync(BAR_CTL, 128);
            PROF(5);
            {
                uint4 v[8];
#pragma unroll
                for (int j = 0; j < 4; j++) v[j] = ld_relaxed_v4(hx_src + j * 256);
                if (hx_half == 0) {
#pragma unroll
                    for (int j = 0; j < 4; j++) v[4 + j] = ld_relaxed_v4(hx_src + j * 256 + 128);
                }
#pragma unroll
                for (int j = 0; j < 4; j++) {
                    if (v[j].y != flag || v[j].w != flag) v[j] = poll_ll(hx_src + j * 256, flag);
                    sts64(hx_dstA + j * 64 + (hx_half ? bo : 0), v[j].x, v[j].z);
                }
                if (hx_half == 0) {
#pragma unroll
                    for (int j = 0; j < 4; j++) {
                        if (v[4 + j].y != flag || v[4 + j].w != flag) v[4 + j] = poll_ll(hx_src + j * 256 + 128, flag);
                        sts64(hx_dstB + j * 64 + bo, v[4 + j].x, v[4 + j].z);
                    }
                }
            }
            cp_async_wait<0>();
            bar_sync(BAR_CTL, 128);
            PROF(6);
            {
                uint32_t a[8][4], b[4][4], b2[4][4];
#pragma unroll
                for (int kk = 0; kk < 4; kk++) ldsm_x4(b[kk], kb0 + bo + kk * 64);
                if (cw == 0) {
#pragma unroll
                    for (int kk = 0; kk < 4; kk++) ldsm_x4(b2[kk], kb0 + bo + 32 * HL * 2 + kk * 64);
                }
#pragma unroll
                for (int kk = 0; kk < 8; kk++) ldsm_x4(a[kk], qa + kk * 32);
                float s0[4] = {0.f, 0.f, 0.f, 0.f}, s1[4] = {0.f, 0.f, 0.f, 0.f};
#pragma unroll
                for (int kk = 0; kk < 4; kk++) { mma16816(s0, a[2 * kk], b[kk][0], b[kk][1]); mma16816(s1, a[2 * kk + 1], b[kk][2], b[kk][3]); }
                const float scale = 0.08838834764831845f;
                *reinterpret_cast<float2*>(&sm.sc[g][cw * 8 + 2 * t]) =
                    make_float2(rbf(rbf(s0[0] + s1[0]) * scale), rbf(rbf(s0[1] + s1[1]) * scale));
                if (cw == 0) {
                    float u0[4] = {0.f, 0.f, 0.f, 0.f}, u1[4] = {0.f, 0.f, 0.f, 0.f};
#pragma unroll
                    for (int kk = 0; kk < 4; kk++) { mma16816(u0, a[2 * kk], b2[kk][0], b2[kk][1]); mma16816(u1, a[2 * kk + 1], b2[kk][2], b2[kk][3]); }
                    *reinterpret_cast<float2*>(&sm.sc[g][32 + 2 * t]) =
                        make_float2(rbf(rbf(u0[0] + u1[0]) * scale), rbf(rbf(u0[1] + u1[1]) * scale));
                }
            }
            bar_sync(BAR_CTL, 128);
            {
                float v0 = sm.sc[cw][lane], v1 = (lane < 8) ? sm.sc[cw][32 + lane] : -INFINITY;
                float y0 = sm.sc[cw + 4][lane], y1 = (lane < 8) ? sm.sc[cw + 4][32 + lane] : -INFINITY;
                float mx = fmaxf(v0, v1), my = fmaxf(y0, y1);
#pragma unroll
                for (int o = 16; o; o >>= 1) { mx = fmaxf(mx, __shfl_xor_sync(0xffffffffu, mx, o)); my = fmaxf(my, __shfl_xor_sync(0xffffffffu, my, o)); }
                float e0 = __expf(v0 - mx), e1 = (lane < 8) ? __expf(v1 - mx) : 0.f;
                float f0 = __expf(y0 - my), f1 = (lane < 8) ? __expf(y1 - my) : 0.f;
                float sx = e0 + e1, sy = f0 + f1;
#pragma unroll
                for (int o = 16; o; o >>= 1) { sx += __shfl_xor_sync(0xffffffffu, sx, o); sy += __shfl_xor_sync(0xffffffffu, sy, o); }
                float ix = 1.0f / sx, iy = 1.0f / sy;
                sm.p[cw][lane] = __float2bfloat16_rn(e0 * ix);
                sm.p[cw + 4][lane] = __float2bfloat16_rn(f0 * iy);
                if (lane < 8) { sm.p[cw][32 + lane] = __float2bfloat16_rn(e1 * ix); sm.p[cw + 4][32 + lane] = __float2bfloat16_rn(f1 * iy); }
            }
            bar_sync(BAR_CTL, 128);
            PROF(7);
            {
                uint32_t a[2][3][4], b[3][2];
#pragma unroll
                for (int kt = 0; kt < 3; kt++) {
                    asm volatile("ldmatrix.sync.aligned.m8n8.x2.shared.b16 {%0,%1}, [%2];" : "=r"(b[kt][0]), "=r"(b[kt][1]) : "r"(pbaddr + kt * 32));
                    ldsm_x4_t(a[0][kt], va0 + bo + kt * 16 * HL * 2);
                    ldsm_x4_t(a[1][kt], va0 + bo + kt * 16 * HL * 2 + 32);
                }
#pragma unroll
                for (int m = 0; m < 2; m++) {
                    float o[4] = {0.f, 0.f, 0.f, 0.f};
#pragma unroll
                    for (int kt = 0; kt < 3; kt++) mma16816(o, a[m][kt], b[kt][0], b[kt][1]);
                    int d0 = cw * 32 + m * 16 + g;
                    sm.om[2 * t][d0] = __float2bfloat16_rn(o[0]);
                    sm.om[2 * t + 1][d0] = __float2bfloat16_rn(o[1]);
                    sm.om[2 * t][d0 + 8] = __float2bfloat16_rn(o[2]);
                    sm.om[2 * t + 1][d0 + 8] = __float2bfloat16_rn(o[3]);
                }
            }
            bar_sync(BAR_CTL, 128);
            PROF(8);
            {
                float acc[5][4];
#pragma unroll
                for (int mi = 0; mi < 5; mi++) { acc[mi][0] = acc[mi][1] = acc[mi][2] = acc[mi][3] = 0.f; }
                uint32_t b[2][4];
                ldsm_x4(b[0], ob); ldsm_x4(b[1], ob + 64);
#pragma unroll
                for (int ki = 0; ki < 4; ki++)
#pragma unroll
                    for (int mi = 0; mi < 5; mi++) mma16816(acc[mi], wf[mi * 4 + ki], b[ki >> 1][(ki & 1) * 2], b[ki >> 1][(ki & 1) * 2 + 1]);
                if (kh == 1) {
#pragma unroll
                    for (int mi = 0; mi < 5; mi++)
                        *reinterpret_cast<float4*>(&sm.wred[mg][mi][lane * 4]) = make_float4(acc[mi][0], acc[mi][1], acc[mi][2], acc[mi][3]);
                }
                bar_sync(BAR_WO + mg, 64);
                if (kh == 0) {
                    float* dst = acc_dst_g + (size_t)s * (MEM_ * D_);
#pragma unroll
                    for (int mi = 0; mi < 5; mi++) {
                        float4 o2 = *reinterpret_cast<float4*>(&sm.wred[mg][mi][lane * 4]);
                        asm volatile("red.global.add.v2.f32 [%0], {%1,%2};" ::"l"(dst + mi * 128), "f"(acc[mi][0] + o2.x), "f"(acc[mi][1] + o2.y) : "memory");
                        asm volatile("red.global.add.v2.f32 [%0], {%1,%2};" ::"l"(dst + mi * 128 + 64), "f"(acc[mi][2] + o2.z), "f"(acc[mi][3] + o2.w) : "memory");
                    }
                    __threadfence();
                    __syncwarp();
                    if (lane == 0) atomicAdd(&g_cnt[s * 32], 1u);
                }
            }
            PROF(9);
            prefetch_kv(s + 1, buf ^ 1);
            PROF(10);
        }
    }
}

__global__ void __launch_bounds__(128)
attn_x_kernel() {
    __shared__ __align__(16) bf16 sq[32][HL], sk[48][HL], sv[48][HL];
    const int s = blockIdx.x >> 5, h = blockIdx.x & 31;
    const int tid = threadIdx.x, lane = tid & 31, w = tid >> 5, g = lane >> 2, t = lane & 3;
    for (int i = tid; i < (32 + 40 + 40) * 16; i += 128) {
        int r = i >> 4, ch = i & 15;
        const bf16* src; bf16* dst;
        if (r < 32) { src = g_qkv + (size_t)(s * SEG_ + r) * (3 * HD_) + h * DH_; dst = sq[r]; }
        else if (r < 72) { int rr = r - 32; dst = sk[rr];
            src = rr < 8 ? g_kmem + ((size_t)s * MEM_ + rr) * HD_ + h * DH_ : g_qkv + (size_t)(s * SEG_ + rr - 8) * (3 * HD_) + HD_ + h * DH_; }
        else { int rr = r - 72; dst = sv[rr];
            src = rr < 8 ? g_vmem + ((size_t)s * MEM_ + rr) * HD_ + h * DH_ : g_qkv + (size_t)(s * SEG_ + rr - 8) * (3 * HD_) + 2 * HD_ + h * DH_; }
        cp_async16(smem_u32(dst + ch * 8), src + ch * 8);
    }
    cp_async_commit();
    for (int i = tid; i < 8 * 16; i += 128) *reinterpret_cast<uint4*>(&sv[40 + (i >> 4)][(i & 15) * 8]) = make_uint4(0, 0, 0, 0);
    cp_async_wait<0>();
    __syncthreads();
    const int rh = w & 1, dhh = w >> 1;
    float sc[5][4];
#pragma unroll
    for (int n = 0; n < 5; n++) sc[n][0] = sc[n][1] = sc[n][2] = sc[n][3] = 0.f;
#pragma unroll
    for (int kk = 0; kk < 8; kk++) {
        uint32_t a[4];
        ldsm_x4(a, smem_u32(&sq[rh * 16 + (lane & 15)][kk * 16 + (lane >> 4) * 8]));
#pragma unroll
        for (int n = 0; n < 5; n++) {
            uint32_t b[2];
            asm volatile("ldmatrix.sync.aligned.m8n8.x2.shared.b16 {%0,%1}, [%2];" : "=r"(b[0]), "=r"(b[1])
                         : "r"(smem_u32(&sk[n * 8 + (lane & 7)][kk * 16 + ((lane >> 3) & 1) * 8])));
            mma16816(sc[n], a, b[0], b[1]);
        }
    }
    const float scale = 0.08838834764831845f;
    float mx[2] = {-INFINITY, -INFINITY};
#pragma unroll
    for (int n = 0; n < 5; n++)
#pragma unroll
        for (int e = 0; e < 4; e++) {
            int row = rh * 16 + g + (e >> 1) * 8, key = n * 8 + 2 * t + (e & 1);
            float v = rbf(rbf(sc[n][e]) * scale);
            if (key > row + MEM_) v = -INFINITY;
            sc[n][e] = v;
            mx[e >> 1] = fmaxf(mx[e >> 1], v);
        }
#pragma unroll
    for (int o = 1; o < 4; o <<= 1) { mx[0] = fmaxf(mx[0], __shfl_xor_sync(0xffffffffu, mx[0], o)); mx[1] = fmaxf(mx[1], __shfl_xor_sync(0xffffffffu, mx[1], o)); }
    float sum[2] = {0.f, 0.f};
#pragma unroll
    for (int n = 0; n < 5; n++)
#pragma unroll
        for (int e = 0; e < 4; e++) { float ev = __expf(sc[n][e] - mx[e >> 1]); sc[n][e] = ev; sum[e >> 1] += ev; }
#pragma unroll
    for (int o = 1; o < 4; o <<= 1) { sum[0] += __shfl_xor_sync(0xffffffffu, sum[0], o); sum[1] += __shfl_xor_sync(0xffffffffu, sum[1], o); }
    float inv[2] = {1.0f / sum[0], 1.0f / sum[1]};
    uint32_t pa[3][4];
#pragma unroll
    for (int kt = 0; kt < 3; kt++) {
        pa[kt][0] = pack_bf16(sc[2 * kt][0] * inv[0], sc[2 * kt][1] * inv[0]);
        pa[kt][1] = pack_bf16(sc[2 * kt][2] * inv[1], sc[2 * kt][3] * inv[1]);
        if (kt < 2) {
            pa[kt][2] = pack_bf16(sc[2 * kt + 1][0] * inv[0], sc[2 * kt + 1][1] * inv[0]);
            pa[kt][3] = pack_bf16(sc[2 * kt + 1][2] * inv[1], sc[2 * kt + 1][3] * inv[1]);
        } else { pa[kt][2] = 0u; pa[kt][3] = 0u; }
    }
#pragma unroll
    for (int n = 0; n < 8; n++) {
        float o[4] = {0.f, 0.f, 0.f, 0.f};
#pragma unroll
        for (int kt = 0; kt < 3; kt++) {
            uint32_t b[2];
            asm volatile("ldmatrix.sync.aligned.m8n8.x2.trans.shared.b16 {%0,%1}, [%2];" : "=r"(b[0]), "=r"(b[1])
                         : "r"(smem_u32(&sv[kt * 16 + (lane & 15)][dhh * 64 + n * 8])));
            mma16816(o, pa[kt], b[0], b[1]);
        }
        int row = s * SEG_ + rh * 16 + g;
        bf16* dst = g_o + (size_t)row * HD_ + h * DH_ + dhh * 64 + n * 8 + 2 * t;
        *reinterpret_cast<uint32_t*>(dst) = pack_bf16(o[0], o[1]);
        *reinterpret_cast<uint32_t*>(dst + 8 * HD_) = pack_bf16(o[2], o[3]);
    }
}

typedef CUresult (*PFN_encodeTiled)(CUtensorMap*, CUtensorMapDataType, cuuint32_t, void*, const cuuint64_t*,
                                    const cuuint64_t*, const cuuint32_t*, const cuuint32_t*, CUtensorMapInterleave,
                                    CUtensorMapSwizzle, CUtensorMapL2promotion, CUtensorMapFloatOOBfill);
static PFN_encodeTiled p_encode = nullptr;

static CUtensorMap make_map(const void* ptr, uint64_t rows, uint64_t cols, uint64_t ld, uint32_t box_rows) {
    CUtensorMap m;
    cuuint64_t dims[2] = {cols, rows};
    cuuint64_t strides[1] = {ld * 2};
    cuuint32_t box[2] = {64, box_rows};
    cuuint32_t es[2] = {1, 1};
    p_encode(&m, CU_TENSOR_MAP_DATA_TYPE_BFLOAT16, 2, const_cast<void*>(ptr), dims, strides, box, es,
             CU_TENSOR_MAP_INTERLEAVE_NONE, CU_TENSOR_MAP_SWIZZLE_128B, CU_TENSOR_MAP_L2_PROMOTION_L2_128B,
             CU_TENSOR_MAP_FLOAT_OOB_FILL_NONE);
    return m;
}

template <int BN, int EPI>
static void launch_gemm(const CUtensorMap& a, const CUtensorMap& b0, const CUtensorMap& b1, const CUtensorMap& b2,
                        int nPerB, int M, int N, int K, EpiParams ep, cudaStream_t st) {
    constexpr int STAGE = 16384 + (BN / 64) * 8192;
    constexpr int NST = (200 * 1024) / STAGE;
    constexpr int SMEM = NST * STAGE + 1024;
    cudaFuncSetAttribute(gemm_kernel<BN, EPI>, cudaFuncAttributeMaxDynamicSharedMemorySize, SMEM);
    dim3 grid((N + BN - 1) / BN, M / 128);
    gemm_kernel<BN, EPI><<<grid, 384, SMEM, st>>>(a, b0, b1, b2, nPerB, N, K, ep);
}

extern "C" void kernel_launch(void* const* d_in, const int* in_sizes, int n_in, void* d_out, int out_size) {
    const bf16* x    = (const bf16*)d_in[0];
    const bf16* mem0 = (const bf16*)d_in[1];
    const bf16* Wq   = (const bf16*)d_in[2];
    const bf16* Wk   = (const bf16*)d_in[3];
    const bf16* Wv   = (const bf16*)d_in[4];
    const bf16* Wo   = (const bf16*)d_in[5];
    const bf16* w_in  = (const bf16*)d_in[8];
    const bf16* w_sp  = (const bf16*)d_in[9];
    const bf16* b_sp  = (const bf16*)d_in[10];
    const bf16* w_out = (const bf16*)d_in[11];
    bf16* out = (bf16*)d_out;
    cudaStream_t st = cudaStreamPerThread;

    if (!p_encode) {
        cudaDriverEntryPointQueryResult qr;
        cudaGetDriverEntryPoint("cuTensorMapEncodeTiled", (void**)&p_encode, cudaEnableDefault, &qr);
    }
    void *p_xn, *p_qkv, *p_z, *p_zg, *p_gate, *p_o, *p_acc, *p_cnt, *p_hx;
    cudaGetSymbolAddress(&p_xn, g_xn); cudaGetSymbolAddress(&p_qkv, g_qkv); cudaGetSymbolAddress(&p_z, g_z);
    cudaGetSymbolAddress(&p_zg, g_zg); cudaGetSymbolAddress(&p_gate, g_gate); cudaGetSymbolAddress(&p_o, g_o);
    cudaGetSymbolAddress(&p_acc, g_acc); cudaGetSymbolAddress(&p_cnt, g_cnt); cudaGetSymbolAddress(&p_hx, g_hx);

    CUtensorMap mA_xn  = make_map(p_xn, S_, D_, D_, 128);
    CUtensorMap mA_wsp = make_map(w_sp, S_, S_, S_, 128);
    CUtensorMap mA_zg  = make_map(p_zg, S_, FH_, FH_, 128);
    CUtensorMap mA_o   = make_map(p_o, S_, HD_, HD_, 128);
    CUtensorMap mB_wq  = make_map(Wq, D_, HD_, HD_, 64);
    CUtensorMap mB_wk  = make_map(Wk, D_, HD_, HD_, 64);
    CUtensorMap mB_wv  = make_map(Wv, D_, HD_, HD_, 64);
    CUtensorMap mB_win = make_map(w_in, D_, F_, F_, 64);
    CUtensorMap mB_z2  = make_map((bf16*)p_z + FH_, S_, FH_, F_, 64);
    CUtensorMap mB_wout = make_map(w_out, FH_, D_, D_, 64);
    CUtensorMap mB_wo  = make_map(Wo, HD_, D_, D_, 64);

    cudaMemsetAsync(p_acc, 0, sizeof(float) * NSEG_ * MEM_ * D_, st);
    cudaMemsetAsync(p_cnt, 0, sizeof(unsigned) * NSEG_ * 32, st);
    void* p_xcnt; cudaGetSymbolAddress(&p_xcnt, g_xcnt);
    cudaMemsetAsync(p_xcnt, 0, sizeof(unsigned) * H_ * NSEG_, st);
    cudaMemsetAsync(p_hx, 0, sizeof(uint2) * H_ * 4 * 256 * 2, st);

    ln_kernel<<<S_ / 8, 256, 0, st>>>(x);
    { EpiParams ep{(bf16*)p_z, F_, nullptr, nullptr}; launch_gemm<128, EPI_GELU>(mA_xn, mB_win, mB_win, mB_win, 1 << 20, S_, F_, D_, ep, st); }
    ln2_kernel<<<S_ / 8, 256, 0, st>>>();
    { EpiParams ep{(bf16*)p_zg, FH_, (const bf16*)p_z, b_sp}; launch_gemm<128, EPI_SP>(mA_wsp, mB_z2, mB_z2, mB_z2, 1 << 20, S_, FH_, S_, ep, st); }
    { EpiParams ep{(bf16*)p_gate, D_, nullptr, nullptr}; launch_gemm<128, EPI_SILU>(mA_zg, mB_wout, mB_wout, mB_wout, 1 << 20, S_, D_, FH_, ep, st); }
    constexpr int RSM = (int)sizeof(RecurSmem) > 16 * 10240 ? (int)sizeof(RecurSmem) : 16 * 10240;
    cudaFuncSetAttribute(recur_kernel, cudaFuncAttributeMaxDynamicSharedMemorySize, RSM);
    recur_kernel<<<128, RT, RSM, st>>>(mem0, Wq, Wk, Wv, Wo);
    attn_x_kernel<<<NSEG_ * H_, 128, 0, st>>>();
    { EpiParams ep{out, D_, x, (const bf16*)p_gate}; launch_gemm<128, EPI_FINAL>(mA_o, mB_wo, mB_wo, mB_wo, 1 << 20, S_, D_, HD_, ep, st); }
}
```

```cpp
#include <cuda_runtime.h>
#include <cuda_bf16.h>
#include <cuda.h>
#include <stdint.h>

typedef __nv_bfloat16 bf16;

constexpr int S_   = 2048;
constexpr int D_   = 640;
constexpr int H_   = 32;
constexpr int DH_  = 128;
constexpr int MEM_ = 8;
constexpr int SEG_ = 32;
constexpr int NSEG_ = S_ / SEG_;
constexpr int HD_  = H_ * DH_;
constexpr int F_   = 1728;
constexpr int FH_  = 864;

__device__ bf16 g_xn[S_ * D_];
__device__ bf16 g_qkv[(size_t)S_ * 3 * HD_];
__device__ bf16 g_z[S_ * F_];
__device__ bf16 g_zg[S_ * FH_];
__device__ bf16 g_gate[S_ * D_];
__device__ bf16 g_kmem[NSEG_ * MEM_ * HD_];
__device__ bf16 g_vmem[NSEG_ * MEM_ * HD_];
__device__ bf16 g_o[(size_t)S_ * HD_];
__device__ float g_acc[NSEG_ * MEM_ * D_];
__device__ unsigned g_cnt[NSEG_ * 32];
__device__ unsigned g_xcnt[H_ * NSEG_];
__device__ uint2 g_hx[H_ * 4 * 256 * 2];

__device__ __forceinline__ uint32_t smem_u32(const void* p) { return (uint32_t)__cvta_generic_to_shared(p); }
__device__ __forceinline__ float bf2f(bf16 v) { return __bfloat162float(v); }
__device__ __forceinline__ float rbf(float v) { return __bfloat162float(__float2bfloat16_rn(v)); }
__device__ __forceinline__ uint32_t pack_bf16(float lo, float hi) {
    __nv_bfloat162 t = __floats2bfloat162_rn(lo, hi);
    return *reinterpret_cast<uint32_t*>(&t);
}
__device__ __forceinline__ float lo_f(uint32_t u) { return __uint_as_float(u << 16); }
__device__ __forceinline__ float hi_f(uint32_t u) { return __uint_as_float(u & 0xffff0000u); }

__device__ __forceinline__ void mbar_init(uint32_t bar, uint32_t cnt) {
    asm volatile("mbarrier.init.shared.b64 [%0], %1;" ::"r"(bar), "r"(cnt));
}
__device__ __forceinline__ void mbar_expect_tx(uint32_t bar, uint32_t bytes) {
    asm volatile("mbarrier.arrive.expect_tx.shared.b64 _, [%0], %1;" ::"r"(bar), "r"(bytes) : "memory");
}
__device__ __forceinline__ void mbar_arrive(uint32_t bar) {
    asm volatile("mbarrier.arrive.shared.b64 _, [%0];" ::"r"(bar) : "memory");
}
__device__ __forceinline__ void mbar_wait(uint32_t bar, uint32_t parity) {
    asm volatile(
        "{\n .reg .pred p;\n"
        "WAIT_%=:\n"
        " mbarrier.try_wait.parity.shared.b64 p, [%0], %1;\n"
        " @p bra DONE_%=;\n"
        " bra WAIT_%=;\n"
        "DONE_%=:\n}\n" ::"r"(bar), "r"(parity) : "memory");
}
__device__ __forceinline__ void tma_load_2d(uint32_t dst, const CUtensorMap* tm, uint32_t bar, int c0, int c1) {
    asm volatile(
        "cp.async.bulk.tensor.2d.shared::cluster.global.mbarrier::complete_tx::bytes [%0], [%1, {%3, %4}], [%2];"
        ::"r"(dst), "l"(tm), "r"(bar), "r"(c0), "r"(c1) : "memory");
}
__device__ __forceinline__ void wgmma_fence() { asm volatile("wgmma.fence.sync.aligned;" ::: "memory"); }
__device__ __forceinline__ void wgmma_commit() { asm volatile("wgmma.commit_group.sync.aligned;" ::: "memory"); }
template <int N> __device__ __forceinline__ void wgmma_wait() { asm volatile("wgmma.wait_group.sync.aligned %0;" ::"n"(N) : "memory"); }

__device__ __forceinline__ uint64_t make_desc(uint32_t addr, uint32_t lbo, uint32_t sbo) {
    return (uint64_t)((addr & 0x3FFFF) >> 4) | ((uint64_t)(lbo >> 4) << 16) | ((uint64_t)(sbo >> 4) << 32) | (1ull << 62);
}

template <int N> struct Wgmma;
template <> struct Wgmma<128> {
    static __device__ __forceinline__ void mma(float* d, uint64_t da, uint64_t db, int sd) {
        asm volatile(
            "{\n.reg .pred p;\nsetp.ne.b32 p, %66, 0;\n"
            "wgmma.mma_async.sync.aligned.m64n128k16.f32.bf16.bf16 "
            "{%0,%1,%2,%3,%4,%5,%6,%7,%8,%9,%10,%11,%12,%13,%14,%15,"
            "%16,%17,%18,%19,%20,%21,%22,%23,%24,%25,%26,%27,%28,%29,%30,%31,"
            "%32,%33,%34,%35,%36,%37,%38,%39,%40,%41,%42,%43,%44,%45,%46,%47,"
            "%48,%49,%50,%51,%52,%53,%54,%55,%56,%57,%58,%59,%60,%61,%62,%63},"
            "%64,%65,p,1,1,0,1;\n}\n"
            : "+f"(d[0]), "+f"(d[1]), "+f"(d[2]), "+f"(d[3]), "+f"(d[4]), "+f"(d[5]), "+f"(d[6]), "+f"(d[7]),
              "+f"(d[8]), "+f"(d[9]), "+f"(d[10]), "+f"(d[11]), "+f"(d[12]), "+f"(d[13]), "+f"(d[14]), "+f"(d[15]),
              "+f"(d[16]), "+f"(d[17]), "+f"(d[18]), "+f"(d[19]), "+f"(d[20]), "+f"(d[21]), "+f"(d[22]), "+f"(d[23]),
              "+f"(d[24]), "+f"(d[25]), "+f"(d[26]), "+f"(d[27]), "+f"(d[28]), "+f"(d[29]), "+f"(d[30]), "+f"(d[31]),
              "+f"(d[32]), "+f"(d[33]), "+f"(d[34]), "+f"(d[35]), "+f"(d[36]), "+f"(d[37]), "+f"(d[38]), "+f"(d[39]),
              "+f"(d[40]), "+f"(d[41]), "+f"(d[42]), "+f"(d[43]), "+f"(d[44]), "+f"(d[45]), "+f"(d[46]), "+f"(d[47]),
              "+f"(d[48]), "+f"(d[49]), "+f"(d[50]), "+f"(d[51]), "+f"(d[52]), "+f"(d[53]), "+f"(d[54]), "+f"(d[55]),
              "+f"(d[56]), "+f"(d[57]), "+f"(d[58]), "+f"(d[59]), "+f"(d[60]), "+f"(d[61]), "+f"(d[62]), "+f"(d[63])
            : "l"(da), "l"(db), "r"(sd));
    }
};
template <> struct Wgmma<192> {
    static __device__ __forceinline__ void mma(float* d, uint64_t da, uint64_t db, int sd) {
        asm volatile(
            "{\n.reg .pred p;\nsetp.ne.b32 p, %98, 0;\n"
            "wgmma.mma_async.sync.aligned.m64n192k16.f32.bf16.bf16 "
            "{%0,%1,%2,%3,%4,%5,%6,%7,%8,%9,%10,%11,%12,%13,%14,%15,"
            "%16,%17,%18,%19,%20,%21,%22,%23,%24,%25,%26,%27,%28,%29,%30,%31,"
            "%32,%33,%34,%35,%36,%37,%38,%39,%40,%41,%42,%43,%44,%45,%46,%47,"
            "%48,%49,%50,%51,%52,%53,%54,%55,%56,%57,%58,%59,%60,%61,%62,%63,"
            "%64,%65,%66,%67,%68,%69,%70,%71,%72,%73,%74,%75,%76,%77,%78,%79,"
            "%80,%81,%82,%83,%84,%85,%86,%87,%88,%89,%90,%91,%92,%93,%94,%95},"
            "%96,%97,p,1,1,0,1;\n}\n"
            : "+f"(d[0]), "+f"(d[1]), "+f"(d[2]), "+f"(d[3]), "+f"(d[4]), "+f"(d[5]), "+f"(d[6]), "+f"(d[7]),
              "+f"(d[8]), "+f"(d[9]), "+f"(d[10]), "+f"(d[11]), "+f"(d[12]), "+f"(d[13]), "+f"(d[14]), "+f"(d[15]),
              "+f"(d[16]), "+f"(d[17]), "+f"(d[18]), "+f"(d[19]), "+f"(d[20]), "+f"(d[21]), "+f"(d[22]), "+f"(d[23]),
              "+f"(d[24]), "+f"(d[25]), "+f"(d[26]), "+f"(d[27]), "+f"(d[28]), "+f"(d[29]), "+f"(d[30]), "+f"(d[31]),
              "+f"(d[32]), "+f"(d[33]), "+f"(d[34]), "+f"(d[35]), "+f"(d[36]), "+f"(d[37]), "+f"(d[38]), "+f"(d[39]),
              "+f"(d[40]), "+f"(d[41]), "+f"(d[42]), "+f"(d[43]), "+f"(d[44]), "+f"(d[45]), "+f"(d[46]), "+f"(d[47]),
              "+f"(d[48]), "+f"(d[49]), "+f"(d[50]), "+f"(d[51]), "+f"(d[52]), "+f"(d[53]), "+f"(d[54]), "+f"(d[55]),
              "+f"(d[56]), "+f"(d[57]), "+f"(d[58]), "+f"(d[59]), "+f"(d[60]), "+f"(d[61]), "+f"(d[62]), "+f"(d[63]),
              "+f"(d[64]), "+f"(d[65]), "+f"(d[66]), "+f"(d[67]), "+f"(d[68]), "+f"(d[69]), "+f"(d[70]), "+f"(d[71]),
              "+f"(d[72]), "+f"(d[73]), "+f"(d[74]), "+f"(d[75]), "+f"(d[76]), "+f"(d[77]), "+f"(d[78]), "+f"(d[79]),
              "+f"(d[80]), "+f"(d[81]), "+f"(d[82]), "+f"(d[83]), "+f"(d[84]), "+f"(d[85]), "+f"(d[86]), "+f"(d[87]),
              "+f"(d[88]), "+f"(d[89]), "+f"(d[90]), "+f"(d[91]), "+f"(d[92]), "+f"(d[93]), "+f"(d[94]), "+f"(d[95])
            : "l"(da), "l"(db), "r"(sd));
    }
};

template <> struct Wgmma<256> {
    static __device__ __forceinline__ void mma(float* d, uint64_t da, uint64_t db, int sd) {
        asm volatile(
            "{\n.reg .pred p;\nsetp.ne.b32 p, %130, 0;\n"
            "wgmma.mma_async.sync.aligned.m64n256k16.f32.bf16.bf16 "
            "{%0,%1,%2,%3,%4,%5,%6,%7,%8,%9,%10,%11,%12,%13,%14,%15,%16,%17,%18,%19,%20,%21,%22,%23,%24,%25,%26,%27,%28,%29,%30,%31,%32,%33,%34,%35,%36,%37,%38,%39,%40,%41,%42,%43,%44,%45,%46,%47,%48,%49,%50,%51,%52,%53,%54,%55,%56,%57,%58,%59,%60,%61,%62,%63,%64,%65,%66,%67,%68,%69,%70,%71,%72,%73,%74,%75,%76,%77,%78,%79,%80,%81,%82,%83,%84,%85,%86,%87,%88,%89,%90,%91,%92,%93,%94,%95,%96,%97,%98,%99,%100,%101,%102,%103,%104,%105,%106,%107,%108,%109,%110,%111,%112,%113,%114,%115,%116,%117,%118,%119,%120,%121,%122,%123,%124,%125,%126,%127},"
            "%128,%129,p,1,1,0,1;\n}\n"
            : "+f"(d[0]), "+f"(d[1]), "+f"(d[2]), "+f"(d[3]), "+f"(d[4]), "+f"(d[5]), "+f"(d[6]), "+f"(d[7]), "+f"(d[8]), "+f"(d[9]), "+f"(d[10]), "+f"(d[11]), "+f"(d[12]), "+f"(d[13]), "+f"(d[14]), "+f"(d[15]), "+f"(d[16]), "+f"(d[17]), "+f"(d[18]), "+f"(d[19]), "+f"(d[20]), "+f"(d[21]), "+f"(d[22]), "+f"(d[23]), "+f"(d[24]), "+f"(d[25]), "+f"(d[26]), "+f"(d[27]), "+f"(d[28]), "+f"(d[29]), "+f"(d[30]), "+f"(d[31]), "+f"(d[32]), "+f"(d[33]), "+f"(d[34]), "+f"(d[35]), "+f"(d[36]), "+f"(d[37]), "+f"(d[38]), "+f"(d[39]), "+f"(d[40]), "+f"(d[41]), "+f"(d[42]), "+f"(d[43]), "+f"(d[44]), "+f"(d[45]), "+f"(d[46]), "+f"(d[47]), "+f"(d[48]), "+f"(d[49]), "+f"(d[50]), "+f"(d[51]), "+f"(d[52]), "+f"(d[53]), "+f"(d[54]), "+f"(d[55]), "+f"(d[56]), "+f"(d[57]), "+f"(d[58]), "+f"(d[59]), "+f"(d[60]), "+f"(d[61]), "+f"(d[62]), "+f"(d[63]), "+f"(d[64]), "+f"(d[65]), "+f"(d[66]), "+f"(d[67]), "+f"(d[68]), "+f"(d[69]), "+f"(d[70]), "+f"(d[71]), "+f"(d[72]), "+f"(d[73]), "+f"(d[74]), "+f"(d[75]), "+f"(d[76]), "+f"(d[77]), "+f"(d[78]), "+f"(d[79]), "+f"(d[80]), "+f"(d[81]), "+f"(d[82]), "+f"(d[83]), "+f"(d[84]), "+f"(d[85]), "+f"(d[86]), "+f"(d[87]), "+f"(d[88]), "+f"(d[89]), "+f"(d[90]), "+f"(d[91]), "+f"(d[92]), "+f"(d[93]), "+f"(d[94]), "+f"(d[95]), "+f"(d[96]), "+f"(d[97]), "+f"(d[98]), "+f"(d[99]), "+f"(d[100]), "+f"(d[101]), "+f"(d[102]), "+f"(d[103]), "+f"(d[104]), "+f"(d[105]), "+f"(d[106]), "+f"(d[107]), "+f"(d[108]), "+f"(d[109]), "+f"(d[110]), "+f"(d[111]), "+f"(d[112]), "+f"(d[113]), "+f"(d[114]), "+f"(d[115]), "+f"(d[116]), "+f"(d[117]), "+f"(d[118]), "+f"(d[119]), "+f"(d[120]), "+f"(d[121]), "+f"(d[122]), "+f"(d[123]), "+f"(d[124]), "+f"(d[125]), "+f"(d[126]), "+f"(d[127])
            : "l"(da), "l"(db), "r"(sd));
    }
};
template <int W>
__device__ __forceinline__ void ln_row(const bf16* __restrict__ src, bf16* __restrict__ dst, int lane) {
    constexpr int NP = W / 64;
    constexpr int REM = (W / 2) % 32;
    uint32_t v[NP + 1];
    const uint32_t* s32 = reinterpret_cast<const uint32_t*>(src);
    float sum = 0.f;
#pragma unroll
    for (int i = 0; i < NP; i++) { v[i] = s32[i * 32 + lane]; sum += lo_f(v[i]) + hi_f(v[i]); }
    if (REM) { v[NP] = (lane < REM) ? s32[NP * 32 + lane] : 0u; if (lane < REM) sum += lo_f(v[NP]) + hi_f(v[NP]); }
#pragma unroll
    for (int o = 16; o; o >>= 1) sum += __shfl_xor_sync(0xffffffffu, sum, o);
    float mean = sum * (1.0f / W);
    float vs = 0.f;
#pragma unroll
    for (int i = 0; i < NP; i++) { float a = lo_f(v[i]) - mean, b = hi_f(v[i]) - mean; vs += a * a + b * b; }
    if (REM && lane < REM) { float a = lo_f(v[NP]) - mean, b = hi_f(v[NP]) - mean; vs += a * a + b * b; }
#pragma unroll
    for (int o = 16; o; o >>= 1) vs += __shfl_xor_sync(0xffffffffu, vs, o);
    float var = rbf(vs * (1.0f / W));
    float mb = rbf(mean);
    float den = rbf(sqrtf(rbf(var + 1e-5f)));
    uint32_t* d32 = reinterpret_cast<uint32_t*>(dst);
#pragma unroll
    for (int i = 0; i < NP; i++) d32[i * 32 + lane] = pack_bf16(rbf(lo_f(v[i]) - mb) / den, rbf(hi_f(v[i]) - mb) / den);
    if (REM && lane < REM) d32[NP * 32 + lane] = pack_bf16(rbf(lo_f(v[NP]) - mb) / den, rbf(hi_f(v[NP]) - mb) / den);
}

__global__ void ln_kernel(const bf16* __restrict__ x) {
    int row = blockIdx.x * 8 + (threadIdx.x >> 5);
    ln_row<D_>(x + (size_t)row * D_, g_xn + (size_t)row * D_, threadIdx.x & 31);
}
__global__ void ln2_kernel() {
    int row = blockIdx.x * 8 + (threadIdx.x >> 5);
    bf16* p = g_z + (size_t)row * F_ + FH_;
    ln_row<FH_>(p, p, threadIdx.x & 31);
}

enum { EPI_STORE = 0, EPI_GELU = 1, EPI_SP = 2, EPI_SILU = 3, EPI_FINAL = 4 };
struct EpiParams {
    bf16* out; int ldo;
    const bf16* aux0;
    const bf16* aux1;
};

__device__ __forceinline__ float gelu_tanh_f(float x) {
    const float k0 = 0.7978845608028654f, k1 = 0.044715f;
    float inner = k0 * (x + k1 * x * x * x);
    return 0.5f * x * (1.0f + tanhf(inner));
}
__device__ __forceinline__ float silu_f(float x) { return x / (1.0f + expf(-x)); }

template <int BN, int EPI>
__global__ void __launch_bounds__(384, 1)
gemm_kernel(const __grid_constant__ CUtensorMap tmA, const __grid_constant__ CUtensorMap tmB0,
            const __grid_constant__ CUtensorMap tmB1, const __grid_constant__ CUtensorMap tmB2,
            int nPerB, int N, int K, EpiParams ep) {
    constexpr int BM = 128, BK = 64;
    constexpr int A_BYTES = BM * BK * 2;
    constexpr int B_BYTES = (BN / 64) * 8192;
    constexpr int STAGE = A_BYTES + B_BYTES;
    constexpr int NST = (200 * 1024) / STAGE;
    constexpr int OLD = BN + 8;
    extern __shared__ __align__(1024) uint8_t smem_raw[];
    uint8_t* smem = (uint8_t*)(((uintptr_t)smem_raw + 1023) & ~(uintptr_t)1023);
    __shared__ __align__(8) uint64_t full_bar[NST], empty_bar[NST];

    const int tid = threadIdx.x, wg = tid >> 7;
    const int m0 = blockIdx.y * BM, n0 = blockIdx.x * BN;
    const int nk = (K + BK - 1) / BK;

    if (tid == 0) {
        for (int i = 0; i < NST; i++) { mbar_init(smem_u32(&full_bar[i]), 1); mbar_init(smem_u32(&empty_bar[i]), 2); }
        asm volatile("fence.mbarrier_init.release.cluster;" ::: "memory");
    }
    __syncthreads();

    if (wg == 0) {
        if (tid == 0) {
            const int bsel = n0 / nPerB;
            const CUtensorMap* tmB = bsel == 0 ? &tmB0 : (bsel == 1 ? &tmB1 : &tmB2);
            const int nb = n0 - bsel * nPerB;
            for (int kt = 0; kt < nk; kt++) {
                int st = kt % NST; uint32_t ph = (kt / NST) & 1;
                mbar_wait(smem_u32(&empty_bar[st]), ph ^ 1);
                uint32_t fb = smem_u32(&full_bar[st]);
                mbar_expect_tx(fb, STAGE);
                uint32_t sa = smem_u32(smem + st * STAGE);
                tma_load_2d(sa, &tmA, fb, kt * BK, m0);
#pragma unroll
                for (int j = 0; j < BN / 64; j++) tma_load_2d(sa + A_BYTES + j * 8192, tmB, fb, nb + j * 64, kt * BK);
            }
        }
    } else {
        const int cw = wg - 1;
        float acc[BN / 2];
        for (int kt = 0; kt < nk; kt++) {
            int st = kt % NST; uint32_t ph = (kt / NST) & 1;
            mbar_wait(smem_u32(&full_bar[st]), ph);
            uint32_t sa = smem_u32(smem + st * STAGE) + cw * 64 * 128;
            uint32_t sb = smem_u32(smem + st * STAGE) + A_BYTES;
            wgmma_fence();
#pragma unroll
            for (int k = 0; k < BK / 16; k++) {
                uint64_t da = make_desc(sa + k * 32, 16, 1024);
                uint64_t db = make_desc(sb + k * 2048, 8192, 1024);
                Wgmma<BN>::mma(acc, da, db, (kt | k) != 0);
            }
            wgmma_commit();
            wgmma_wait<1>();
            if (kt > 0 && (tid & 127) == 0) mbar_arrive(smem_u32(&empty_bar[(kt - 1) % NST]));
        }
        wgmma_wait<0>();
        asm volatile("bar.sync 1, 256;" ::: "memory");
        const int lane = tid & 31, wi = (tid >> 5) & 3, g = lane >> 2, t = lane & 3;
        bf16* stg = reinterpret_cast<bf16*>(smem) + cw * 64 * OLD;
#pragma unroll
        for (int j = 0; j < BN / 8; j++) {
            *reinterpret_cast<uint32_t*>(&stg[(wi * 16 + g) * OLD + j * 8 + 2 * t]) = pack_bf16(acc[4 * j], acc[4 * j + 1]);
            *reinterpret_cast<uint32_t*>(&stg[(wi * 16 + g + 8) * OLD + j * 8 + 2 * t]) = pack_bf16(acc[4 * j + 2], acc[4 * j + 3]);
        }
        asm volatile("bar.sync %0, 128;" ::"r"(2 + cw) : "memory");
        constexpr int CPR = BN / 8;
        const int ltid = tid & 127;
#pragma unroll 4
        for (int i = ltid; i < 64 * CPR; i += 128) {
            int r = i / CPR, ch = i % CPR;
            int row = m0 + cw * 64 + r, col = n0 + ch * 8;
            if (col >= N) continue;
            uint4 v = *reinterpret_cast<const uint4*>(&stg[r * OLD + ch * 8]);
            uint32_t u[4] = {v.x, v.y, v.z, v.w}, o[4];
            if (EPI == EPI_STORE) {
#pragma unroll
                for (int q = 0; q < 4; q++) o[q] = u[q];
            } else if (EPI == EPI_GELU) {
#pragma unroll
                for (int q = 0; q < 4; q++) o[q] = pack_bf16(gelu_tanh_f(lo_f(u[q])), gelu_tanh_f(hi_f(u[q])));
            } else if (EPI == EPI_SP) {
                float bb = bf2f(ep.aux1[row]);
                uint4 z = *reinterpret_cast<const uint4*>(ep.aux0 + (size_t)row * F_ + col);
                uint32_t zz[4] = {z.x, z.y, z.z, z.w};
#pragma unroll
                for (int q = 0; q < 4; q++) o[q] = pack_bf16(lo_f(zz[q]) * rbf(lo_f(u[q]) + bb), hi_f(zz[q]) * rbf(hi_f(u[q]) + bb));
            } else if (EPI == EPI_SILU) {
#pragma unroll
                for (int q = 0; q < 4; q++) o[q] = pack_bf16(silu_f(lo_f(u[q])), silu_f(hi_f(u[q])));
            } else {
                uint4 xv = *reinterpret_cast<const uint4*>(ep.aux0 + (size_t)row * D_ + col);
                uint4 gv = *reinterpret_cast<const uint4*>(ep.aux1 + (size_t)row * D_ + col);
                uint32_t xx[4] = {xv.x, xv.y, xv.z, xv.w}, gg[4] = {gv.x, gv.y, gv.z, gv.w};
#pragma unroll
                for (int q = 0; q < 4; q++)
                    o[q] = pack_bf16(lo_f(xx[q]) + rbf(lo_f(u[q]) * lo_f(gg[q])), hi_f(xx[q]) + rbf(hi_f(u[q]) * hi_f(gg[q])));
            }
            *reinterpret_cast<uint4*>(ep.out + (size_t)row * ep.ldo + col) = make_uint4(o[0], o[1], o[2], o[3]);
        }
    }
}

__device__ __forceinline__ void mma16816(float* c, const uint32_t* a, uint32_t b0, uint32_t b1) {
    asm volatile(
        "mma.sync.aligned.m16n8k16.row.col.f32.bf16.bf16.f32 {%0,%1,%2,%3}, {%4,%5,%6,%7}, {%8,%9}, {%0,%1,%2,%3};"
        : "+f"(c[0]), "+f"(c[1]), "+f"(c[2]), "+f"(c[3])
        : "r"(a[0]), "r"(a[1]), "r"(a[2]), "r"(a[3]), "r"(b0), "r"(b1));
}
__device__ __forceinline__ void ldsm_x4(uint32_t* r, uint32_t addr) {
    asm volatile("ldmatrix.sync.aligned.m8n8.x4.shared.b16 {%0,%1,%2,%3}, [%4];"
                 : "=r"(r[0]), "=r"(r[1]), "=r"(r[2]), "=r"(r[3]) : "r"(addr));
}
__device__ __forceinline__ void ldsm_x4_t(uint32_t* r, uint32_t addr) {
    asm volatile("ldmatrix.sync.aligned.m8n8.x4.trans.shared.b16 {%0,%1,%2,%3}, [%4];"
                 : "=r"(r[0]), "=r"(r[1]), "=r"(r[2]), "=r"(r[3]) : "r"(addr));
}
__device__ __forceinline__ uint4 ld_relaxed_v4(const void* p) {
    uint4 v;
    asm volatile("ld.relaxed.gpu.global.v4.u32 {%0,%1,%2,%3}, [%4];" : "=r"(v.x), "=r"(v.y), "=r"(v.z), "=r"(v.w) : "l"(p) : "memory");
    return v;
}
__device__ __forceinline__ void st_relaxed_v4(void* p, uint32_t a, uint32_t b, uint32_t c, uint32_t d) {
    asm volatile("st.relaxed.gpu.global.v4.u32 [%0], {%1,%2,%3,%4};" ::"l"(p), "r"(a), "r"(b), "r"(c), "r"(d) : "memory");
}
__device__ __forceinline__ void st_relaxed_v2(void* p, uint32_t a, uint32_t b) {
    asm volatile("st.relaxed.gpu.global.v2.u32 [%0], {%1,%2};" ::"l"(p), "r"(a), "r"(b) : "memory");
}
__device__ __forceinline__ void cp_async16(uint32_t dst, const void* src) {
    asm volatile("cp.async.cg.shared.global [%0], [%1], 16;" ::"r"(dst), "l"(src) : "memory");
}
__device__ __forceinline__ void cp_async_commit() { asm volatile("cp.async.commit_group;" ::: "memory"); }
template <int N> __device__ __forceinline__ void cp_async_wait() { asm volatile("cp.async.wait_group %0;" ::"n"(N) : "memory"); }

#define PROF(i) do {} while (0)
constexpr int SPIN_LIMIT = 4000000;

__device__ __forceinline__ uint4 poll_ll(const void* p, uint32_t flag) {
    uint4 v = ld_relaxed_v4(p);
    int n = 0;
    while ((v.y != flag || v.w != flag) && ++n < SPIN_LIMIT) {
        v = ld_relaxed_v4(p);
    }
    return v;
}

constexpr int RT = 512;
constexpr int MEMS_LD = D_ + 8;
constexpr int HL = DH_ + 8;
struct RecurSmem {
    bf16 mem[MEM_][MEMS_LD];
    bf16 kall[2][48][HL];
    bf16 vall[2][48][HL];
    bf16 qm[16][HL];
    float sc[MEM_][40];
    bf16 p[MEM_][48 + 8];
    bf16 om[MEM_][HL];
    float red[12][16 * 8];
    float wred[2][5][16 * 8];
    bf16 xs[SEG_][MEMS_LD];
    float redx[6][4][16 * 8];
    bf16 xo[SEG_][96 + 8];
};

__device__ __forceinline__ void bar_sync(int id, int n) { asm volatile("bar.sync %0, %1;" ::"r"(id), "r"(n) : "memory"); }
__device__ __forceinline__ void bar_arrive(int id, int n) { asm volatile("bar.arrive %0, %1;" ::"r"(id), "r"(n) : "memory"); }
__device__ __forceinline__ void sts64(uint32_t a, uint32_t x, uint32_t y) { asm volatile("st.shared.v2.u32 [%0], {%1,%2};" ::"r"(a), "r"(x), "r"(y) : "memory"); }
__device__ __forceinline__ uint32_t ldg_u16x2(const bf16* p0, const bf16* p1) {
    return (uint32_t)*(const uint16_t*)p0 | ((uint32_t)*(const uint16_t*)p1 << 16);
}
enum { BAR_MEM = 1, BAR_RED = 2, BAR_CTL = 3, BAR_WO = 4, BAR_INIT = 6, BAR_X = 7, BAR_GO = 8 };

__global__ void __launch_bounds__(RT, 1)
recur_kernel(const bf16* __restrict__ mem0, const bf16* __restrict__ Wq, const bf16* __restrict__ Wk,
             const bf16* __restrict__ Wv, const bf16* __restrict__ Wo) {
    extern __shared__ __align__(16) uint8_t smem_raw[];
    RecurSmem& sm = *reinterpret_cast<RecurSmem*>(smem_raw);
    const int tid = threadIdx.x, lane = tid & 31, w = tid >> 5;
    const int g = lane >> 2, t = lane & 3;
    const int h = blockIdx.x >> 2, c = blockIdx.x & 3;

    if (w < 12) {
        asm volatile("setmaxnreg.dec.sync.aligned.u32 112;");
        uint32_t wf[20][4];
        const int mt = w % 6, kh = w / 6;
        {
            const bf16* W = (mt < 2) ? Wq : (mt < 4 ? Wk : Wv);
            int f0 = h * DH_ + c * 32 + (mt & 1) * 16;
            uint32_t stg = smem_u32(smem_raw) + w * 10240;
#pragma unroll 4
            for (int i = lane; i < 640; i += 32)
                cp_async16(stg + i * 16, W + (size_t)(kh * 320 + (i >> 1)) * HD_ + f0 + (i & 1) * 8);
            cp_async_commit(); cp_async_wait<0>(); __syncwarp();
            uint32_t la = stg + ((lane & 7) + ((lane >> 4) & 1) * 8) * 32 + ((lane >> 3) & 1) * 16;
#pragma unroll
            for (int i = 0; i < 20; i++) ldsm_x4_t(wf[i], la + i * 512);
        }
        bar_sync(BAR_INIT, RT);
        const uint32_t base = smem_u32(&sm.mem[lane & 7][kh * 320 + (lane >> 3) * 8]);
        const uint32_t rp = smem_u32(&sm.red[w][g * 8 + 2 * t]);
        const uint32_t xbase = smem_u32(&sm.xs[lane & 7][kh * 320 + (lane >> 3) * 8]);
        const uint32_t rxp = smem_u32(&sm.redx[mt][0][lane * 4]);
        auto load_x = [&](int seg) {
            for (int i = tid; i < SEG_ * (D_ / 8); i += 384) {
                int r = i / (D_ / 8), ch = i % (D_ / 8);
                cp_async16(smem_u32(&sm.xs[r][ch * 8]), g_xn + (size_t)(seg * SEG_ + r) * D_ + ch * 8);
            }
            cp_async_commit();
        };
        auto xwork = [&](int seg) {
            cp_async_wait<0>();
            bar_sync(BAR_X, 384);
            float acc[4][4];
#pragma unroll
            for (int nt = 0; nt < 4; nt++) {
                float a0[4] = {0.f, 0.f, 0.f, 0.f}, a1[4] = {0.f, 0.f, 0.f, 0.f};
#pragma unroll
                for (int i = 0; i < 10; i++) {
                    uint32_t b[4];
                    ldsm_x4(b, xbase + nt * (8 * MEMS_LD * 2) + i * 64);
                    mma16816(a0, wf[2 * i], b[0], b[1]);
                    mma16816(a1, wf[2 * i + 1], b[2], b[3]);
                }
#pragma unroll
                for (int e = 0; e < 4; e++) acc[nt][e] = a0[e] + a1[e];
            }
            if (kh == 1) {
#pragma unroll
                for (int nt = 0; nt < 4; nt++)
                    asm volatile("st.shared.v4.f32 [%0], {%1,%2,%3,%4};" ::"r"(rxp + nt * 512), "f"(acc[nt][0]), "f"(acc[nt][1]), "f"(acc[nt][2]), "f"(acc[nt][3]) : "memory");
            }
            bar_sync(BAR_X, 384);
            if (seg + 1 < NSEG_) load_x(seg + 1);
            if (kh == 0) {
#pragma unroll
                for (int nt = 0; nt < 4; nt++) {
                    float4 o;
                    asm volatile("ld.shared.v4.f32 {%0,%1,%2,%3}, [%4];" : "=f"(o.x), "=f"(o.y), "=f"(o.z), "=f"(o.w) : "r"(rxp + nt * 512) : "memory");
                    bf16* d = &sm.xo[nt * 8 + 2 * t][mt * 16 + g];
                    d[0] = __float2bfloat16_rn(acc[nt][0] + o.x);
                    d[104] = __float2bfloat16_rn(acc[nt][1] + o.y);
                    d[8] = __float2bfloat16_rn(acc[nt][2] + o.z);
                    d[104 + 8] = __float2bfloat16_rn(acc[nt][3] + o.w);
                }
            }
            bar_sync(BAR_X, 384);
            {
                int r = tid / 12, ch = tid % 12;
                uint4 v = *reinterpret_cast<const uint4*>(&sm.xo[r][ch * 8]);
                *reinterpret_cast<uint4*>(g_qkv + (size_t)(seg * SEG_ + r) * (3 * HD_) + (ch >> 2) * HD_ + h * DH_ + c * 32 + (ch & 3) * 8) = v;
                __threadfence();
                __syncwarp();
                if (lane == 0) atomicAdd(&g_xcnt[h * NSEG_ + seg], 1u);
            }
        };
        load_x(0);
        xwork(0);
        xwork(1);
        for (int s = 0; s < NSEG_; s++) {
            bar_sync(BAR_MEM, RT);
            float a0[4] = {0.f, 0.f, 0.f, 0.f}, a1[4] = {0.f, 0.f, 0.f, 0.f};
#pragma unroll
            for (int i = 0; i < 10; i++) {
                uint32_t b[4];
                ldsm_x4(b, base + i * 64);
                mma16816(a0, wf[2 * i], b[0], b[1]);
                mma16816(a1, wf[2 * i + 1], b[2], b[3]);
            }
            sts64(rp, __float_as_uint(a0[0] + a1[0]), __float_as_uint(a0[1] + a1[1]));
            sts64(rp + 256, __float_as_uint(a0[2] + a1[2]), __float_as_uint(a0[3] + a1[3]));
            bar_arrive(BAR_RED, RT);
            if (s + 1 < NSEG_) bar_sync(BAR_GO, RT);
            if (s + 2 < NSEG_) xwork(s + 2);
        }
    } else {
        asm volatile("setmaxnreg.inc.sync.aligned.u32 176;");
        const int ct = tid - 384, cw = w - 12;
        const int mg = cw >> 1, kh = cw & 1;
        uint32_t wf[20][4];
        {
            uint32_t stg = smem_u32(smem_raw) + 12 * 10240 + cw * 10240;
#pragma unroll 4
            for (int i = lane; i < 640; i += 32) {
                int r = i / 10, ch = i % 10;
                cp_async16(stg + r * 160 + ch * 16, Wo + (size_t)(h * DH_ + kh * 64 + r) * D_ + c * 160 + mg * 80 + ch * 8);
            }
            cp_async_commit(); cp_async_wait<0>(); __syncwarp();
            uint32_t la = stg + ((lane & 7) + ((lane >> 4) & 1) * 8) * 160 + ((lane >> 3) & 1) * 16;
#pragma unroll
            for (int mi = 0; mi < 5; mi++)
#pragma unroll
                for (int ki = 0; ki < 4; ki++) ldsm_x4_t(wf[mi * 4 + ki], la + ki * 16 * 160 + mi * 32);
        }
        bar_sync(BAR_INIT, RT);
        for (int i = ct; i < 2 * 8 * HL; i += 128) {
            int b = i / (8 * HL), r = (i / HL) % 8, cc = i % HL;
            sm.kall[b][40 + r][cc] = __float2bfloat16(0.f);
            sm.vall[b][40 + r][cc] = __float2bfloat16(0.f);
        }
        for (int i = ct; i < 8 * HL; i += 128) sm.qm[8 + i / HL][i % HL] = __float2bfloat16(0.f);
        for (int i = ct; i < 8 * 56; i += 128) sm.p[i / 56][i % 56] = __float2bfloat16(0.f);
        bar_sync(BAR_CTL, 128);
        constexpr uint32_t KV_BUF = 48 * HL * 2;
        const bf16* kv_src = g_qkv + (size_t)(ct >> 4) * (3 * HD_) + HD_ + h * DH_ + (ct & 15) * 8;
        const uint32_t kv_dst0 = smem_u32(&sm.kall[0][MEM_ + (ct >> 4)][(ct & 15) * 8]);
        const uint32_t kv_dst1 = smem_u32(&sm.vall[0][MEM_ + (ct >> 4)][(ct & 15) * 8]);
        auto prefetch_kv = [&](int s, int buf) {
            if (ct == 0) {
                const unsigned* cp = g_xcnt + h * NSEG_ + s;
                unsigned v; int n = 0;
                do { asm volatile("ld.acquire.gpu.global.u32 %0, [%1];" : "=r"(v) : "l"(cp) : "memory"); } while (v < 48u && ++n < SPIN_LIMIT);
            }
            bar_sync(BAR_CTL, 128);
            const bf16* src = kv_src + (size_t)s * SEG_ * (3 * HD_);
#pragma unroll
            for (int j = 0; j < 4; j++) {
                cp_async16(kv_dst0 + buf * KV_BUF + j * (8 * HL * 2), src + (size_t)j * 8 * (3 * HD_));
                cp_async16(kv_dst1 + buf * KV_BUF + j * (8 * HL * 2), src + (size_t)j * 8 * (3 * HD_) + HD_);
            }
            cp_async_commit();
        };
        const float4* acc_src = reinterpret_cast<const float4*>(g_acc) + ct;
        const uint32_t acc_dst = smem_u32(&sm.mem[(ct & 1) * 4][ct >> 1]);
        const uint4* hx_base = reinterpret_cast<const uint4*>(g_hx) + h * 1024;
        const int hx_rq = ct & 63, hx_half = ct >> 6;
        const uint4* hx_src = hx_base + hx_half * 64 + hx_rq;
        const uint32_t hx_col = (hx_rq & 7) * 8, hx_r = hx_rq >> 3;
        const uint32_t hx_dstA = (hx_half == 0 ? smem_u32(&sm.qm[hx_r][0]) : smem_u32(&sm.kall[0][hx_r][0])) + hx_col;
        const uint32_t hx_dstB = smem_u32(&sm.vall[0][hx_r][0]) + hx_col;
        const uint4* hx_probe = hx_base + (lane >> 3) * 256 + ((lane & 7) % 3) * 64 + (lane & 7) * 8 + 3;
        const int pb_r = ct >> 4, pb_pr = ct & 15;
        uint2* pb_dst = g_hx + (h * 1024 + c * 256 + pb_r * 8) * 2 + pb_pr;
        const float* pb_src = &sm.red[pb_pr >> 3][(pb_pr & 7) * 16 + pb_r];
        bf16* pb_k = g_kmem + (size_t)pb_r * HD_ + h * DH_ + c * 32 + pb_pr * 2;
        bf16* pb_v = g_vmem + (size_t)pb_r * HD_ + h * DH_ + c * 32 + pb_pr * 2;
        const uint32_t qa = smem_u32(&sm.qm[lane & 15][(lane >> 4) * 8]);
        const uint32_t kb0 = smem_u32(&sm.kall[0][cw * 8 + (lane & 7)][(lane >> 3) * 8]);
        const uint32_t va0 = smem_u32(&sm.vall[0][(lane & 7) + ((lane >> 4) & 1) * 8][cw * 32 + ((lane >> 3) & 1) * 8]);
        const uint32_t pbaddr = smem_u32(&sm.p[lane & 7][((lane >> 3) & 1) * 8]);
        const uint32_t ob = smem_u32(&sm.om[lane & 7][kh * 64 + (lane >> 3) * 8]);
        float* acc_dst_g = g_acc + (c * 160 + mg * 80 + g) * 8 + 2 * t;

        prefetch_kv(0, 0);
        for (int s = 0; s < NSEG_; s++) {
            const int buf = s & 1;
            const uint32_t flag = s + 1;
            const uint32_t bo = buf * KV_BUF;
            PROF(0);
            if (s == 0) {
                for (int i = ct; i < MEM_ * D_ / 8; i += 128) {
                    int r = i / (D_ / 8), cc = (i % (D_ / 8)) * 8;
                    *reinterpret_cast<uint4*>(&sm.mem[r][cc]) = *reinterpret_cast<const uint4*>(mem0 + r * D_ + cc);
                }
            } else {
                if (ct == 0) {
                    const unsigned* cp = g_cnt + (s - 1) * 32;
                    unsigned v; int n = 0;
                    do { asm volatile("ld.acquire.gpu.global.u32 %0, [%1];" : "=r"(v) : "l"(cp) : "memory"); } while (v < 256u && ++n < SPIN_LIMIT);
                }
                bar_sync(BAR_CTL, 128);
                PROF(1);
                const float4* src = acc_src + (size_t)(s - 1) * (MEM_ * D_ / 4);
                float4 v[10];
#pragma unroll
                for (int j = 0; j < 10; j++)
                    asm volatile("ld.relaxed.gpu.global.v4.f32 {%0,%1,%2,%3}, [%4];" : "=f"(v[j].x), "=f"(v[j].y), "=f"(v[j].z), "=f"(v[j].w) : "l"(src + 128 * j) : "memory");
#pragma unroll
                for (int j = 0; j < 10; j++) {
                    uint32_t lo = pack_bf16(v[j].x, v[j].y), hi = pack_bf16(v[j].z, v[j].w);
                    uint32_t d = acc_dst + j * 128;
                    asm volatile("st.shared.u16 [%0], %1;" ::"r"(d), "h"((uint16_t)(lo & 0xffff)) : "memory");
                    asm volatile("st.shared.u16 [%0], %1;" ::"r"(d + MEMS_LD * 2), "h"((uint16_t)(lo >> 16)) : "memory");
                    asm volatile("st.shared.u16 [%0], %1;" ::"r"(d + MEMS_LD * 4), "h"((uint16_t)(hi & 0xffff)) : "memory");
                    asm volatile("st.shared.u16 [%0], %1;" ::"r"(d + MEMS_LD * 6), "h"((uint16_t)(hi >> 16)) : "memory");
                }
            }
            bar_arrive(BAR_MEM, RT);
            PROF(2);
            bar_sync(BAR_RED, RT);
            PROF(3);
            {
                uint32_t pk0 = pack_bf16(pb_src[0] + pb_src[768], pb_src[8] + pb_src[768 + 8]);
                uint32_t pk1 = pack_bf16(pb_src[256] + pb_src[1024], pb_src[256 + 8] + pb_src[1024 + 8]);
                uint32_t pk2 = pack_bf16(pb_src[512] + pb_src[1280], pb_src[512 + 8] + pb_src[1280 + 8]);
                st_relaxed_v2(pb_dst, pk0, flag);
                st_relaxed_v2(pb_dst + 128, pk1, flag);
                st_relaxed_v2(pb_dst + 256, pk2, flag);
                *reinterpret_cast<uint32_t*>(pb_k + (size_t)s * (MEM_ * HD_)) = pk1;
                *reinterpret_cast<uint32_t*>(pb_v + (size_t)s * (MEM_ * HD_)) = pk2;
            }
            if (s == NSEG_ - 1) break;
            PROF(4);
            if (cw == 0) (void)poll_ll(hx_probe, flag);
            bar_sync(BAR_CTL, 128);
            PROF(5);
            {
                uint4 v[8];
#pragma unroll
                for (int j = 0; j < 4; j++) v[j] = ld_relaxed_v4(hx_src + j * 256);
                if (hx_half == 0) {
#pragma unroll
                    for (int j = 0; j < 4; j++) v[4 + j] = ld_relaxed_v4(hx_src + j * 256 + 128);
                }
#pragma unroll
                for (int j = 0; j < 4; j++) {
                    if (v[j].y != flag || v[j].w != flag) v[j] = poll_ll(hx_src + j * 256, flag);
                    sts64(hx_dstA + j * 64 + (hx_half ? bo : 0), v[j].x, v[j].z);
                }
                if (hx_half == 0) {
#pragma unroll
                    for (int j = 0; j < 4; j++) {
                        if (v[4 + j].y != flag || v[4 + j].w != flag) v[4 + j] = poll_ll(hx_src + j * 256 + 128, flag);
                        sts64(hx_dstB + j * 64 + bo, v[4 + j].x, v[4 + j].z);
                    }
                }
            }
            cp_async_wait<0>();
            bar_sync(BAR_CTL, 128);
            PROF(6);
            {
                uint32_t a[8][4], b[4][4], b2[4][4];
#pragma unroll
                for (int kk = 0; kk < 4; kk++) ldsm_x4(b[kk], kb0 + bo + kk * 64);
                if (cw == 0) {
#pragma unroll
                    for (int kk = 0; kk < 4; kk++) ldsm_x4(b2[kk], kb0 + bo + 32 * HL * 2 + kk * 64);
                }
#pragma unroll
                for (int kk = 0; kk < 8; kk++) ldsm_x4(a[kk], qa + kk * 32);
                float s0[4] = {0.f, 0.f, 0.f, 0.f}, s1[4] = {0.f, 0.f, 0.f, 0.f};
#pragma unroll
                for (int kk = 0; kk < 4; kk++) { mma16816(s0, a[2 * kk], b[kk][0], b[kk][1]); mma16816(s1, a[2 * kk + 1], b[kk][2], b[kk][3]); }
                const float scale = 0.08838834764831845f;
                *reinterpret_cast<float2*>(&sm.sc[g][cw * 8 + 2 * t]) =
                    make_float2(rbf(rbf(s0[0] + s1[0]) * scale), rbf(rbf(s0[1] + s1[1]) * scale));
                if (cw == 0) {
                    float u0[4] = {0.f, 0.f, 0.f, 0.f}, u1[4] = {0.f, 0.f, 0.f, 0.f};
#pragma unroll
                    for (int kk = 0; kk < 4; kk++) { mma16816(u0, a[2 * kk], b2[kk][0], b2[kk][1]); mma16816(u1, a[2 * kk + 1], b2[kk][2], b2[kk][3]); }
                    *reinterpret_cast<float2*>(&sm.sc[g][32 + 2 * t]) =
                        make_float2(rbf(rbf(u0[0] + u1[0]) * scale), rbf(rbf(u0[1] + u1[1]) * scale));
                }
            }
            bar_sync(BAR_CTL, 128);
            {
                float v0 = sm.sc[cw][lane], v1 = (lane < 8) ? sm.sc[cw][32 + lane] : -INFINITY;
                float y0 = sm.sc[cw + 4][lane], y1 = (lane < 8) ? sm.sc[cw + 4][32 + lane] : -INFINITY;
                float mx = fmaxf(v0, v1), my = fmaxf(y0, y1);
#pragma unroll
                for (int o = 16; o; o >>= 1) { mx = fmaxf(mx, __shfl_xor_sync(0xffffffffu, mx, o)); my = fmaxf(my, __shfl_xor_sync(0xffffffffu, my, o)); }
                float e0 = __expf(v0 - mx), e1 = (lane < 8) ? __expf(v1 - mx) : 0.f;
                float f0 = __expf(y0 - my), f1 = (lane < 8) ? __expf(y1 - my) : 0.f;
                float sx = e0 + e1, sy = f0 + f1;
#pragma unroll
                for (int o = 16; o; o >>= 1) { sx += __shfl_xor_sync(0xffffffffu, sx, o); sy += __shfl_xor_sync(0xffffffffu, sy, o); }
                float ix = 1.0f / sx, iy = 1.0f / sy;
                sm.p[cw][lane] = __float2bfloat16_rn(e0 * ix);
                sm.p[cw + 4][lane] = __float2bfloat16_rn(f0 * iy);
                if (lane < 8) { sm.p[cw][32 + lane] = __float2bfloat16_rn(e1 * ix); sm.p[cw + 4][32 + lane] = __float2bfloat16_rn(f1 * iy); }
            }
            bar_sync(BAR_CTL, 128);
            PROF(7);
            {
                uint32_t a[2][3][4], b[3][2];
#pragma unroll
                for (int kt = 0; kt < 3; kt++) {
                    asm volatile("ldmatrix.sync.aligned.m8n8.x2.shared.b16 {%0,%1}, [%2];" : "=r"(b[kt][0]), "=r"(b[kt][1]) : "r"(pbaddr + kt * 32));
                    ldsm_x4_t(a[0][kt], va0 + bo + kt * 16 * HL * 2);
                    ldsm_x4_t(a[1][kt], va0 + bo + kt * 16 * HL * 2 + 32);
                }
#pragma unroll
                for (int m = 0; m < 2; m++) {
                    float o[4] = {0.f, 0.f, 0.f, 0.f};
#pragma unroll
                    for (int kt = 0; kt < 3; kt++) mma16816(o, a[m][kt], b[kt][0], b[kt][1]);
                    int d0 = cw * 32 + m * 16 + g;
                    sm.om[2 * t][d0] = __float2bfloat16_rn(o[0]);
                    sm.om[2 * t + 1][d0] = __float2bfloat16_rn(o[1]);
                    sm.om[2 * t][d0 + 8] = __float2bfloat16_rn(o[2]);
                    sm.om[2 * t + 1][d0 + 8] = __float2bfloat16_rn(o[3]);
                }
            }
            bar_sync(BAR_CTL, 128);
            PROF(8);
            {
                float acc[5][4];
#pragma unroll
                for (int mi = 0; mi < 5; mi++) { acc[mi][0] = acc[mi][1] = acc[mi][2] = acc[mi][3] = 0.f; }
                uint32_t b[2][4];
                ldsm_x4(b[0], ob); ldsm_x4(b[1], ob + 64);
#pragma unroll
                for (int ki = 0; ki < 4; ki++)
#pragma unroll
                    for (int mi = 0; mi < 5; mi++) mma16816(acc[mi], wf[mi * 4 + ki], b[ki >> 1][(ki & 1) * 2], b[ki >> 1][(ki & 1) * 2 + 1]);
                if (kh == 1) {
#pragma unroll
                    for (int mi = 0; mi < 5; mi++)
                        *reinterpret_cast<float4*>(&sm.wred[mg][mi][lane * 4]) = make_float4(acc[mi][0], acc[mi][1], acc[mi][2], acc[mi][3]);
                }
                bar_sync(BAR_WO + mg, 64);
                if (kh == 0) {
                    float* dst = acc_dst_g + (size_t)s * (MEM_ * D_);
#pragma unroll
                    for (int mi = 0; mi < 5; mi++) {
                        float4 o2 = *reinterpret_cast<float4*>(&sm.wred[mg][mi][lane * 4]);
                        asm volatile("red.global.add.v2.f32 [%0], {%1,%2};" ::"l"(dst + mi * 128), "f"(acc[mi][0] + o2.x), "f"(acc[mi][1] + o2.y) : "memory");
                        asm volatile("red.global.add.v2.f32 [%0], {%1,%2};" ::"l"(dst + mi * 128 + 64), "f"(acc[mi][2] + o2.z), "f"(acc[mi][3] + o2.w) : "memory");
                    }
                    __threadfence();
                    __syncwarp();
                    if (lane == 0) atomicAdd(&g_cnt[s * 32], 1u);
                }
            }
            bar_arrive(BAR_GO, RT);
            PROF(9);
            prefetch_kv(s + 1, buf ^ 1);
            PROF(10);
        }
    }
}

__global__ void __launch_bounds__(128)
attn_x_kernel() {
    __shared__ __align__(16) bf16 sq[32][HL], sk[48][HL], sv[48][HL];
    const int s = blockIdx.x >> 5, h = blockIdx.x & 31;
    const int tid = threadIdx.x, lane = tid & 31, w = tid >> 5, g = lane >> 2, t = lane & 3;
    for (int i = tid; i < (32 + 40 + 40) * 16; i += 128) {
        int r = i >> 4, ch = i & 15;
        const bf16* src; bf16* dst;
        if (r < 32) { src = g_qkv + (size_t)(s * SEG_ + r) * (3 * HD_) + h * DH_; dst = sq[r]; }
        else if (r < 72) { int rr = r - 32; dst = sk[rr];
            src = rr < 8 ? g_kmem + ((size_t)s * MEM_ + rr) * HD_ + h * DH_ : g_qkv + (size_t)(s * SEG_ + rr - 8) * (3 * HD_) + HD_ + h * DH_; }
        else { int rr = r - 72; dst = sv[rr];
            src = rr < 8 ? g_vmem + ((size_t)s * MEM_ + rr) * HD_ + h * DH_ : g_qkv + (size_t)(s * SEG_ + rr - 8) * (3 * HD_) + 2 * HD_ + h * DH_; }
        cp_async16(smem_u32(dst + ch * 8), src + ch * 8);
    }
    cp_async_commit();
    for (int i = tid; i < 8 * 16; i += 128) *reinterpret_cast<uint4*>(&sv[40 + (i >> 4)][(i & 15) * 8]) = make_uint4(0, 0, 0, 0);
    cp_async_wait<0>();
    __syncthreads();
    const int rh = w & 1, dhh = w >> 1;
    float sc[5][4];
#pragma unroll
    for (int n = 0; n < 5; n++) sc[n][0] = sc[n][1] = sc[n][2] = sc[n][3] = 0.f;
#pragma unroll
    for (int kk = 0; kk < 8; kk++) {
        uint32_t a[4];
        ldsm_x4(a, smem_u32(&sq[rh * 16 + (lane & 15)][kk * 16 + (lane >> 4) * 8]));
#pragma unroll
        for (int n = 0; n < 5; n++) {
            uint32_t b[2];
            asm volatile("ldmatrix.sync.aligned.m8n8.x2.shared.b16 {%0,%1}, [%2];" : "=r"(b[0]), "=r"(b[1])
                         : "r"(smem_u32(&sk[n * 8 + (lane & 7)][kk * 16 + ((lane >> 3) & 1) * 8])));
            mma16816(sc[n], a, b[0], b[1]);
        }
    }
    const float scale = 0.08838834764831845f;
    float mx[2] = {-INFINITY, -INFINITY};
#pragma unroll
    for (int n = 0; n < 5; n++)
#pragma unroll
        for (int e = 0; e < 4; e++) {
            int row = rh * 16 + g + (e >> 1) * 8, key = n * 8 + 2 * t + (e & 1);
            float v = rbf(rbf(sc[n][e]) * scale);
            if (key > row + MEM_) v = -INFINITY;
            sc[n][e] = v;
            mx[e >> 1] = fmaxf(mx[e >> 1], v);
        }
#pragma unroll
    for (int o = 1; o < 4; o <<= 1) { mx[0] = fmaxf(mx[0], __shfl_xor_sync(0xffffffffu, mx[0], o)); mx[1] = fmaxf(mx[1], __shfl_xor_sync(0xffffffffu, mx[1], o)); }
    float sum[2] = {0.f, 0.f};
#pragma unroll
    for (int n = 0; n < 5; n++)
#pragma unroll
        for (int e = 0; e < 4; e++) { float ev = __expf(sc[n][e] - mx[e >> 1]); sc[n][e] = ev; sum[e >> 1] += ev; }
#pragma unroll
    for (int o = 1; o < 4; o <<= 1) { sum[0] += __shfl_xor_sync(0xffffffffu, sum[0], o); sum[1] += __shfl_xor_sync(0xffffffffu, sum[1], o); }
    float inv[2] = {1.0f / sum[0], 1.0f / sum[1]};
    uint32_t pa[3][4];
#pragma unroll
    for (int kt = 0; kt < 3; kt++) {
        pa[kt][0] = pack_bf16(sc[2 * kt][0] * inv[0], sc[2 * kt][1] * inv[0]);
        pa[kt][1] = pack_bf16(sc[2 * kt][2] * inv[1], sc[2 * kt][3] * inv[1]);
        if (kt < 2) {
            pa[kt][2] = pack_bf16(sc[2 * kt + 1][0] * inv[0], sc[2 * kt + 1][1] * inv[0]);
            pa[kt][3] = pack_bf16(sc[2 * kt + 1][2] * inv[1], sc[2 * kt + 1][3] * inv[1]);
        } else { pa[kt][2] = 0u; pa[kt][3] = 0u; }
    }
#pragma unroll
    for (int n = 0; n < 8; n++) {
        float o[4] = {0.f, 0.f, 0.f, 0.f};
#pragma unroll
        for (int kt = 0; kt < 3; kt++) {
            uint32_t b[2];
            asm volatile("ldmatrix.sync.aligned.m8n8.x2.trans.shared.b16 {%0,%1}, [%2];" : "=r"(b[0]), "=r"(b[1])
                         : "r"(smem_u32(&sv[kt * 16 + (lane & 15)][dhh * 64 + n * 8])));
            mma16816(o, pa[kt], b[0], b[1]);
        }
        int row = s * SEG_ + rh * 16 + g;
        bf16* dst = g_o + (size_t)row * HD_ + h * DH_ + dhh * 64 + n * 8 + 2 * t;
        *reinterpret_cast<uint32_t*>(dst) = pack_bf16(o[0], o[1]);
        *reinterpret_cast<uint32_t*>(dst + 8 * HD_) = pack_bf16(o[2], o[3]);
    }
}

typedef CUresult (*PFN_encodeTiled)(CUtensorMap*, CUtensorMapDataType, cuuint32_t, void*, const cuuint64_t*,
                                    const cuuint64_t*, const cuuint32_t*, const cuuint32_t*, CUtensorMapInterleave,
                                    CUtensorMapSwizzle, CUtensorMapL2promotion, CUtensorMapFloatOOBfill);
static PFN_encodeTiled p_encode = nullptr;

static CUtensorMap make_map(const void* ptr, uint64_t rows, uint64_t cols, uint64_t ld, uint32_t box_rows) {
    CUtensorMap m;
    cuuint64_t dims[2] = {cols, rows};
    cuuint64_t strides[1] = {ld * 2};
    cuuint32_t box[2] = {64, box_rows};
    cuuint32_t es[2] = {1, 1};
    p_encode(&m, CU_TENSOR_MAP_DATA_TYPE_BFLOAT16, 2, const_cast<void*>(ptr), dims, strides, box, es,
             CU_TENSOR_MAP_INTERLEAVE_NONE, CU_TENSOR_MAP_SWIZZLE_128B, CU_TENSOR_MAP_L2_PROMOTION_L2_128B,
             CU_TENSOR_MAP_FLOAT_OOB_FILL_NONE);
    return m;
}

template <int BN, int EPI>
static void launch_gemm(const CUtensorMap& a, const CUtensorMap& b0, const CUtensorMap& b1, const CUtensorMap& b2,
                        int nPerB, int M, int N, int K, EpiParams ep, cudaStream_t st) {
    constexpr int STAGE = 16384 + (BN / 64) * 8192;
    constexpr int NST = (200 * 1024) / STAGE;
    constexpr int SMEM = NST * STAGE + 1024;
    cudaFuncSetAttribute(gemm_kernel<BN, EPI>, cudaFuncAttributeMaxDynamicSharedMemorySize, SMEM);
    dim3 grid((N + BN - 1) / BN, M / 128);
    gemm_kernel<BN, EPI><<<grid, 384, SMEM, st>>>(a, b0, b1, b2, nPerB, N, K, ep);
}

extern "C" void kernel_launch(void* const* d_in, const int* in_sizes, int n_in, void* d_out, int out_size) {
    const bf16* x    = (const bf16*)d_in[0];
    const bf16* mem0 = (const bf16*)d_in[1];
    const bf16* Wq   = (const bf16*)d_in[2];
    const bf16* Wk   = (const bf16*)d_in[3];
    const bf16* Wv   = (const bf16*)d_in[4];
    const bf16* Wo   = (const bf16*)d_in[5];
    const bf16* w_in  = (const bf16*)d_in[8];
    const bf16* w_sp  = (const bf16*)d_in[9];
    const bf16* b_sp  = (const bf16*)d_in[10];
    const bf16* w_out = (const bf16*)d_in[11];
    bf16* out = (bf16*)d_out;
    cudaStream_t st = cudaStreamPerThread;

    if (!p_encode) {
        cudaDriverEntryPointQueryResult qr;
        cudaGetDriverEntryPoint("cuTensorMapEncodeTiled", (void**)&p_encode, cudaEnableDefault, &qr);
    }
    void *p_xn, *p_qkv, *p_z, *p_zg, *p_gate, *p_o, *p_acc, *p_cnt, *p_hx;
    cudaGetSymbolAddress(&p_xn, g_xn); cudaGetSymbolAddress(&p_qkv, g_qkv); cudaGetSymbolAddress(&p_z, g_z);
    cudaGetSymbolAddress(&p_zg, g_zg); cudaGetSymbolAddress(&p_gate, g_gate); cudaGetSymbolAddress(&p_o, g_o);
    cudaGetSymbolAddress(&p_acc, g_acc); cudaGetSymbolAddress(&p_cnt, g_cnt); cudaGetSymbolAddress(&p_hx, g_hx);

    CUtensorMap mA_xn  = make_map(p_xn, S_, D_, D_, 128);
    CUtensorMap mA_wsp = make_map(w_sp, S_, S_, S_, 128);
    CUtensorMap mA_zg  = make_map(p_zg, S_, FH_, FH_, 128);
    CUtensorMap mA_o   = make_map(p_o, S_, HD_, HD_, 128);
    CUtensorMap mB_wq  = make_map(Wq, D_, HD_, HD_, 64);
    CUtensorMap mB_wk  = make_map(Wk, D_, HD_, HD_, 64);
    CUtensorMap mB_wv  = make_map(Wv, D_, HD_, HD_, 64);
    CUtensorMap mB_win = make_map(w_in, D_, F_, F_, 64);
    CUtensorMap mB_z2  = make_map((bf16*)p_z + FH_, S_, FH_, F_, 64);
    CUtensorMap mB_wout = make_map(w_out, FH_, D_, D_, 64);
    CUtensorMap mB_wo  = make_map(Wo, HD_, D_, D_, 64);

    cudaMemsetAsync(p_acc, 0, sizeof(float) * NSEG_ * MEM_ * D_, st);
    cudaMemsetAsync(p_cnt, 0, sizeof(unsigned) * NSEG_ * 32, st);
    void* p_xcnt; cudaGetSymbolAddress(&p_xcnt, g_xcnt);
    cudaMemsetAsync(p_xcnt, 0, sizeof(unsigned) * H_ * NSEG_, st);
    cudaMemsetAsync(p_hx, 0, sizeof(uint2) * H_ * 4 * 256 * 2, st);

    ln_kernel<<<S_ / 8, 256, 0, st>>>(x);
    { EpiParams ep{(bf16*)p_z, F_, nullptr, nullptr}; launch_gemm<128, EPI_GELU>(mA_xn, mB_win, mB_win, mB_win, 1 << 20, S_, F_, D_, ep, st); }
    ln2_kernel<<<S_ / 8, 256, 0, st>>>();
    { EpiParams ep{(bf16*)p_zg, FH_, (const bf16*)p_z, b_sp}; launch_gemm<128, EPI_SP>(mA_wsp, mB_z2, mB_z2, mB_z2, 1 << 20, S_, FH_, S_, ep, st); }
    { EpiParams ep{(bf16*)p_gate, D_, nullptr, nullptr}; launch_gemm<128, EPI_SILU>(mA_zg, mB_wout, mB_wout, mB_wout, 1 << 20, S_, D_, FH_, ep, st); }
    constexpr int RSM = (int)sizeof(RecurSmem) > 16 * 10240 ? (int)sizeof(RecurSmem) : 16 * 10240;
    cudaFuncSetAttribute(recur_kernel, cudaFuncAttributeMaxDynamicSharedMemorySize, RSM);
    recur_kernel<<<128, RT, RSM, st>>>(mem0, Wq, Wk, Wv, Wo);
    attn_x_kernel<<<NSEG_ * H_, 128, 0, st>>>();
    { EpiParams ep{out, D_, x, (const bf16*)p_gate}; launch_gemm<128, EPI_FINAL>(mA_o, mB_wo, mB_wo, mB_wo, 1 << 20, S_, D_, HD_, ep, st); }
}
```

```cpp
#include <cuda_runtime.h>
#include <cuda_bf16.h>
#include <cuda.h>
#include <stdint.h>

typedef __nv_bfloat16 bf16;

constexpr int S_   = 2048;
constexpr int D_   = 640;
constexpr int H_   = 32;
constexpr int DH_  = 128;
constexpr int MEM_ = 8;
constexpr int SEG_ = 32;
constexpr int NSEG_ = S_ / SEG_;
constexpr int HD_  = H_ * DH_;
constexpr int F_   = 1728;
constexpr int FH_  = 864;

__device__ bf16 g_xn[S_ * D_];
__device__ bf16 g_qkv[(size_t)S_ * 3 * HD_];
__device__ bf16 g_z[S_ * F_];
__device__ bf16 g_zg[S_ * FH_];
__device__ bf16 g_gate[S_ * D_];
__device__ bf16 g_kmem[NSEG_ * MEM_ * HD_];
__device__ bf16 g_vmem[NSEG_ * MEM_ * HD_];
__device__ bf16 g_o[(size_t)S_ * HD_];
__device__ float g_acc[NSEG_ * MEM_ * D_];
__device__ unsigned g_cnt[NSEG_ * 32];
__device__ unsigned g_xcnt[H_ * NSEG_];
__device__ uint2 g_hx[H_ * 4 * 256 * 2];

__device__ __forceinline__ uint32_t smem_u32(const void* p) { return (uint32_t)__cvta_generic_to_shared(p); }
__device__ __forceinline__ float bf2f(bf16 v) { return __bfloat162float(v); }
__device__ __forceinline__ float rbf(float v) { return __bfloat162float(__float2bfloat16_rn(v)); }
__device__ __forceinline__ uint32_t pack_bf16(float lo, float hi) {
    __nv_bfloat162 t = __floats2bfloat162_rn(lo, hi);
    return *reinterpret_cast<uint32_t*>(&t);
}
__device__ __forceinline__ float lo_f(uint32_t u) { return __uint_as_float(u << 16); }
__device__ __forceinline__ float hi_f(uint32_t u) { return __uint_as_float(u & 0xffff0000u); }

__device__ __forceinline__ void mbar_init(uint32_t bar, uint32_t cnt) {
    asm volatile("mbarrier.init.shared.b64 [%0], %1;" ::"r"(bar), "r"(cnt));
}
__device__ __forceinline__ void mbar_expect_tx(uint32_t bar, uint32_t bytes) {
    asm volatile("mbarrier.arrive.expect_tx.shared.b64 _, [%0], %1;" ::"r"(bar), "r"(bytes) : "memory");
}
__device__ __forceinline__ void mbar_arrive(uint32_t bar) {
    asm volatile("mbarrier.arrive.shared.b64 _, [%0];" ::"r"(bar) : "memory");
}
__device__ __forceinline__ void mbar_wait(uint32_t bar, uint32_t parity) {
    asm volatile(
        "{\n .reg .pred p;\n"
        "WAIT_%=:\n"
        " mbarrier.try_wait.parity.shared.b64 p, [%0], %1;\n"
        " @p bra DONE_%=;\n"
        " bra WAIT_%=;\n"
        "DONE_%=:\n}\n" ::"r"(bar), "r"(parity) : "memory");
}
__device__ __forceinline__ void tma_load_2d(uint32_t dst, const CUtensorMap* tm, uint32_t bar, int c0, int c1) {
    asm volatile(
        "cp.async.bulk.tensor.2d.shared::cluster.global.mbarrier::complete_tx::bytes [%0], [%1, {%3, %4}], [%2];"
        ::"r"(dst), "l"(tm), "r"(bar), "r"(c0), "r"(c1) : "memory");
}
__device__ __forceinline__ void wgmma_fence() { asm volatile("wgmma.fence.sync.aligned;" ::: "memory"); }
__device__ __forceinline__ void wgmma_commit() { asm volatile("wgmma.commit_group.sync.aligned;" ::: "memory"); }
template <int N> __device__ __forceinline__ void wgmma_wait() { asm volatile("wgmma.wait_group.sync.aligned %0;" ::"n"(N) : "memory"); }

__device__ __forceinline__ uint64_t make_desc(uint32_t addr, uint32_t lbo, uint32_t sbo) {
    return (uint64_t)((addr & 0x3FFFF) >> 4) | ((uint64_t)(lbo >> 4) << 16) | ((uint64_t)(sbo >> 4) << 32) | (1ull << 62);
}

template <int N> struct Wgmma;
template <> struct Wgmma<128> {
    static __device__ __forceinline__ void mma(float* d, uint64_t da, uint64_t db, int sd) {
        asm volatile(
            "{\n.reg .pred p;\nsetp.ne.b32 p, %66, 0;\n"
            "wgmma.mma_async.sync.aligned.m64n128k16.f32.bf16.bf16 "
            "{%0,%1,%2,%3,%4,%5,%6,%7,%8,%9,%10,%11,%12,%13,%14,%15,"
            "%16,%17,%18,%19,%20,%21,%22,%23,%24,%25,%26,%27,%28,%29,%30,%31,"
            "%32,%33,%34,%35,%36,%37,%38,%39,%40,%41,%42,%43,%44,%45,%46,%47,"
            "%48,%49,%50,%51,%52,%53,%54,%55,%56,%57,%58,%59,%60,%61,%62,%63},"
            "%64,%65,p,1,1,0,1;\n}\n"
            : "+f"(d[0]), "+f"(d[1]), "+f"(d[2]), "+f"(d[3]), "+f"(d[4]), "+f"(d[5]), "+f"(d[6]), "+f"(d[7]),
              "+f"(d[8]), "+f"(d[9]), "+f"(d[10]), "+f"(d[11]), "+f"(d[12]), "+f"(d[13]), "+f"(d[14]), "+f"(d[15]),
              "+f"(d[16]), "+f"(d[17]), "+f"(d[18]), "+f"(d[19]), "+f"(d[20]), "+f"(d[21]), "+f"(d[22]), "+f"(d[23]),
              "+f"(d[24]), "+f"(d[25]), "+f"(d[26]), "+f"(d[27]), "+f"(d[28]), "+f"(d[29]), "+f"(d[30]), "+f"(d[31]),
              "+f"(d[32]), "+f"(d[33]), "+f"(d[34]), "+f"(d[35]), "+f"(d[36]), "+f"(d[37]), "+f"(d[38]), "+f"(d[39]),
              "+f"(d[40]), "+f"(d[41]), "+f"(d[42]), "+f"(d[43]), "+f"(d[44]), "+f"(d[45]), "+f"(d[46]), "+f"(d[47]),
              "+f"(d[48]), "+f"(d[49]), "+f"(d[50]), "+f"(d[51]), "+f"(d[52]), "+f"(d[53]), "+f"(d[54]), "+f"(d[55]),
              "+f"(d[56]), "+f"(d[57]), "+f"(d[58]), "+f"(d[59]), "+f"(d[60]), "+f"(d[61]), "+f"(d[62]), "+f"(d[63])
            : "l"(da), "l"(db), "r"(sd));
    }
};
template <> struct Wgmma<192> {
    static __device__ __forceinline__ void mma(float* d, uint64_t da, uint64_t db, int sd) {
        asm volatile(
            "{\n.reg .pred p;\nsetp.ne.b32 p, %98, 0;\n"
            "wgmma.mma_async.sync.aligned.m64n192k16.f32.bf16.bf16 "
            "{%0,%1,%2,%3,%4,%5,%6,%7,%8,%9,%10,%11,%12,%13,%14,%15,"
            "%16,%17,%18,%19,%20,%21,%22,%23,%24,%25,%26,%27,%28,%29,%30,%31,"
            "%32,%33,%34,%35,%36,%37,%38,%39,%40,%41,%42,%43,%44,%45,%46,%47,"
            "%48,%49,%50,%51,%52,%53,%54,%55,%56,%57,%58,%59,%60,%61,%62,%63,"
            "%64,%65,%66,%67,%68,%69,%70,%71,%72,%73,%74,%75,%76,%77,%78,%79,"
            "%80,%81,%82,%83,%84,%85,%86,%87,%88,%89,%90,%91,%92,%93,%94,%95},"
            "%96,%97,p,1,1,0,1;\n}\n"
            : "+f"(d[0]), "+f"(d[1]), "+f"(d[2]), "+f"(d[3]), "+f"(d[4]), "+f"(d[5]), "+f"(d[6]), "+f"(d[7]),
              "+f"(d[8]), "+f"(d[9]), "+f"(d[10]), "+f"(d[11]), "+f"(d[12]), "+f"(d[13]), "+f"(d[14]), "+f"(d[15]),
              "+f"(d[16]), "+f"(d[17]), "+f"(d[18]), "+f"(d[19]), "+f"(d[20]), "+f"(d[21]), "+f"(d[22]), "+f"(d[23]),
              "+f"(d[24]), "+f"(d[25]), "+f"(d[26]), "+f"(d[27]), "+f"(d[28]), "+f"(d[29]), "+f"(d[30]), "+f"(d[31]),
              "+f"(d[32]), "+f"(d[33]), "+f"(d[34]), "+f"(d[35]), "+f"(d[36]), "+f"(d[37]), "+f"(d[38]), "+f"(d[39]),
              "+f"(d[40]), "+f"(d[41]), "+f"(d[42]), "+f"(d[43]), "+f"(d[44]), "+f"(d[45]), "+f"(d[46]), "+f"(d[47]),
              "+f"(d[48]), "+f"(d[49]), "+f"(d[50]), "+f"(d[51]), "+f"(d[52]), "+f"(d[53]), "+f"(d[54]), "+f"(d[55]),
              "+f"(d[56]), "+f"(d[57]), "+f"(d[58]), "+f"(d[59]), "+f"(d[60]), "+f"(d[61]), "+f"(d[62]), "+f"(d[63]),
              "+f"(d[64]), "+f"(d[65]), "+f"(d[66]), "+f"(d[67]), "+f"(d[68]), "+f"(d[69]), "+f"(d[70]), "+f"(d[71]),
              "+f"(d[72]), "+f"(d[73]), "+f"(d[74]), "+f"(d[75]), "+f"(d[76]), "+f"(d[77]), "+f"(d[78]), "+f"(d[79]),
              "+f"(d[80]), "+f"(d[81]), "+f"(d[82]), "+f"(d[83]), "+f"(d[84]), "+f"(d[85]), "+f"(d[86]), "+f"(d[87]),
              "+f"(d[88]), "+f"(d[89]), "+f"(d[90]), "+f"(d[91]), "+f"(d[92]), "+f"(d[93]), "+f"(d[94]), "+f"(d[95])
            : "l"(da), "l"(db), "r"(sd));
    }
};

template <> struct Wgmma<256> {
    static __device__ __forceinline__ void mma(float* d, uint64_t da, uint64_t db, int sd) {
        asm volatile(
            "{\n.reg .pred p;\nsetp.ne.b32 p, %130, 0;\n"
            "wgmma.mma_async.sync.aligned.m64n256k16.f32.bf16.bf16 "
            "{%0,%1,%2,%3,%4,%5,%6,%7,%8,%9,%10,%11,%12,%13,%14,%15,%16,%17,%18,%19,%20,%21,%22,%23,%24,%25,%26,%27,%28,%29,%30,%31,%32,%33,%34,%35,%36,%37,%38,%39,%40,%41,%42,%43,%44,%45,%46,%47,%48,%49,%50,%51,%52,%53,%54,%55,%56,%57,%58,%59,%60,%61,%62,%63,%64,%65,%66,%67,%68,%69,%70,%71,%72,%73,%74,%75,%76,%77,%78,%79,%80,%81,%82,%83,%84,%85,%86,%87,%88,%89,%90,%91,%92,%93,%94,%95,%96,%97,%98,%99,%100,%101,%102,%103,%104,%105,%106,%107,%108,%109,%110,%111,%112,%113,%114,%115,%116,%117,%118,%119,%120,%121,%122,%123,%124,%125,%126,%127},"
            "%128,%129,p,1,1,0,1;\n}\n"
            : "+f"(d[0]), "+f"(d[1]), "+f"(d[2]), "+f"(d[3]), "+f"(d[4]), "+f"(d[5]), "+f"(d[6]), "+f"(d[7]), "+f"(d[8]), "+f"(d[9]), "+f"(d[10]), "+f"(d[11]), "+f"(d[12]), "+f"(d[13]), "+f"(d[14]), "+f"(d[15]), "+f"(d[16]), "+f"(d[17]), "+f"(d[18]), "+f"(d[19]), "+f"(d[20]), "+f"(d[21]), "+f"(d[22]), "+f"(d[23]), "+f"(d[24]), "+f"(d[25]), "+f"(d[26]), "+f"(d[27]), "+f"(d[28]), "+f"(d[29]), "+f"(d[30]), "+f"(d[31]), "+f"(d[32]), "+f"(d[33]), "+f"(d[34]), "+f"(d[35]), "+f"(d[36]), "+f"(d[37]), "+f"(d[38]), "+f"(d[39]), "+f"(d[40]), "+f"(d[41]), "+f"(d[42]), "+f"(d[43]), "+f"(d[44]), "+f"(d[45]), "+f"(d[46]), "+f"(d[47]), "+f"(d[48]), "+f"(d[49]), "+f"(d[50]), "+f"(d[51]), "+f"(d[52]), "+f"(d[53]), "+f"(d[54]), "+f"(d[55]), "+f"(d[56]), "+f"(d[57]), "+f"(d[58]), "+f"(d[59]), "+f"(d[60]), "+f"(d[61]), "+f"(d[62]), "+f"(d[63]), "+f"(d[64]), "+f"(d[65]), "+f"(d[66]), "+f"(d[67]), "+f"(d[68]), "+f"(d[69]), "+f"(d[70]), "+f"(d[71]), "+f"(d[72]), "+f"(d[73]), "+f"(d[74]), "+f"(d[75]), "+f"(d[76]), "+f"(d[77]), "+f"(d[78]), "+f"(d[79]), "+f"(d[80]), "+f"(d[81]), "+f"(d[82]), "+f"(d[83]), "+f"(d[84]), "+f"(d[85]), "+f"(d[86]), "+f"(d[87]), "+f"(d[88]), "+f"(d[89]), "+f"(d[90]), "+f"(d[91]), "+f"(d[92]), "+f"(d[93]), "+f"(d[94]), "+f"(d[95]), "+f"(d[96]), "+f"(d[97]), "+f"(d[98]), "+f"(d[99]), "+f"(d[100]), "+f"(d[101]), "+f"(d[102]), "+f"(d[103]), "+f"(d[104]), "+f"(d[105]), "+f"(d[106]), "+f"(d[107]), "+f"(d[108]), "+f"(d[109]), "+f"(d[110]), "+f"(d[111]), "+f"(d[112]), "+f"(d[113]), "+f"(d[114]), "+f"(d[115]), "+f"(d[116]), "+f"(d[117]), "+f"(d[118]), "+f"(d[119]), "+f"(d[120]), "+f"(d[121]), "+f"(d[122]), "+f"(d[123]), "+f"(d[124]), "+f"(d[125]), "+f"(d[126]), "+f"(d[127])
            : "l"(da), "l"(db), "r"(sd));
    }
};
template <int W>
__device__ __forceinline__ void ln_row(const bf16* __restrict__ src, bf16* __restrict__ dst, int lane) {
    constexpr int NP = W / 64;
    constexpr int REM = (W / 2) % 32;
    uint32_t v[NP + 1];
    const uint32_t* s32 = reinterpret_cast<const uint32_t*>(src);
    float sum = 0.f;
#pragma unroll
    for (int i = 0; i < NP; i++) { v[i] = s32[i * 32 + lane]; sum += lo_f(v[i]) + hi_f(v[i]); }
    if (REM) { v[NP] = (lane < REM) ? s32[NP * 32 + lane] : 0u; if (lane < REM) sum += lo_f(v[NP]) + hi_f(v[NP]); }
#pragma unroll
    for (int o = 16; o; o >>= 1) sum += __shfl_xor_sync(0xffffffffu, sum, o);
    float mean = sum * (1.0f / W);
    float vs = 0.f;
#pragma unroll
    for (int i = 0; i < NP; i++) { float a = lo_f(v[i]) - mean, b = hi_f(v[i]) - mean; vs += a * a + b * b; }
    if (REM && lane < REM) { float a = lo_f(v[NP]) - mean, b = hi_f(v[NP]) - mean; vs += a * a + b * b; }
#pragma unroll
    for (int o = 16; o; o >>= 1) vs += __shfl_xor_sync(0xffffffffu, vs, o);
    float var = rbf(vs * (1.0f / W));
    float mb = rbf(mean);
    float den = rbf(sqrtf(rbf(var + 1e-5f)));
    uint32_t* d32 = reinterpret_cast<uint32_t*>(dst);
#pragma unroll
    for (int i = 0; i < NP; i++) d32[i * 32 + lane] = pack_bf16(rbf(lo_f(v[i]) - mb) / den, rbf(hi_f(v[i]) - mb) / den);
    if (REM && lane < REM) d32[NP * 32 + lane] = pack_bf16(rbf(lo_f(v[NP]) - mb) / den, rbf(hi_f(v[NP]) - mb) / den);
}

__global__ void ln_kernel(const bf16* __restrict__ x) {
    int row = blockIdx.x * 8 + (threadIdx.x >> 5);
    ln_row<D_>(x + (size_t)row * D_, g_xn + (size_t)row * D_, threadIdx.x & 31);
}
__global__ void ln2_kernel() {
    int row = blockIdx.x * 8 + (threadIdx.x >> 5);
    bf16* p = g_z + (size_t)row * F_ + FH_;
    ln_row<FH_>(p, p, threadIdx.x & 31);
}

enum { EPI_STORE = 0, EPI_GELU = 1, EPI_SP = 2, EPI_SILU = 3, EPI_FINAL = 4 };
struct EpiParams {
    bf16* out; int ldo;
    const bf16* aux0;
    const bf16* aux1;
};

__device__ __forceinline__ float gelu_tanh_f(float x) {
    const float k0 = 0.7978845608028654f, k1 = 0.044715f;
    float inner = k0 * (x + k1 * x * x * x);
    return 0.5f * x * (1.0f + tanhf(inner));
}
__device__ __forceinline__ float silu_f(float x) { return x / (1.0f + expf(-x)); }

template <int BN, int EPI>
__global__ void __launch_bounds__(384, 1)
gemm_kernel(const __grid_constant__ CUtensorMap tmA, const __grid_constant__ CUtensorMap tmB0,
            const __grid_constant__ CUtensorMap tmB1, const __grid_constant__ CUtensorMap tmB2,
            int nPerB, int N, int K, EpiParams ep) {
    constexpr int BM = 128, BK = 64;
    constexpr int A_BYTES = BM * BK * 2;
    constexpr int B_BYTES = (BN / 64) * 8192;
    constexpr int STAGE = A_BYTES + B_BYTES;
    constexpr int NST = (200 * 1024) / STAGE;
    constexpr int OLD = BN + 8;
    extern __shared__ __align__(1024) uint8_t smem_raw[];
    uint8_t* smem = (uint8_t*)(((uintptr_t)smem_raw + 1023) & ~(uintptr_t)1023);
    __shared__ __align__(8) uint64_t full_bar[NST], empty_bar[NST];

    const int tid = threadIdx.x, wg = tid >> 7;
    const int m0 = blockIdx.y * BM, n0 = blockIdx.x * BN;
    const int nk = (K + BK - 1) / BK;

    if (tid == 0) {
        for (int i = 0; i < NST; i++) { mbar_init(smem_u32(&full_bar[i]), 1); mbar_init(smem_u32(&empty_bar[i]), 2); }
        asm volatile("fence.mbarrier_init.release.cluster;" ::: "memory");
    }
    __syncthreads();

    if (wg == 0) {
        if (tid == 0) {
            const int bsel = n0 / nPerB;
            const CUtensorMap* tmB = bsel == 0 ? &tmB0 : (bsel == 1 ? &tmB1 : &tmB2);
            const int nb = n0 - bsel * nPerB;
            for (int kt = 0; kt < nk; kt++) {
                int st = kt % NST; uint32_t ph = (kt / NST) & 1;
                mbar_wait(smem_u32(&empty_bar[st]), ph ^ 1);
                uint32_t fb = smem_u32(&full_bar[st]);
                mbar_expect_tx(fb, STAGE);
                uint32_t sa = smem_u32(smem + st * STAGE);
                tma_load_2d(sa, &tmA, fb, kt * BK, m0);
#pragma unroll
                for (int j = 0; j < BN / 64; j++) tma_load_2d(sa + A_BYTES + j * 8192, tmB, fb, nb + j * 64, kt * BK);
            }
        }
    } else {
        const int cw = wg - 1;
        float acc[BN / 2];
        for (int kt = 0; kt < nk; kt++) {
            int st = kt % NST; uint32_t ph = (kt / NST) & 1;
            mbar_wait(smem_u32(&full_bar[st]), ph);
            uint32_t sa = smem_u32(smem + st * STAGE) + cw * 64 * 128;
            uint32_t sb = smem_u32(smem + st * STAGE) + A_BYTES;
            wgmma_fence();
#pragma unroll
            for (int k = 0; k < BK / 16; k++) {
                uint64_t da = make_desc(sa + k * 32, 16, 1024);
                uint64_t db = make_desc(sb + k * 2048, 8192, 1024);
                Wgmma<BN>::mma(acc, da, db, (kt | k) != 0);
            }
            wgmma_commit();
            wgmma_wait<1>();
            if (kt > 0 && (tid & 127) == 0) mbar_arrive(smem_u32(&empty_bar[(kt - 1) % NST]));
        }
        wgmma_wait<0>();
        asm volatile("bar.sync 1, 256;" ::: "memory");
        const int lane = tid & 31, wi = (tid >> 5) & 3, g = lane >> 2, t = lane & 3;
        bf16* stg = reinterpret_cast<bf16*>(smem) + cw * 64 * OLD;
#pragma unroll
        for (int j = 0; j < BN / 8; j++) {
            *reinterpret_cast<uint32_t*>(&stg[(wi * 16 + g) * OLD + j * 8 + 2 * t]) = pack_bf16(acc[4 * j], acc[4 * j + 1]);
            *reinterpret_cast<uint32_t*>(&stg[(wi * 16 + g + 8) * OLD + j * 8 + 2 * t]) = pack_bf16(acc[4 * j + 2], acc[4 * j + 3]);
        }
        asm volatile("bar.sync %0, 128;" ::"r"(2 + cw) : "memory");
        constexpr int CPR = BN / 8;
        const int ltid = tid & 127;
#pragma unroll 4
        for (int i = ltid; i < 64 * CPR; i += 128) {
            int r = i / CPR, ch = i % CPR;
            int row = m0 + cw * 64 + r, col = n0 + ch * 8;
            if (col >= N) continue;
            uint4 v = *reinterpret_cast<const uint4*>(&stg[r * OLD + ch * 8]);
            uint32_t u[4] = {v.x, v.y, v.z, v.w}, o[4];
            if (EPI == EPI_STORE) {
#pragma unroll
                for (int q = 0; q < 4; q++) o[q] = u[q];
            } else if (EPI == EPI_GELU) {
#pragma unroll
                for (int q = 0; q < 4; q++) o[q] = pack_bf16(gelu_tanh_f(lo_f(u[q])), gelu_tanh_f(hi_f(u[q])));
            } else if (EPI == EPI_SP) {
                float bb = bf2f(ep.aux1[row]);
                uint4 z = *reinterpret_cast<const uint4*>(ep.aux0 + (size_t)row * F_ + col);
                uint32_t zz[4] = {z.x, z.y, z.z, z.w};
#pragma unroll
                for (int q = 0; q < 4; q++) o[q] = pack_bf16(lo_f(zz[q]) * rbf(lo_f(u[q]) + bb), hi_f(zz[q]) * rbf(hi_f(u[q]) + bb));
            } else if (EPI == EPI_SILU) {
#pragma unroll
                for (int q = 0; q < 4; q++) o[q] = pack_bf16(silu_f(lo_f(u[q])), silu_f(hi_f(u[q])));
            } else {
                uint4 xv = *reinterpret_cast<const uint4*>(ep.aux0 + (size_t)row * D_ + col);
                uint4 gv = *reinterpret_cast<const uint4*>(ep.aux1 + (size_t)row * D_ + col);
                uint32_t xx[4] = {xv.x, xv.y, xv.z, xv.w}, gg[4] = {gv.x, gv.y, gv.z, gv.w};
#pragma unroll
                for (int q = 0; q < 4; q++)
                    o[q] = pack_bf16(lo_f(xx[q]) + rbf(lo_f(u[q]) * lo_f(gg[q])), hi_f(xx[q]) + rbf(hi_f(u[q]) * hi_f(gg[q])));
            }
            *reinterpret_cast<uint4*>(ep.out + (size_t)row * ep.ldo + col) = make_uint4(o[0], o[1], o[2], o[3]);
        }
    }
}

__device__ __forceinline__ void mma16816(float* c, const uint32_t* a, uint32_t b0, uint32_t b1) {
    asm volatile(
        "mma.sync.aligned.m16n8k16.row.col.f32.bf16.bf16.f32 {%0,%1,%2,%3}, {%4,%5,%6,%7}, {%8,%9}, {%0,%1,%2,%3};"
        : "+f"(c[0]), "+f"(c[1]), "+f"(c[2]), "+f"(c[3])
        : "r"(a[0]), "r"(a[1]), "r"(a[2]), "r"(a[3]), "r"(b0), "r"(b1));
}
__device__ __forceinline__ void ldsm_x4(uint32_t* r, uint32_t addr) {
    asm volatile("ldmatrix.sync.aligned.m8n8.x4.shared.b16 {%0,%1,%2,%3}, [%4];"
                 : "=r"(r[0]), "=r"(r[1]), "=r"(r[2]), "=r"(r[3]) : "r"(addr));
}
__device__ __forceinline__ void ldsm_x4_t(uint32_t* r, uint32_t addr) {
    asm volatile("ldmatrix.sync.aligned.m8n8.x4.trans.shared.b16 {%0,%1,%2,%3}, [%4];"
                 : "=r"(r[0]), "=r"(r[1]), "=r"(r[2]), "=r"(r[3]) : "r"(addr));
}
__device__ __forceinline__ uint4 ld_relaxed_v4(const void* p) {
    uint4 v;
    asm volatile("ld.relaxed.gpu.global.v4.u32 {%0,%1,%2,%3}, [%4];" : "=r"(v.x), "=r"(v.y), "=r"(v.z), "=r"(v.w) : "l"(p) : "memory");
    return v;
}
__device__ __forceinline__ void st_relaxed_v4(void* p, uint32_t a, uint32_t b, uint32_t c, uint32_t d) {
    asm volatile("st.relaxed.gpu.global.v4.u32 [%0], {%1,%2,%3,%4};" ::"l"(p), "r"(a), "r"(b), "r"(c), "r"(d) : "memory");
}
__device__ __forceinline__ void st_relaxed_v2(void* p, uint32_t a, uint32_t b) {
    asm volatile("st.relaxed.gpu.global.v2.u32 [%0], {%1,%2};" ::"l"(p), "r"(a), "r"(b) : "memory");
}
__device__ __forceinline__ void cp_async16(uint32_t dst, const void* src) {
    asm volatile("cp.async.cg.shared.global [%0], [%1], 16;" ::"r"(dst), "l"(src) : "memory");
}
__device__ __forceinline__ void cp_async_commit() { asm volatile("cp.async.commit_group;" ::: "memory"); }
template <int N> __device__ __forceinline__ void cp_async_wait() { asm volatile("cp.async.wait_group %0;" ::"n"(N) : "memory"); }

#define PROF(i) do {} while (0)
constexpr int SPIN_LIMIT = 4000000;

__device__ __forceinline__ uint4 poll_ll(const void* p, uint32_t flag) {
    uint4 v = ld_relaxed_v4(p);
    int n = 0;
    while ((v.y != flag || v.w != flag) && ++n < SPIN_LIMIT) {
        v = ld_relaxed_v4(p);
    }
    return v;
}

constexpr int RT = 512;
constexpr int MEMS_LD = D_ + 8;
constexpr int HL = DH_ + 8;
struct RecurSmem {
    bf16 mem[MEM_][MEMS_LD];
    bf16 kall[2][48][HL];
    bf16 vall[2][48][HL];
    bf16 qm[16][HL];
    float sc[MEM_][40];
    bf16 p[MEM_][48 + 8];
    bf16 om[MEM_][HL];
    float red[12][16 * 8];
    float wred[2][5][16 * 8];
    bf16 xs[SEG_][MEMS_LD];
    float redx[6][4][16 * 8];
    bf16 xo[SEG_][96 + 8];
};

__device__ __forceinline__ void bar_sync(int id, int n) { asm volatile("bar.sync %0, %1;" ::"r"(id), "r"(n) : "memory"); }
__device__ __forceinline__ void bar_arrive(int id, int n) { asm volatile("bar.arrive %0, %1;" ::"r"(id), "r"(n) : "memory"); }
__device__ __forceinline__ void sts64(uint32_t a, uint32_t x, uint32_t y) { asm volatile("st.shared.v2.u32 [%0], {%1,%2};" ::"r"(a), "r"(x), "r"(y) : "memory"); }
__device__ __forceinline__ uint32_t ldg_u16x2(const bf16* p0, const bf16* p1) {
    return (uint32_t)*(const uint16_t*)p0 | ((uint32_t)*(const uint16_t*)p1 << 16);
}
enum { BAR_MEM = 1, BAR_RED = 2, BAR_CTL = 3, BAR_WO = 4, BAR_INIT = 6, BAR_X = 7, BAR_GO = 8 };

__global__ void __launch_bounds__(RT, 1)
recur_kernel(const bf16* __restrict__ mem0, const bf16* __restrict__ Wq, const bf16* __restrict__ Wk,
             const bf16* __restrict__ Wv, const bf16* __restrict__ Wo) {
    extern __shared__ __align__(16) uint8_t smem_raw[];
    RecurSmem& sm = *reinterpret_cast<RecurSmem*>(smem_raw);
    const int tid = threadIdx.x, lane = tid & 31, w = tid >> 5;
    const int g = lane >> 2, t = lane & 3;
    const int h = blockIdx.x >> 2, c = blockIdx.x & 3;

    if (w < 12) {
        asm volatile("setmaxnreg.dec.sync.aligned.u32 112;");
        uint32_t wf[20][4];
        const int mt = w % 6, kh = w / 6;
        {
            const bf16* W = (mt < 2) ? Wq : (mt < 4 ? Wk : Wv);
            int f0 = h * DH_ + c * 32 + (mt & 1) * 16;
            uint32_t stg = smem_u32(smem_raw) + w * 10240;
#pragma unroll 4
            for (int i = lane; i < 640; i += 32)
                cp_async16(stg + i * 16, W + (size_t)(kh * 320 + (i >> 1)) * HD_ + f0 + (i & 1) * 8);
            cp_async_commit(); cp_async_wait<0>(); __syncwarp();
            uint32_t la = stg + ((lane & 7) + ((lane >> 4) & 1) * 8) * 32 + ((lane >> 3) & 1) * 16;
#pragma unroll
            for (int i = 0; i < 20; i++) ldsm_x4_t(wf[i], la + i * 512);
        }
        bar_sync(BAR_INIT, RT);
        const uint32_t base = smem_u32(&sm.mem[lane & 7][kh * 320 + (lane >> 3) * 8]);
        const uint32_t rp = smem_u32(&sm.red[w][g * 8 + 2 * t]);
        const uint32_t xbase = smem_u32(&sm.xs[lane & 7][kh * 320 + (lane >> 3) * 8]);
        const uint32_t rxp = smem_u32(&sm.redx[mt][0][lane * 4]);
        auto load_x = [&](int seg) {
            for (int i = tid; i < SEG_ * (D_ / 8); i += 384) {
                int r = i / (D_ / 8), ch = i % (D_ / 8);
                cp_async16(smem_u32(&sm.xs[r][ch * 8]), g_xn + (size_t)(seg * SEG_ + r) * D_ + ch * 8);
            }
            cp_async_commit();
        };
        auto xwork = [&](int seg) {
            cp_async_wait<0>();
            bar_sync(BAR_X, 384);
            float acc[4][4];
#pragma unroll
            for (int nt = 0; nt < 4; nt++) { acc[nt][0] = acc[nt][1] = acc[nt][2] = acc[nt][3] = 0.f; }
#pragma unroll
            for (int i = 0; i < 10; i++) {
#pragma unroll
                for (int nt = 0; nt < 4; nt++) {
                    uint32_t b[4];
                    ldsm_x4(b, xbase + nt * (8 * MEMS_LD * 2) + i * 64);
                    mma16816(acc[nt], wf[2 * i], b[0], b[1]);
                    mma16816(acc[nt], wf[2 * i + 1], b[2], b[3]);
                }
            }
            if (kh == 1) {
#pragma unroll
                for (int nt = 0; nt < 4; nt++)
                    asm volatile("st.shared.v4.f32 [%0], {%1,%2,%3,%4};" ::"r"(rxp + nt * 512), "f"(acc[nt][0]), "f"(acc[nt][1]), "f"(acc[nt][2]), "f"(acc[nt][3]) : "memory");
            }
            bar_sync(BAR_X, 384);
            if (seg + 1 < NSEG_) load_x(seg + 1);
            if (kh == 0) {
#pragma unroll
                for (int nt = 0; nt < 4; nt++) {
                    float4 o;
                    asm volatile("ld.shared.v4.f32 {%0,%1,%2,%3}, [%4];" : "=f"(o.x), "=f"(o.y), "=f"(o.z), "=f"(o.w) : "r"(rxp + nt * 512) : "memory");
                    bf16* d = &sm.xo[nt * 8 + 2 * t][mt * 16 + g];
                    d[0] = __float2bfloat16_rn(acc[nt][0] + o.x);
                    d[104] = __float2bfloat16_rn(acc[nt][1] + o.y);
                    d[8] = __float2bfloat16_rn(acc[nt][2] + o.z);
                    d[104 + 8] = __float2bfloat16_rn(acc[nt][3] + o.w);
                }
            }
            bar_sync(BAR_X, 384);
            {
                int r = tid / 12, ch = tid % 12;
                uint4 v = *reinterpret_cast<const uint4*>(&sm.xo[r][ch * 8]);
                *reinterpret_cast<uint4*>(g_qkv + (size_t)(seg * SEG_ + r) * (3 * HD_) + (ch >> 2) * HD_ + h * DH_ + c * 32 + (ch & 3) * 8) = v;
            }
        };
        auto xsignal = [&](int seg) {
            __threadfence();
            __syncwarp();
            if (lane == 0) atomicAdd(&g_xcnt[h * NSEG_ + seg], 1u);
        };
        load_x(0);
        xwork(0); xsignal(0);
        xwork(1); xsignal(1);
        for (int s = 0; s < NSEG_; s++) {
            bar_sync(BAR_MEM, RT);
            float a0[4] = {0.f, 0.f, 0.f, 0.f}, a1[4] = {0.f, 0.f, 0.f, 0.f};
#pragma unroll
            for (int i = 0; i < 10; i++) {
                uint32_t b[4];
                ldsm_x4(b, base + i * 64);
                mma16816(a0, wf[2 * i], b[0], b[1]);
                mma16816(a1, wf[2 * i + 1], b[2], b[3]);
            }
            sts64(rp, __float_as_uint(a0[0] + a1[0]), __float_as_uint(a0[1] + a1[1]));
            sts64(rp + 256, __float_as_uint(a0[2] + a1[2]), __float_as_uint(a0[3] + a1[3]));
            bar_arrive(BAR_RED, RT);
            if (s >= 1 && s + 1 < NSEG_) xsignal(s + 1);
            if (s + 1 < NSEG_) bar_sync(BAR_GO, RT);
            if (s + 2 < NSEG_) xwork(s + 2);
        }
    } else {
        asm volatile("setmaxnreg.inc.sync.aligned.u32 176;");
        const int ct = tid - 384, cw = w - 12;
        const int mg = cw >> 1, kh = cw & 1;
        uint32_t wf[20][4];
        {
            uint32_t stg = smem_u32(smem_raw) + 12 * 10240 + cw * 10240;
#pragma unroll 4
            for (int i = lane; i < 640; i += 32) {
                int r = i / 10, ch = i % 10;
                cp_async16(stg + r * 160 + ch * 16, Wo + (size_t)(h * DH_ + kh * 64 + r) * D_ + c * 160 + mg * 80 + ch * 8);
            }
            cp_async_commit(); cp_async_wait<0>(); __syncwarp();
            uint32_t la = stg + ((lane & 7) + ((lane >> 4) & 1) * 8) * 160 + ((lane >> 3) & 1) * 16;
#pragma unroll
            for (int mi = 0; mi < 5; mi++)
#pragma unroll
                for (int ki = 0; ki < 4; ki++) ldsm_x4_t(wf[mi * 4 + ki], la + ki * 16 * 160 + mi * 32);
        }
        bar_sync(BAR_INIT, RT);
        for (int i = ct; i < 2 * 8 * HL; i += 128) {
            int b = i / (8 * HL), r = (i / HL) % 8, cc = i % HL;
            sm.kall[b][40 + r][cc] = __float2bfloat16(0.f);
            sm.vall[b][40 + r][cc] = __float2bfloat16(0.f);
        }
        for (int i = ct; i < 8 * HL; i += 128) sm.qm[8 + i / HL][i % HL] = __float2bfloat16(0.f);
        for (int i = ct; i < 8 * 56; i += 128) sm.p[i / 56][i % 56] = __float2bfloat16(0.f);
        bar_sync(BAR_CTL, 128);
        constexpr uint32_t KV_BUF = 48 * HL * 2;
        const bf16* kv_src = g_qkv + (size_t)(ct >> 4) * (3 * HD_) + HD_ + h * DH_ + (ct & 15) * 8;
        const uint32_t kv_dst0 = smem_u32(&sm.kall[0][MEM_ + (ct >> 4)][(ct & 15) * 8]);
        const uint32_t kv_dst1 = smem_u32(&sm.vall[0][MEM_ + (ct >> 4)][(ct & 15) * 8]);
        auto prefetch_kv = [&](int s, int buf) {
            if (ct == 0) {
                const unsigned* cp = g_xcnt + h * NSEG_ + s;
                unsigned v; int n = 0;
                do { asm volatile("ld.acquire.gpu.global.u32 %0, [%1];" : "=r"(v) : "l"(cp) : "memory"); } while (v < 48u && ++n < SPIN_LIMIT);
            }
            bar_sync(BAR_CTL, 128);
            const bf16* src = kv_src + (size_t)s * SEG_ * (3 * HD_);
#pragma unroll
            for (int j = 0; j < 4; j++) {
                cp_async16(kv_dst0 + buf * KV_BUF + j * (8 * HL * 2), src + (size_t)j * 8 * (3 * HD_));
                cp_async16(kv_dst1 + buf * KV_BUF + j * (8 * HL * 2), src + (size_t)j * 8 * (3 * HD_) + HD_);
            }
            cp_async_commit();
        };
        const float4* acc_src = reinterpret_cast<const float4*>(g_acc) + ct;
        const uint32_t acc_dst = smem_u32(&sm.mem[(ct & 1) * 4][ct >> 1]);
        const uint4* hx_base = reinterpret_cast<const uint4*>(g_hx) + h * 1024;
        const int hx_rq = ct & 63, hx_half = ct >> 6;
        const uint4* hx_src = hx_base + hx_half * 64 + hx_rq;
        const uint32_t hx_col = (hx_rq & 7) * 8, hx_r = hx_rq >> 3;
        const uint32_t hx_dstA = (hx_half == 0 ? smem_u32(&sm.qm[hx_r][0]) : smem_u32(&sm.kall[0][hx_r][0])) + hx_col;
        const uint32_t hx_dstB = smem_u32(&sm.vall[0][hx_r][0]) + hx_col;
        const uint4* hx_probe = hx_base + (lane >> 3) * 256 + ((lane & 7) % 3) * 64 + (lane & 7) * 8 + 3;
        const int pb_r = ct >> 4, pb_pr = ct & 15;
        uint2* pb_dst = g_hx + (h * 1024 + c * 256 + pb_r * 8) * 2 + pb_pr;
        const float* pb_src = &sm.red[pb_pr >> 3][(pb_pr & 7) * 16 + pb_r];
        bf16* pb_k = g_kmem + (size_t)pb_r * HD_ + h * DH_ + c * 32 + pb_pr * 2;
        bf16* pb_v = g_vmem + (size_t)pb_r * HD_ + h * DH_ + c * 32 + pb_pr * 2;
        const uint32_t qa = smem_u32(&sm.qm[lane & 15][(lane >> 4) * 8]);
        const uint32_t kb0 = smem_u32(&sm.kall[0][cw * 8 + (lane & 7)][(lane >> 3) * 8]);
        const uint32_t va0 = smem_u32(&sm.vall[0][(lane & 7) + ((lane >> 4) & 1) * 8][cw * 32 + ((lane >> 3) & 1) * 8]);
        const uint32_t pbaddr = smem_u32(&sm.p[lane & 7][((lane >> 3) & 1) * 8]);
        const uint32_t ob = smem_u32(&sm.om[lane & 7][kh * 64 + (lane >> 3) * 8]);
        float* acc_dst_g = g_acc + (c * 160 + mg * 80 + g) * 8 + 2 * t;

        prefetch_kv(0, 0);
        for (int s = 0; s < NSEG_; s++) {
            const int buf = s & 1;
            const uint32_t flag = s + 1;
            const uint32_t bo = buf * KV_BUF;
            PROF(0);
            if (s == 0) {
                for (int i = ct; i < MEM_ * D_ / 8; i += 128) {
                    int r = i / (D_ / 8), cc = (i % (D_ / 8)) * 8;
                    *reinterpret_cast<uint4*>(&sm.mem[r][cc]) = *reinterpret_cast<const uint4*>(mem0 + r * D_ + cc);
                }
            } else {
                if (ct == 0) {
                    const unsigned* cp = g_cnt + (s - 1) * 32;
                    unsigned v; int n = 0;
                    do { asm volatile("ld.acquire.gpu.global.u32 %0, [%1];" : "=r"(v) : "l"(cp) : "memory"); } while (v < 256u && ++n < SPIN_LIMIT);
                }
                bar_sync(BAR_CTL, 128);
                PROF(1);
                const float4* src = acc_src + (size_t)(s - 1) * (MEM_ * D_ / 4);
                float4 v[10];
#pragma unroll
                for (int j = 0; j < 10; j++)
                    asm volatile("ld.relaxed.gpu.global.v4.f32 {%0,%1,%2,%3}, [%4];" : "=f"(v[j].x), "=f"(v[j].y), "=f"(v[j].z), "=f"(v[j].w) : "l"(src + 128 * j) : "memory");
#pragma unroll
                for (int j = 0; j < 10; j++) {
                    uint32_t lo = pack_bf16(v[j].x, v[j].y), hi = pack_bf16(v[j].z, v[j].w);
                    uint32_t d = acc_dst + j * 128;
                    asm volatile("st.shared.u16 [%0], %1;" ::"r"(d), "h"((uint16_t)(lo & 0xffff)) : "memory");
                    asm volatile("st.shared.u16 [%0], %1;" ::"r"(d + MEMS_LD * 2), "h"((uint16_t)(lo >> 16)) : "memory");
                    asm volatile("st.shared.u16 [%0], %1;" ::"r"(d + MEMS_LD * 4), "h"((uint16_t)(hi & 0xffff)) : "memory");
                    asm volatile("st.shared.u16 [%0], %1;" ::"r"(d + MEMS_LD * 6), "h"((uint16_t)(hi >> 16)) : "memory");
                }
            }
            bar_arrive(BAR_MEM, RT);
            PROF(2);
            bar_sync(BAR_RED, RT);
            PROF(3);
            {
                uint32_t pk0 = pack_bf16(pb_src[0] + pb_src[768], pb_src[8] + pb_src[768 + 8]);
                uint32_t pk1 = pack_bf16(pb_src[256] + pb_src[1024], pb_src[256 + 8] + pb_src[1024 + 8]);
                uint32_t pk2 = pack_bf16(pb_src[512] + pb_src[1280], pb_src[512 + 8] + pb_src[1280 + 8]);
                st_relaxed_v2(pb_dst, pk0, flag);
                st_relaxed_v2(pb_dst + 128, pk1, flag);
                st_relaxed_v2(pb_dst + 256, pk2, flag);
                *reinterpret_cast<uint32_t*>(pb_k + (size_t)s * (MEM_ * HD_)) = pk1;
                *reinterpret_cast<uint32_t*>(pb_v + (size_t)s * (MEM_ * HD_)) = pk2;
            }
            if (s == NSEG_ - 1) break;
            PROF(4);
            if (cw == 0) (void)poll_ll(hx_probe, flag);
            bar_sync(BAR_CTL, 128);
            PROF(5);
            {
                uint4 v[8];
#pragma unroll
                for (int j = 0; j < 4; j++) v[j] = ld_relaxed_v4(hx_src + j * 256);
                if (hx_half == 0) {
#pragma unroll
                    for (int j = 0; j < 4; j++) v[4 + j] = ld_relaxed_v4(hx_src + j * 256 + 128);
                }
#pragma unroll
                for (int j = 0; j < 4; j++) {
                    if (v[j].y != flag || v[j].w != flag) v[j] = poll_ll(hx_src + j * 256, flag);
                    sts64(hx_dstA + j * 64 + (hx_half ? bo : 0), v[j].x, v[j].z);
                }
                if (hx_half == 0) {
#pragma unroll
                    for (int j = 0; j < 4; j++) {
                        if (v[4 + j].y != flag || v[4 + j].w != flag) v[4 + j] = poll_ll(hx_src + j * 256 + 128, flag);
                        sts64(hx_dstB + j * 64 + bo, v[4 + j].x, v[4 + j].z);
                    }
                }
            }
            cp_async_wait<0>();
            bar_sync(BAR_CTL, 128);
            PROF(6);
            {
                uint32_t a[8][4], b[4][4], b2[4][4];
#pragma unroll
                for (int kk = 0; kk < 4; kk++) ldsm_x4(b[kk], kb0 + bo + kk * 64);
                if (cw == 0) {
#pragma unroll
                    for (int kk = 0; kk < 4; kk++) ldsm_x4(b2[kk], kb0 + bo + 32 * HL * 2 + kk * 64);
                }
#pragma unroll
                for (int kk = 0; kk < 8; kk++) ldsm_x4(a[kk], qa + kk * 32);
                float s0[4] = {0.f, 0.f, 0.f, 0.f}, s1[4] = {0.f, 0.f, 0.f, 0.f};
#pragma unroll
                for (int kk = 0; kk < 4; kk++) { mma16816(s0, a[2 * kk], b[kk][0], b[kk][1]); mma16816(s1, a[2 * kk + 1], b[kk][2], b[kk][3]); }
                const float scale = 0.08838834764831845f;
                *reinterpret_cast<float2*>(&sm.sc[g][cw * 8 + 2 * t]) =
                    make_float2(rbf(rbf(s0[0] + s1[0]) * scale), rbf(rbf(s0[1] + s1[1]) * scale));
                if (cw == 0) {
                    float u0[4] = {0.f, 0.f, 0.f, 0.f}, u1[4] = {0.f, 0.f, 0.f, 0.f};
#pragma unroll
                    for (int kk = 0; kk < 4; kk++) { mma16816(u0, a[2 * kk], b2[kk][0], b2[kk][1]); mma16816(u1, a[2 * kk + 1], b2[kk][2], b2[kk][3]); }
                    *reinterpret_cast<float2*>(&sm.sc[g][32 + 2 * t]) =
                        make_float2(rbf(rbf(u0[0] + u1[0]) * scale), rbf(rbf(u0[1] + u1[1]) * scale));
                }
            }
            bar_sync(BAR_CTL, 128);
            {
                float v0 = sm.sc[cw][lane], v1 = (lane < 8) ? sm.sc[cw][32 + lane] : -INFINITY;
                float y0 = sm.sc[cw + 4][lane], y1 = (lane < 8) ? sm.sc[cw + 4][32 + lane] : -INFINITY;
                float mx = fmaxf(v0, v1), my = fmaxf(y0, y1);
#pragma unroll
                for (int o = 16; o; o >>= 1) { mx = fmaxf(mx, __shfl_xor_sync(0xffffffffu, mx, o)); my = fmaxf(my, __shfl_xor_sync(0xffffffffu, my, o)); }
                float e0 = __expf(v0 - mx), e1 = (lane < 8) ? __expf(v1 - mx) : 0.f;
                float f0 = __expf(y0 - my), f1 = (lane < 8) ? __expf(y1 - my) : 0.f;
                float sx = e0 + e1, sy = f0 + f1;
#pragma unroll
                for (int o = 16; o; o >>= 1) { sx += __shfl_xor_sync(0xffffffffu, sx, o); sy += __shfl_xor_sync(0xffffffffu, sy, o); }
                float ix = 1.0f / sx, iy = 1.0f / sy;
                sm.p[cw][lane] = __float2bfloat16_rn(e0 * ix);
                sm.p[cw + 4][lane] = __float2bfloat16_rn(f0 * iy);
                if (lane < 8) { sm.p[cw][32 + lane] = __float2bfloat16_rn(e1 * ix); sm.p[cw + 4][32 + lane] = __float2bfloat16_rn(f1 * iy); }
            }
            bar_sync(BAR_CTL, 128);
            PROF(7);
            {
                uint32_t a[2][3][4], b[3][2];
#pragma unroll
                for (int kt = 0; kt < 3; kt++) {
                    asm volatile("ldmatrix.sync.aligned.m8n8.x2.shared.b16 {%0,%1}, [%2];" : "=r"(b[kt][0]), "=r"(b[kt][1]) : "r"(pbaddr + kt * 32));
                    ldsm_x4_t(a[0][kt], va0 + bo + kt * 16 * HL * 2);
                    ldsm_x4_t(a[1][kt], va0 + bo + kt * 16 * HL * 2 + 32);
                }
#pragma unroll
                for (int m = 0; m < 2; m++) {
                    float o[4] = {0.f, 0.f, 0.f, 0.f};
#pragma unroll
                    for (int kt = 0; kt < 3; kt++) mma16816(o, a[m][kt], b[kt][0], b[kt][1]);
                    int d0 = cw * 32 + m * 16 + g;
                    sm.om[2 * t][d0] = __float2bfloat16_rn(o[0]);
                    sm.om[2 * t + 1][d0] = __float2bfloat16_rn(o[1]);
                    sm.om[2 * t][d0 + 8] = __float2bfloat16_rn(o[2]);
                    sm.om[2 * t + 1][d0 + 8] = __float2bfloat16_rn(o[3]);
                }
            }
            bar_sync(BAR_CTL, 128);
            PROF(8);
            {
                float acc[5][4];
#pragma unroll
                for (int mi = 0; mi < 5; mi++) { acc[mi][0] = acc[mi][1] = acc[mi][2] = acc[mi][3] = 0.f; }
                uint32_t b[2][4];
                ldsm_x4(b[0], ob); ldsm_x4(b[1], ob + 64);
#pragma unroll
                for (int ki = 0; ki < 4; ki++)
#pragma unroll
                    for (int mi = 0; mi < 5; mi++) mma16816(acc[mi], wf[mi * 4 + ki], b[ki >> 1][(ki & 1) * 2], b[ki >> 1][(ki & 1) * 2 + 1]);
                if (kh == 1) {
#pragma unroll
                    for (int mi = 0; mi < 5; mi++)
                        *reinterpret_cast<float4*>(&sm.wred[mg][mi][lane * 4]) = make_float4(acc[mi][0], acc[mi][1], acc[mi][2], acc[mi][3]);
                }
                bar_sync(BAR_WO + mg, 64);
                if (kh == 0) {
                    float* dst = acc_dst_g + (size_t)s * (MEM_ * D_);
#pragma unroll
                    for (int mi = 0; mi < 5; mi++) {
                        float4 o2 = *reinterpret_cast<float4*>(&sm.wred[mg][mi][lane * 4]);
                        asm volatile("red.global.add.v2.f32 [%0], {%1,%2};" ::"l"(dst + mi * 128), "f"(acc[mi][0] + o2.x), "f"(acc[mi][1] + o2.y) : "memory");
                        asm volatile("red.global.add.v2.f32 [%0], {%1,%2};" ::"l"(dst + mi * 128 + 64), "f"(acc[mi][2] + o2.z), "f"(acc[mi][3] + o2.w) : "memory");
                    }
                    __threadfence();
                    __syncwarp();
                    if (lane == 0) atomicAdd(&g_cnt[s * 32], 1u);
                }
            }
            bar_arrive(BAR_GO, RT);
            PROF(9);
            prefetch_kv(s + 1, buf ^ 1);
            PROF(10);
        }
    }
}

__global__ void __launch_bounds__(128)
attn_x_kernel() {
    __shared__ __align__(16) bf16 sq[32][HL], sk[48][HL], sv[48][HL];
    const int s = blockIdx.x >> 5, h = blockIdx.x & 31;
    const int tid = threadIdx.x, lane = tid & 31, w = tid >> 5, g = lane >> 2, t = lane & 3;
    for (int i = tid; i < (32 + 40 + 40) * 16; i += 128) {
        int r = i >> 4, ch = i & 15;
        const bf16* src; bf16* dst;
        if (r < 32) { src = g_qkv + (size_t)(s * SEG_ + r) * (3 * HD_) + h * DH_; dst = sq[r]; }
        else if (r < 72) { int rr = r - 32; dst = sk[rr];
            src = rr < 8 ? g_kmem + ((size_t)s * MEM_ + rr) * HD_ + h * DH_ : g_qkv + (size_t)(s * SEG_ + rr - 8) * (3 * HD_) + HD_ + h * DH_; }
        else { int rr = r - 72; dst = sv[rr];
            src = rr < 8 ? g_vmem + ((size_t)s * MEM_ + rr) * HD_ + h * DH_ : g_qkv + (size_t)(s * SEG_ + rr - 8) * (3 * HD_) + 2 * HD_ + h * DH_; }
        cp_async16(smem_u32(dst + ch * 8), src + ch * 8);
    }
    cp_async_commit();
    for (int i = tid; i < 8 * 16; i += 128) *reinterpret_cast<uint4*>(&sv[40 + (i >> 4)][(i & 15) * 8]) = make_uint4(0, 0, 0, 0);
    cp_async_wait<0>();
    __syncthreads();
    const int rh = w & 1, dhh = w >> 1;
    float sc[5][4];
#pragma unroll
    for (int n = 0; n < 5; n++) sc[n][0] = sc[n][1] = sc[n][2] = sc[n][3] = 0.f;
#pragma unroll
    for (int kk = 0; kk < 8; kk++) {
        uint32_t a[4];
        ldsm_x4(a, smem_u32(&sq[rh * 16 + (lane & 15)][kk * 16 + (lane >> 4) * 8]));
#pragma unroll
        for (int n = 0; n < 5; n++) {
            uint32_t b[2];
            asm volatile("ldmatrix.sync.aligned.m8n8.x2.shared.b16 {%0,%1}, [%2];" : "=r"(b[0]), "=r"(b[1])
                         : "r"(smem_u32(&sk[n * 8 + (lane & 7)][kk * 16 + ((lane >> 3) & 1) * 8])));
            mma16816(sc[n], a, b[0], b[1]);
        }
    }
    const float scale = 0.08838834764831845f;
    float mx[2] = {-INFINITY, -INFINITY};
#pragma unroll
    for (int n = 0; n < 5; n++)
#pragma unroll
        for (int e = 0; e < 4; e++) {
            int row = rh * 16 + g + (e >> 1) * 8, key = n * 8 + 2 * t + (e & 1);
            float v = rbf(rbf(sc[n][e]) * scale);
            if (key > row + MEM_) v = -INFINITY;
            sc[n][e] = v;
            mx[e >> 1] = fmaxf(mx[e >> 1], v);
        }
#pragma unroll
    for (int o = 1; o < 4; o <<= 1) { mx[0] = fmaxf(mx[0], __shfl_xor_sync(0xffffffffu, mx[0], o)); mx[1] = fmaxf(mx[1], __shfl_xor_sync(0xffffffffu, mx[1], o)); }
    float sum[2] = {0.f, 0.f};
#pragma unroll
    for (int n = 0; n < 5; n++)
#pragma unroll
        for (int e = 0; e < 4; e++) { float ev = __expf(sc[n][e] - mx[e >> 1]); sc[n][e] = ev; sum[e >> 1] += ev; }
#pragma unroll
    for (int o = 1; o < 4; o <<= 1) { sum[0] += __shfl_xor_sync(0xffffffffu, sum[0], o); sum[1] += __shfl_xor_sync(0xffffffffu, sum[1], o); }
    float inv[2] = {1.0f / sum[0], 1.0f / sum[1]};
    uint32_t pa[3][4];
#pragma unroll
    for (int kt = 0; kt < 3; kt++) {
        pa[kt][0] = pack_bf16(sc[2 * kt][0] * inv[0], sc[2 * kt][1] * inv[0]);
        pa[kt][1] = pack_bf16(sc[2 * kt][2] * inv[1], sc[2 * kt][3] * inv[1]);
        if (kt < 2) {
            pa[kt][2] = pack_bf16(sc[2 * kt + 1][0] * inv[0], sc[2 * kt + 1][1] * inv[0]);
            pa[kt][3] = pack_bf16(sc[2 * kt + 1][2] * inv[1], sc[2 * kt + 1][3] * inv[1]);
        } else { pa[kt][2] = 0u; pa[kt][3] = 0u; }
    }
#pragma unroll
    for (int n = 0; n < 8; n++) {
        float o[4] = {0.f, 0.f, 0.f, 0.f};
#pragma unroll
        for (int kt = 0; kt < 3; kt++) {
            uint32_t b[2];
            asm volatile("ldmatrix.sync.aligned.m8n8.x2.trans.shared.b16 {%0,%1}, [%2];" : "=r"(b[0]), "=r"(b[1])
                         : "r"(smem_u32(&sv[kt * 16 + (lane & 15)][dhh * 64 + n * 8])));
            mma16816(o, pa[kt], b[0], b[1]);
        }
        int row = s * SEG_ + rh * 16 + g;
        bf16* dst = g_o + (size_t)row * HD_ + h * DH_ + dhh * 64 + n * 8 + 2 * t;
        *reinterpret_cast<uint32_t*>(dst) = pack_bf16(o[0], o[1]);
        *reinterpret_cast<uint32_t*>(dst + 8 * HD_) = pack_bf16(o[2], o[3]);
    }
}

typedef CUresult (*PFN_encodeTiled)(CUtensorMap*, CUtensorMapDataType, cuuint32_t, void*, const cuuint64_t*,
                                    const cuuint64_t*, const cuuint32_t*, const cuuint32_t*, CUtensorMapInterleave,
                                    CUtensorMapSwizzle, CUtensorMapL2promotion, CUtensorMapFloatOOBfill);
static PFN_encodeTiled p_encode = nullptr;

static CUtensorMap make_map(const void* ptr, uint64_t rows, uint64_t cols, uint64_t ld, uint32_t box_rows) {
    CUtensorMap m;
    cuuint64_t dims[2] = {cols, rows};
    cuuint64_t strides[1] = {ld * 2};
    cuuint32_t box[2] = {64, box_rows};
    cuuint32_t es[2] = {1, 1};
    p_encode(&m, CU_TENSOR_MAP_DATA_TYPE_BFLOAT16, 2, const_cast<void*>(ptr), dims, strides, box, es,
             CU_TENSOR_MAP_INTERLEAVE_NONE, CU_TENSOR_MAP_SWIZZLE_128B, CU_TENSOR_MAP_L2_PROMOTION_L2_128B,
             CU_TENSOR_MAP_FLOAT_OOB_FILL_NONE);
    return m;
}

template <int BN, int EPI>
static void launch_gemm(const CUtensorMap& a, const CUtensorMap& b0, const CUtensorMap& b1, const CUtensorMap& b2,
                        int nPerB, int M, int N, int K, EpiParams ep, cudaStream_t st) {
    constexpr int STAGE = 16384 + (BN / 64) * 8192;
    constexpr int NST = (200 * 1024) / STAGE;
    constexpr int SMEM = NST * STAGE + 1024;
    cudaFuncSetAttribute(gemm_kernel<BN, EPI>, cudaFuncAttributeMaxDynamicSharedMemorySize, SMEM);
    dim3 grid((N + BN - 1) / BN, M / 128);
    gemm_kernel<BN, EPI><<<grid, 384, SMEM, st>>>(a, b0, b1, b2, nPerB, N, K, ep);
}

extern "C" void kernel_launch(void* const* d_in, const int* in_sizes, int n_in, void* d_out, int out_size) {
    const bf16* x    = (const bf16*)d_in[0];
    const bf16* mem0 = (const bf16*)d_in[1];
    const bf16* Wq   = (const bf16*)d_in[2];
    const bf16* Wk   = (const bf16*)d_in[3];
    const bf16* Wv   = (const bf16*)d_in[4];
    const bf16* Wo   = (const bf16*)d_in[5];
    const bf16* w_in  = (const bf16*)d_in[8];
    const bf16* w_sp  = (const bf16*)d_in[9];
    const bf16* b_sp  = (const bf16*)d_in[10];
    const bf16* w_out = (const bf16*)d_in[11];
    bf16* out = (bf16*)d_out;
    cudaStream_t st = cudaStreamPerThread;

    if (!p_encode) {
        cudaDriverEntryPointQueryResult qr;
        cudaGetDriverEntryPoint("cuTensorMapEncodeTiled", (void**)&p_encode, cudaEnableDefault, &qr);
    }
    void *p_xn, *p_qkv, *p_z, *p_zg, *p_gate, *p_o, *p_acc, *p_cnt, *p_hx;
    cudaGetSymbolAddress(&p_xn, g_xn); cudaGetSymbolAddress(&p_qkv, g_qkv); cudaGetSymbolAddress(&p_z, g_z);
    cudaGetSymbolAddress(&p_zg, g_zg); cudaGetSymbolAddress(&p_gate, g_gate); cudaGetSymbolAddress(&p_o, g_o);
    cudaGetSymbolAddress(&p_acc, g_acc); cudaGetSymbolAddress(&p_cnt, g_cnt); cudaGetSymbolAddress(&p_hx, g_hx);

    CUtensorMap mA_xn  = make_map(p_xn, S_, D_, D_, 128);
    CUtensorMap mA_wsp = make_map(w_sp, S_, S_, S_, 128);
    CUtensorMap mA_zg  = make_map(p_zg, S_, FH_, FH_, 128);
    CUtensorMap mA_o   = make_map(p_o, S_, HD_, HD_, 128);
    CUtensorMap mB_wq  = make_map(Wq, D_, HD_, HD_, 64);
    CUtensorMap mB_wk  = make_map(Wk, D_, HD_, HD_, 64);
    CUtensorMap mB_wv  = make_map(Wv, D_, HD_, HD_, 64);
    CUtensorMap mB_win = make_map(w_in, D_, F_, F_, 64);
    CUtensorMap mB_z2  = make_map((bf16*)p_z + FH_, S_, FH_, F_, 64);
    CUtensorMap mB_wout = make_map(w_out, FH_, D_, D_, 64);
    CUtensorMap mB_wo  = make_map(Wo, HD_, D_, D_, 64);

    cudaMemsetAsync(p_acc, 0, sizeof(float) * NSEG_ * MEM_ * D_, st);
    cudaMemsetAsync(p_cnt, 0, sizeof(unsigned) * NSEG_ * 32, st);
    void* p_xcnt; cudaGetSymbolAddress(&p_xcnt, g_xcnt);
    cudaMemsetAsync(p_xcnt, 0, sizeof(unsigned) * H_ * NSEG_, st);
    cudaMemsetAsync(p_hx, 0, sizeof(uint2) * H_ * 4 * 256 * 2, st);

    ln_kernel<<<S_ / 8, 256, 0, st>>>(x);
    { EpiParams ep{(bf16*)p_z, F_, nullptr, nullptr}; launch_gemm<128, EPI_GELU>(mA_xn, mB_win, mB_win, mB_win, 1 << 20, S_, F_, D_, ep, st); }
    ln2_kernel<<<S_ / 8, 256, 0, st>>>();
    { EpiParams ep{(bf16*)p_zg, FH_, (const bf16*)p_z, b_sp}; launch_gemm<128, EPI_SP>(mA_wsp, mB_z2, mB_z2, mB_z2, 1 << 20, S_, FH_, S_, ep, st); }
    { EpiParams ep{(bf16*)p_gate, D_, nullptr, nullptr}; launch_gemm<128, EPI_SILU>(mA_zg, mB_wout, mB_wout, mB_wout, 1 << 20, S_, D_, FH_, ep, st); }
    constexpr int RSM = (int)sizeof(RecurSmem) > 16 * 10240 ? (int)sizeof(RecurSmem) : 16 * 10240;
    cudaFuncSetAttribute(recur_kernel, cudaFuncAttributeMaxDynamicSharedMemorySize, RSM);
    recur_kernel<<<128, RT, RSM, st>>>(mem0, Wq, Wk, Wv, Wo);
    attn_x_kernel<<<NSEG_ * H_, 128, 0, st>>>();
    { EpiParams ep{out, D_, x, (const bf16*)p_gate}; launch_gemm<128, EPI_FINAL>(mA_o, mB_wo, mB_wo, mB_wo, 1 << 20, S_, D_, HD_, ep, st); }
}
```

```cpp
#include <cuda_runtime.h>
#include <cuda_bf16.h>
#include <cuda.h>
#include <stdint.h>

typedef __nv_bfloat16 bf16;

constexpr int S_   = 2048;
constexpr int D_   = 640;
constexpr int H_   = 32;
constexpr int DH_  = 128;
constexpr int MEM_ = 8;
constexpr int SEG_ = 32;
constexpr int NSEG_ = S_ / SEG_;
constexpr int HD_  = H_ * DH_;
constexpr int F_   = 1728;
constexpr int FH_  = 864;

__device__ bf16 g_xn[S_ * D_];
__device__ bf16 g_qkv[(size_t)S_ * 3 * HD_];
__device__ bf16 g_z[S_ * F_];
__device__ bf16 g_zg[S_ * FH_];
__device__ bf16 g_gate[S_ * D_];
__device__ bf16 g_kmem[NSEG_ * MEM_ * HD_];
__device__ bf16 g_vmem[NSEG_ * MEM_ * HD_];
__device__ bf16 g_o[(size_t)S_ * HD_];
__device__ float g_acc[NSEG_ * MEM_ * D_];
__device__ unsigned g_cnt[NSEG_ * 32];
__device__ unsigned g_xcnt[H_ * NSEG_];
__device__ uint2 g_hx[H_ * 4 * 256 * 2];

__device__ __forceinline__ uint32_t smem_u32(const void* p) { return (uint32_t)__cvta_generic_to_shared(p); }
__device__ __forceinline__ float bf2f(bf16 v) { return __bfloat162float(v); }
__device__ __forceinline__ float rbf(float v) { return __bfloat162float(__float2bfloat16_rn(v)); }
__device__ __forceinline__ uint32_t pack_bf16(float lo, float hi) {
    __nv_bfloat162 t = __floats2bfloat162_rn(lo, hi);
    return *reinterpret_cast<uint32_t*>(&t);
}
__device__ __forceinline__ float lo_f(uint32_t u) { return __uint_as_float(u << 16); }
__device__ __forceinline__ float hi_f(uint32_t u) { return __uint_as_float(u & 0xffff0000u); }

__device__ __forceinline__ void mbar_init(uint32_t bar, uint32_t cnt) {
    asm volatile("mbarrier.init.shared.b64 [%0], %1;" ::"r"(bar), "r"(cnt));
}
__device__ __forceinline__ void mbar_expect_tx(uint32_t bar, uint32_t bytes) {
    asm volatile("mbarrier.arrive.expect_tx.shared.b64 _, [%0], %1;" ::"r"(bar), "r"(bytes) : "memory");
}
__device__ __forceinline__ void mbar_arrive(uint32_t bar) {
    asm volatile("mbarrier.arrive.shared.b64 _, [%0];" ::"r"(bar) : "memory");
}
__device__ __forceinline__ void mbar_wait(uint32_t bar, uint32_t parity) {
    asm volatile(
        "{\n .reg .pred p;\n"
        "WAIT_%=:\n"
        " mbarrier.try_wait.parity.shared.b64 p, [%0], %1;\n"
        " @p bra DONE_%=;\n"
        " bra WAIT_%=;\n"
        "DONE_%=:\n}\n" ::"r"(bar), "r"(parity) : "memory");
}
__device__ __forceinline__ void tma_load_2d(uint32_t dst, const CUtensorMap* tm, uint32_t bar, int c0, int c1) {
    asm volatile(
        "cp.async.bulk.tensor.2d.shared::cluster.global.mbarrier::complete_tx::bytes [%0], [%1, {%3, %4}], [%2];"
        ::"r"(dst), "l"(tm), "r"(bar), "r"(c0), "r"(c1) : "memory");
}
__device__ __forceinline__ void wgmma_fence() { asm volatile("wgmma.fence.sync.aligned;" ::: "memory"); }
__device__ __forceinline__ void wgmma_commit() { asm volatile("wgmma.commit_group.sync.aligned;" ::: "memory"); }
template <int N> __device__ __forceinline__ void wgmma_wait() { asm volatile("wgmma.wait_group.sync.aligned %0;" ::"n"(N) : "memory"); }

__device__ __forceinline__ uint64_t make_desc(uint32_t addr, uint32_t lbo, uint32_t sbo) {
    return (uint64_t)((addr & 0x3FFFF) >> 4) | ((uint64_t)(lbo >> 4) << 16) | ((uint64_t)(sbo >> 4) << 32) | (1ull << 62);
}

template <int N> struct Wgmma;
template <> struct Wgmma<128> {
    static __device__ __forceinline__ void mma(float* d, uint64_t da, uint64_t db, int sd) {
        asm volatile(
            "{\n.reg .pred p;\nsetp.ne.b32 p, %66, 0;\n"
            "wgmma.mma_async.sync.aligned.m64n128k16.f32.bf16.bf16 "
            "{%0,%1,%2,%3,%4,%5,%6,%7,%8,%9,%10,%11,%12,%13,%14,%15,"
            "%16,%17,%18,%19,%20,%21,%22,%23,%24,%25,%26,%27,%28,%29,%30,%31,"
            "%32,%33,%34,%35,%36,%37,%38,%39,%40,%41,%42,%43,%44,%45,%46,%47,"
            "%48,%49,%50,%51,%52,%53,%54,%55,%56,%57,%58,%59,%60,%61,%62,%63},"
            "%64,%65,p,1,1,0,1;\n}\n"
            : "+f"(d[0]), "+f"(d[1]), "+f"(d[2]), "+f"(d[3]), "+f"(d[4]), "+f"(d[5]), "+f"(d[6]), "+f"(d[7]),
              "+f"(d[8]), "+f"(d[9]), "+f"(d[10]), "+f"(d[11]), "+f"(d[12]), "+f"(d[13]), "+f"(d[14]), "+f"(d[15]),
              "+f"(d[16]), "+f"(d[17]), "+f"(d[18]), "+f"(d[19]), "+f"(d[20]), "+f"(d[21]), "+f"(d[22]), "+f"(d[23]),
              "+f"(d[24]), "+f"(d[25]), "+f"(d[26]), "+f"(d[27]), "+f"(d[28]), "+f"(d[29]), "+f"(d[30]), "+f"(d[31]),
              "+f"(d[32]), "+f"(d[33]), "+f"(d[34]), "+f"(d[35]), "+f"(d[36]), "+f"(d[37]), "+f"(d[38]), "+f"(d[39]),
              "+f"(d[40]), "+f"(d[41]), "+f"(d[42]), "+f"(d[43]), "+f"(d[44]), "+f"(d[45]), "+f"(d[46]), "+f"(d[47]),
              "+f"(d[48]), "+f"(d[49]), "+f"(d[50]), "+f"(d[51]), "+f"(d[52]), "+f"(d[53]), "+f"(d[54]), "+f"(d[55]),
              "+f"(d[56]), "+f"(d[57]), "+f"(d[58]), "+f"(d[59]), "+f"(d[60]), "+f"(d[61]), "+f"(d[62]), "+f"(d[63])
            : "l"(da), "l"(db), "r"(sd));
    }
};
template <> struct Wgmma<192> {
    static __device__ __forceinline__ void mma(float* d, uint64_t da, uint64_t db, int sd) {
        asm volatile(
            "{\n.reg .pred p;\nsetp.ne.b32 p, %98, 0;\n"
            "wgmma.mma_async.sync.aligned.m64n192k16.f32.bf16.bf16 "
            "{%0,%1,%2,%3,%4,%5,%6,%7,%8,%9,%10,%11,%12,%13,%14,%15,"
            "%16,%17,%18,%19,%20,%21,%22,%23,%24,%25,%26,%27,%28,%29,%30,%31,"
            "%32,%33,%34,%35,%36,%37,%38,%39,%40,%41,%42,%43,%44,%45,%46,%47,"
            "%48,%49,%50,%51,%52,%53,%54,%55,%56,%57,%58,%59,%60,%61,%62,%63,"
            "%64,%65,%66,%67,%68,%69,%70,%71,%72,%73,%74,%75,%76,%77,%78,%79,"
            "%80,%81,%82,%83,%84,%85,%86,%87,%88,%89,%90,%91,%92,%93,%94,%95},"
            "%96,%97,p,1,1,0,1;\n}\n"
            : "+f"(d[0]), "+f"(d[1]), "+f"(d[2]), "+f"(d[3]), "+f"(d[4]), "+f"(d[5]), "+f"(d[6]), "+f"(d[7]),
              "+f"(d[8]), "+f"(d[9]), "+f"(d[10]), "+f"(d[11]), "+f"(d[12]), "+f"(d[13]), "+f"(d[14]), "+f"(d[15]),
              "+f"(d[16]), "+f"(d[17]), "+f"(d[18]), "+f"(d[19]), "+f"(d[20]), "+f"(d[21]), "+f"(d[22]), "+f"(d[23]),
              "+f"(d[24]), "+f"(d[25]), "+f"(d[26]), "+f"(d[27]), "+f"(d[28]), "+f"(d[29]), "+f"(d[30]), "+f"(d[31]),
              "+f"(d[32]), "+f"(d[33]), "+f"(d[34]), "+f"(d[35]), "+f"(d[36]), "+f"(d[37]), "+f"(d[38]), "+f"(d[39]),
              "+f"(d[40]), "+f"(d[41]), "+f"(d[42]), "+f"(d[43]), "+f"(d[44]), "+f"(d[45]), "+f"(d[46]), "+f"(d[47]),
              "+f"(d[48]), "+f"(d[49]), "+f"(d[50]), "+f"(d[51]), "+f"(d[52]), "+f"(d[53]), "+f"(d[54]), "+f"(d[55]),
              "+f"(d[56]), "+f"(d[57]), "+f"(d[58]), "+f"(d[59]), "+f"(d[60]), "+f"(d[61]), "+f"(d[62]), "+f"(d[63]),
              "+f"(d[64]), "+f"(d[65]), "+f"(d[66]), "+f"(d[67]), "+f"(d[68]), "+f"(d[69]), "+f"(d[70]), "+f"(d[71]),
              "+f"(d[72]), "+f"(d[73]), "+f"(d[74]), "+f"(d[75]), "+f"(d[76]), "+f"(d[77]), "+f"(d[78]), "+f"(d[79]),
              "+f"(d[80]), "+f"(d[81]), "+f"(d[82]), "+f"(d[83]), "+f"(d[84]), "+f"(d[85]), "+f"(d[86]), "+f"(d[87]),
              "+f"(d[88]), "+f"(d[89]), "+f"(d[90]), "+f"(d[91]), "+f"(d[92]), "+f"(d[93]), "+f"(d[94]), "+f"(d[95])
            : "l"(da), "l"(db), "r"(sd));
    }
};

template <> struct Wgmma<256> {
    static __device__ __forceinline__ void mma(float* d, uint64_t da, uint64_t db, int sd) {
        asm volatile(
            "{\n.reg .pred p;\nsetp.ne.b32 p, %130, 0;\n"
            "wgmma.mma_async.sync.aligned.m64n256k16.f32.bf16.bf16 "
            "{%0,%1,%2,%3,%4,%5,%6,%7,%8,%9,%10,%11,%12,%13,%14,%15,%16,%17,%18,%19,%20,%21,%22,%23,%24,%25,%26,%27,%28,%29,%30,%31,%32,%33,%34,%35,%36,%37,%38,%39,%40,%41,%42,%43,%44,%45,%46,%47,%48,%49,%50,%51,%52,%53,%54,%55,%56,%57,%58,%59,%60,%61,%62,%63,%64,%65,%66,%67,%68,%69,%70,%71,%72,%73,%74,%75,%76,%77,%78,%79,%80,%81,%82,%83,%84,%85,%86,%87,%88,%89,%90,%91,%92,%93,%94,%95,%96,%97,%98,%99,%100,%101,%102,%103,%104,%105,%106,%107,%108,%109,%110,%111,%112,%113,%114,%115,%116,%117,%118,%119,%120,%121,%122,%123,%124,%125,%126,%127},"
            "%128,%129,p,1,1,0,1;\n}\n"
            : "+f"(d[0]), "+f"(d[1]), "+f"(d[2]), "+f"(d[3]), "+f"(d[4]), "+f"(d[5]), "+f"(d[6]), "+f"(d[7]), "+f"(d[8]), "+f"(d[9]), "+f"(d[10]), "+f"(d[11]), "+f"(d[12]), "+f"(d[13]), "+f"(d[14]), "+f"(d[15]), "+f"(d[16]), "+f"(d[17]), "+f"(d[18]), "+f"(d[19]), "+f"(d[20]), "+f"(d[21]), "+f"(d[22]), "+f"(d[23]), "+f"(d[24]), "+f"(d[25]), "+f"(d[26]), "+f"(d[27]), "+f"(d[28]), "+f"(d[29]), "+f"(d[30]), "+f"(d[31]), "+f"(d[32]), "+f"(d[33]), "+f"(d[34]), "+f"(d[35]), "+f"(d[36]), "+f"(d[37]), "+f"(d[38]), "+f"(d[39]), "+f"(d[40]), "+f"(d[41]), "+f"(d[42]), "+f"(d[43]), "+f"(d[44]), "+f"(d[45]), "+f"(d[46]), "+f"(d[47]), "+f"(d[48]), "+f"(d[49]), "+f"(d[50]), "+f"(d[51]), "+f"(d[52]), "+f"(d[53]), "+f"(d[54]), "+f"(d[55]), "+f"(d[56]), "+f"(d[57]), "+f"(d[58]), "+f"(d[59]), "+f"(d[60]), "+f"(d[61]), "+f"(d[62]), "+f"(d[63]), "+f"(d[64]), "+f"(d[65]), "+f"(d[66]), "+f"(d[67]), "+f"(d[68]), "+f"(d[69]), "+f"(d[70]), "+f"(d[71]), "+f"(d[72]), "+f"(d[73]), "+f"(d[74]), "+f"(d[75]), "+f"(d[76]), "+f"(d[77]), "+f"(d[78]), "+f"(d[79]), "+f"(d[80]), "+f"(d[81]), "+f"(d[82]), "+f"(d[83]), "+f"(d[84]), "+f"(d[85]), "+f"(d[86]), "+f"(d[87]), "+f"(d[88]), "+f"(d[89]), "+f"(d[90]), "+f"(d[91]), "+f"(d[92]), "+f"(d[93]), "+f"(d[94]), "+f"(d[95]), "+f"(d[96]), "+f"(d[97]), "+f"(d[98]), "+f"(d[99]), "+f"(d[100]), "+f"(d[101]), "+f"(d[102]), "+f"(d[103]), "+f"(d[104]), "+f"(d[105]), "+f"(d[106]), "+f"(d[107]), "+f"(d[108]), "+f"(d[109]), "+f"(d[110]), "+f"(d[111]), "+f"(d[112]), "+f"(d[113]), "+f"(d[114]), "+f"(d[115]), "+f"(d[116]), "+f"(d[117]), "+f"(d[118]), "+f"(d[119]), "+f"(d[120]), "+f"(d[121]), "+f"(d[122]), "+f"(d[123]), "+f"(d[124]), "+f"(d[125]), "+f"(d[126]), "+f"(d[127])
            : "l"(da), "l"(db), "r"(sd));
    }
};
template <int W>
__device__ __forceinline__ void ln_row(const bf16* __restrict__ src, bf16* __restrict__ dst, int lane) {
    constexpr int NP = W / 64;
    constexpr int REM = (W / 2) % 32;
    uint32_t v[NP + 1];
    const uint32_t* s32 = reinterpret_cast<const uint32_t*>(src);
    float sum = 0.f;
#pragma unroll
    for (int i = 0; i < NP; i++) { v[i] = s32[i * 32 + lane]; sum += lo_f(v[i]) + hi_f(v[i]); }
    if (REM) { v[NP] = (lane < REM) ? s32[NP * 32 + lane] : 0u; if (lane < REM) sum += lo_f(v[NP]) + hi_f(v[NP]); }
#pragma unroll
    for (int o = 16; o; o >>= 1) sum += __shfl_xor_sync(0xffffffffu, sum, o);
    float mean = sum * (1.0f / W);
    float vs = 0.f;
#pragma unroll
    for (int i = 0; i < NP; i++) { float a = lo_f(v[i]) - mean, b = hi_f(v[i]) - mean; vs += a * a + b * b; }
    if (REM && lane < REM) { float a = lo_f(v[NP]) - mean, b = hi_f(v[NP]) - mean; vs += a * a + b * b; }
#pragma unroll
    for (int o = 16; o; o >>= 1) vs += __shfl_xor_sync(0xffffffffu, vs, o);
    float var = rbf(vs * (1.0f / W));
    float mb = rbf(mean);
    float den = rbf(sqrtf(rbf(var + 1e-5f)));
    uint32_t* d32 = reinterpret_cast<uint32_t*>(dst);
#pragma unroll
    for (int i = 0; i < NP; i++) d32[i * 32 + lane] = pack_bf16(rbf(lo_f(v[i]) - mb) / den, rbf(hi_f(v[i]) - mb) / den);
    if (REM && lane < REM) d32[NP * 32 + lane] = pack_bf16(rbf(lo_f(v[NP]) - mb) / den, rbf(hi_f(v[NP]) - mb) / den);
}

__global__ void ln_kernel(const bf16* __restrict__ x) {
    int row = blockIdx.x * 8 + (threadIdx.x >> 5);
    ln_row<D_>(x + (size_t)row * D_, g_xn + (size_t)row * D_, threadIdx.x & 31);
}
__global__ void ln2_kernel() {
    int row = blockIdx.x * 8 + (threadIdx.x >> 5);
    bf16* p = g_z + (size_t)row * F_ + FH_;
    ln_row<FH_>(p, p, threadIdx.x & 31);
}

enum { EPI_STORE = 0, EPI_GELU = 1, EPI_SP = 2, EPI_SILU = 3, EPI_FINAL = 4 };
struct EpiParams {
    bf16* out; int ldo;
    const bf16* aux0;
    const bf16* aux1;
};

__device__ __forceinline__ float gelu_tanh_f(float x) {
    const float k0 = 0.7978845608028654f, k1 = 0.044715f;
    float inner = k0 * (x + k1 * x * x * x);
    return 0.5f * x * (1.0f + tanhf(inner));
}
__device__ __forceinline__ float silu_f(float x) { return x / (1.0f + expf(-x)); }

template <int BN, int EPI>
__global__ void __launch_bounds__(384, 1)
gemm_kernel(const __grid_constant__ CUtensorMap tmA, const __grid_constant__ CUtensorMap tmB0,
            const __grid_constant__ CUtensorMap tmB1, const __grid_constant__ CUtensorMap tmB2,
            int nPerB, int N, int K, EpiParams ep) {
    constexpr int BM = 128, BK = 64;
    constexpr int A_BYTES = BM * BK * 2;
    constexpr int B_BYTES = (BN / 64) * 8192;
    constexpr int STAGE = A_BYTES + B_BYTES;
    constexpr int NST = (200 * 1024) / STAGE;
    constexpr int OLD = BN + 8;
    extern __shared__ __align__(1024) uint8_t smem_raw[];
    uint8_t* smem = (uint8_t*)(((uintptr_t)smem_raw + 1023) & ~(uintptr_t)1023);
    __shared__ __align__(8) uint64_t full_bar[NST], empty_bar[NST];

    const int tid = threadIdx.x, wg = tid >> 7;
    const int m0 = blockIdx.y * BM, n0 = blockIdx.x * BN;
    const int nk = (K + BK - 1) / BK;

    if (tid == 0) {
        for (int i = 0; i < NST; i++) { mbar_init(smem_u32(&full_bar[i]), 1); mbar_init(smem_u32(&empty_bar[i]), 2); }
        asm volatile("fence.mbarrier_init.release.cluster;" ::: "memory");
    }
    __syncthreads();

    if (wg == 0) {
        if (tid == 0) {
            const int bsel = n0 / nPerB;
            const CUtensorMap* tmB = bsel == 0 ? &tmB0 : (bsel == 1 ? &tmB1 : &tmB2);
            const int nb = n0 - bsel * nPerB;
            for (int kt = 0; kt < nk; kt++) {
                int st = kt % NST; uint32_t ph = (kt / NST) & 1;
                mbar_wait(smem_u32(&empty_bar[st]), ph ^ 1);
                uint32_t fb = smem_u32(&full_bar[st]);
                mbar_expect_tx(fb, STAGE);
                uint32_t sa = smem_u32(smem + st * STAGE);
                tma_load_2d(sa, &tmA, fb, kt * BK, m0);
#pragma unroll
                for (int j = 0; j < BN / 64; j++) tma_load_2d(sa + A_BYTES + j * 8192, tmB, fb, nb + j * 64, kt * BK);
            }
        }
    } else {
        const int cw = wg - 1;
        float acc[BN / 2];
        for (int kt = 0; kt < nk; kt++) {
            int st = kt % NST; uint32_t ph = (kt / NST) & 1;
            mbar_wait(smem_u32(&full_bar[st]), ph);
            uint32_t sa = smem_u32(smem + st * STAGE) + cw * 64 * 128;
            uint32_t sb = smem_u32(smem + st * STAGE) + A_BYTES;
            wgmma_fence();
#pragma unroll
            for (int k = 0; k < BK / 16; k++) {
                uint64_t da = make_desc(sa + k * 32, 16, 1024);
                uint64_t db = make_desc(sb + k * 2048, 8192, 1024);
                Wgmma<BN>::mma(acc, da, db, (kt | k) != 0);
            }
            wgmma_commit();
            wgmma_wait<1>();
            if (kt > 0 && (tid & 127) == 0) mbar_arrive(smem_u32(&empty_bar[(kt - 1) % NST]));
        }
        wgmma_wait<0>();
        asm volatile("bar.sync 1, 256;" ::: "memory");
        const int lane = tid & 31, wi = (tid >> 5) & 3, g = lane >> 2, t = lane & 3;
        bf16* stg = reinterpret_cast<bf16*>(smem) + cw * 64 * OLD;
#pragma unroll
        for (int j = 0; j < BN / 8; j++) {
            *reinterpret_cast<uint32_t*>(&stg[(wi * 16 + g) * OLD + j * 8 + 2 * t]) = pack_bf16(acc[4 * j], acc[4 * j + 1]);
            *reinterpret_cast<uint32_t*>(&stg[(wi * 16 + g + 8) * OLD + j * 8 + 2 * t]) = pack_bf16(acc[4 * j + 2], acc[4 * j + 3]);
        }
        asm volatile("bar.sync %0, 128;" ::"r"(2 + cw) : "memory");
        constexpr int CPR = BN / 8;
        const int ltid = tid & 127;
#pragma unroll 4
        for (int i = ltid; i < 64 * CPR; i += 128) {
            int r = i / CPR, ch = i % CPR;
            int row = m0 + cw * 64 + r, col = n0 + ch * 8;
            if (col >= N) continue;
            uint4 v = *reinterpret_cast<const uint4*>(&stg[r * OLD + ch * 8]);
            uint32_t u[4] = {v.x, v.y, v.z, v.w}, o[4];
            if (EPI == EPI_STORE) {
#pragma unroll
                for (int q = 0; q < 4; q++) o[q] = u[q];
            } else if (EPI == EPI_GELU) {
#pragma unroll
                for (int q = 0; q < 4; q++) o[q] = pack_bf16(gelu_tanh_f(lo_f(u[q])), gelu_tanh_f(hi_f(u[q])));
            } else if (EPI == EPI_SP) {
                float bb = bf2f(ep.aux1[row]);
                uint4 z = *reinterpret_cast<const uint4*>(ep.aux0 + (size_t)row * F_ + col);
                uint32_t zz[4] = {z.x, z.y, z.z, z.w};
#pragma unroll
                for (int q = 0; q < 4; q++) o[q] = pack_bf16(lo_f(zz[q]) * rbf(lo_f(u[q]) + bb), hi_f(zz[q]) * rbf(hi_f(u[q]) + bb));
            } else if (EPI == EPI_SILU) {
#pragma unroll
                for (int q = 0; q < 4; q++) o[q] = pack_bf16(silu_f(lo_f(u[q])), silu_f(hi_f(u[q])));
            } else {
                uint4 xv = *reinterpret_cast<const uint4*>(ep.aux0 + (size_t)row * D_ + col);
                uint4 gv = *reinterpret_cast<const uint4*>(ep.aux1 + (size_t)row * D_ + col);
                uint32_t xx[4] = {xv.x, xv.y, xv.z, xv.w}, gg[4] = {gv.x, gv.y, gv.z, gv.w};
#pragma unroll
                for (int q = 0; q < 4; q++)
                    o[q] = pack_bf16(lo_f(xx[q]) + rbf(lo_f(u[q]) * lo_f(gg[q])), hi_f(xx[q]) + rbf(hi_f(u[q]) * hi_f(gg[q])));
            }
            *reinterpret_cast<uint4*>(ep.out + (size_t)row * ep.ldo + col) = make_uint4(o[0], o[1], o[2], o[3]);
        }
    }
}

__device__ __forceinline__ void mma16816(float* c, const uint32_t* a, uint32_t b0, uint32_t b1) {
    asm volatile(
        "mma.sync.aligned.m16n8k16.row.col.f32.bf16.bf16.f32 {%0,%1,%2,%3}, {%4,%5,%6,%7}, {%8,%9}, {%0,%1,%2,%3};"
        : "+f"(c[0]), "+f"(c[1]), "+f"(c[2]), "+f"(c[3])
        : "r"(a[0]), "r"(a[1]), "r"(a[2]), "r"(a[3]), "r"(b0), "r"(b1));
}
__device__ __forceinline__ void ldsm_x4(uint32_t* r, uint32_t addr) {
    asm volatile("ldmatrix.sync.aligned.m8n8.x4.shared.b16 {%0,%1,%2,%3}, [%4];"
                 : "=r"(r[0]), "=r"(r[1]), "=r"(r[2]), "=r"(r[3]) : "r"(addr));
}
__device__ __forceinline__ void ldsm_x4_t(uint32_t* r, uint32_t addr) {
    asm volatile("ldmatrix.sync.aligned.m8n8.x4.trans.shared.b16 {%0,%1,%2,%3}, [%4];"
                 : "=r"(r[0]), "=r"(r[1]), "=r"(r[2]), "=r"(r[3]) : "r"(addr));
}
__device__ __forceinline__ uint4 ld_relaxed_v4(const void* p) {
    uint4 v;
    asm volatile("ld.relaxed.gpu.global.v4.u32 {%0,%1,%2,%3}, [%4];" : "=r"(v.x), "=r"(v.y), "=r"(v.z), "=r"(v.w) : "l"(p) : "memory");
    return v;
}
__device__ __forceinline__ void st_relaxed_v4(void* p, uint32_t a, uint32_t b, uint32_t c, uint32_t d) {
    asm volatile("st.relaxed.gpu.global.v4.u32 [%0], {%1,%2,%3,%4};" ::"l"(p), "r"(a), "r"(b), "r"(c), "r"(d) : "memory");
}
__device__ __forceinline__ void st_relaxed_v2(void* p, uint32_t a, uint32_t b) {
    asm volatile("st.relaxed.gpu.global.v2.u32 [%0], {%1,%2};" ::"l"(p), "r"(a), "r"(b) : "memory");
}
__device__ __forceinline__ void cp_async16(uint32_t dst, const void* src) {
    asm volatile("cp.async.cg.shared.global [%0], [%1], 16;" ::"r"(dst), "l"(src) : "memory");
}
__device__ __forceinline__ void cp_async_commit() { asm volatile("cp.async.commit_group;" ::: "memory"); }
template <int N> __device__ __forceinline__ void cp_async_wait() { asm volatile("cp.async.wait_group %0;" ::"n"(N) : "memory"); }

#define PROF(i) do {} while (0)
constexpr int SPIN_LIMIT = 4000000;

__device__ __forceinline__ uint4 poll_ll(const void* p, uint32_t flag) {
    uint4 v = ld_relaxed_v4(p);
    int n = 0;
    while ((v.y != flag || v.w != flag) && ++n < SPIN_LIMIT) {
        v = ld_relaxed_v4(p);
    }
    return v;
}

constexpr int RT = 512;
constexpr int MEMS_LD = D_ + 8;
constexpr int HL = DH_ + 8;
struct RecurSmem {
    bf16 mem[MEM_][MEMS_LD];
    bf16 kall[2][48][HL];
    bf16 vall[2][48][HL];
    bf16 qm[16][HL];
    float sc[MEM_][40];
    bf16 p[MEM_][48 + 8];
    bf16 om[MEM_][HL];
    float red[12][16 * 8];
    float wred[2][5][16 * 8];
    bf16 xs[SEG_][MEMS_LD];
    float redx[6][4][16 * 8];
    bf16 xo[SEG_][96 + 8];
};

__device__ __forceinline__ void bar_sync(int id, int n) { asm volatile("bar.sync %0, %1;" ::"r"(id), "r"(n) : "memory"); }
__device__ __forceinline__ void bar_arrive(int id, int n) { asm volatile("bar.arrive %0, %1;" ::"r"(id), "r"(n) : "memory"); }
__device__ __forceinline__ void sts64(uint32_t a, uint32_t x, uint32_t y) { asm volatile("st.shared.v2.u32 [%0], {%1,%2};" ::"r"(a), "r"(x), "r"(y) : "memory"); }
__device__ __forceinline__ uint32_t ldg_u16x2(const bf16* p0, const bf16* p1) {
    return (uint32_t)*(const uint16_t*)p0 | ((uint32_t)*(const uint16_t*)p1 << 16);
}
enum { BAR_MEM = 1, BAR_RED = 2, BAR_CTL = 3, BAR_WO = 4, BAR_INIT = 6, BAR_X = 7, BAR_GO = 8 };

__global__ void __launch_bounds__(RT, 1)
recur_kernel(const bf16* __restrict__ mem0, const bf16* __restrict__ Wq, const bf16* __restrict__ Wk,
             const bf16* __restrict__ Wv, const bf16* __restrict__ Wo) {
    extern __shared__ __align__(16) uint8_t smem_raw[];
    RecurSmem& sm = *reinterpret_cast<RecurSmem*>(smem_raw);
    const int tid = threadIdx.x, lane = tid & 31, w = tid >> 5;
    const int g = lane >> 2, t = lane & 3;
    const int h = blockIdx.x >> 2, c = blockIdx.x & 3;

    if (w < 12) {
        asm volatile("setmaxnreg.dec.sync.aligned.u32 112;");
        uint32_t wf[20][4];
        const int mt = w % 6, kh = w / 6;
        {
            const bf16* W = (mt < 2) ? Wq : (mt < 4 ? Wk : Wv);
            int f0 = h * DH_ + c * 32 + (mt & 1) * 16;
            uint32_t stg = smem_u32(smem_raw) + w * 10240;
#pragma unroll 4
            for (int i = lane; i < 640; i += 32)
                cp_async16(stg + i * 16, W + (size_t)(kh * 320 + (i >> 1)) * HD_ + f0 + (i & 1) * 8);
            cp_async_commit(); cp_async_wait<0>(); __syncwarp();
            uint32_t la = stg + ((lane & 7) + ((lane >> 4) & 1) * 8) * 32 + ((lane >> 3) & 1) * 16;
#pragma unroll
            for (int i = 0; i < 20; i++) ldsm_x4_t(wf[i], la + i * 512);
        }
        bar_sync(BAR_INIT, RT);
        const uint32_t base = smem_u32(&sm.mem[lane & 7][kh * 320 + (lane >> 3) * 8]);
        const uint32_t rp = smem_u32(&sm.red[w][g * 8 + 2 * t]);
        const uint32_t xbase = smem_u32(&sm.xs[lane & 7][kh * 320 + (lane >> 3) * 8]);
        const uint32_t rxp = smem_u32(&sm.redx[mt][0][lane * 4]);
        auto load_x = [&](int seg) {
            for (int i = tid; i < SEG_ * (D_ / 8); i += 384) {
                int r = i / (D_ / 8), ch = i % (D_ / 8);
                cp_async16(smem_u32(&sm.xs[r][ch * 8]), g_xn + (size_t)(seg * SEG_ + r) * D_ + ch * 8);
            }
            cp_async_commit();
        };
        float acc[4][4];
        auto xhalf = [&](int n0) {
#pragma unroll
            for (int nt = 0; nt < 2; nt++) { acc[n0 + nt][0] = acc[n0 + nt][1] = acc[n0 + nt][2] = acc[n0 + nt][3] = 0.f; }
#pragma unroll
            for (int i = 0; i < 10; i++) {
#pragma unroll
                for (int nt = 0; nt < 2; nt++) {
                    uint32_t b[4];
                    ldsm_x4(b, xbase + (n0 + nt) * (8 * MEMS_LD * 2) + i * 64);
                    mma16816(acc[n0 + nt], wf[2 * i], b[0], b[1]);
                    mma16816(acc[n0 + nt], wf[2 * i + 1], b[2], b[3]);
                }
            }
        };
        auto xworkA = [&]() {
            cp_async_wait<0>();
            bar_sync(BAR_X, 384);
            xhalf(0);
        };
        auto xwork = [&](int seg) {
            xhalf(2);
            if (kh == 1) {
#pragma unroll
                for (int nt = 0; nt < 4; nt++)
                    asm volatile("st.shared.v4.f32 [%0], {%1,%2,%3,%4};" ::"r"(rxp + nt * 512), "f"(acc[nt][0]), "f"(acc[nt][1]), "f"(acc[nt][2]), "f"(acc[nt][3]) : "memory");
            }
            bar_sync(BAR_X, 384);
            if (seg + 1 < NSEG_) load_x(seg + 1);
            if (kh == 0) {
#pragma unroll
                for (int nt = 0; nt < 4; nt++) {
                    float4 o;
                    asm volatile("ld.shared.v4.f32 {%0,%1,%2,%3}, [%4];" : "=f"(o.x), "=f"(o.y), "=f"(o.z), "=f"(o.w) : "r"(rxp + nt * 512) : "memory");
                    bf16* d = &sm.xo[nt * 8 + 2 * t][mt * 16 + g];
                    d[0] = __float2bfloat16_rn(acc[nt][0] + o.x);
                    d[104] = __float2bfloat16_rn(acc[nt][1] + o.y);
                    d[8] = __float2bfloat16_rn(acc[nt][2] + o.z);
                    d[104 + 8] = __float2bfloat16_rn(acc[nt][3] + o.w);
                }
            }
            bar_sync(BAR_X, 384);
            {
                int r = tid / 12, ch = tid % 12;
                uint4 v = *reinterpret_cast<const uint4*>(&sm.xo[r][ch * 8]);
                *reinterpret_cast<uint4*>(g_qkv + (size_t)(seg * SEG_ + r) * (3 * HD_) + (ch >> 2) * HD_ + h * DH_ + c * 32 + (ch & 3) * 8) = v;
            }
        };
        auto xsignal = [&](int seg) {
            __threadfence();
            __syncwarp();
            if (lane == 0) atomicAdd(&g_xcnt[h * NSEG_ + seg], 1u);
        };
        load_x(0);
        xworkA(); xwork(0); xsignal(0);
        xworkA(); xwork(1); xsignal(1);
        for (int s = 0; s < NSEG_; s++) {
            bar_sync(BAR_MEM, RT);
            float a0[4] = {0.f, 0.f, 0.f, 0.f}, a1[4] = {0.f, 0.f, 0.f, 0.f};
#pragma unroll
            for (int i = 0; i < 10; i++) {
                uint32_t b[4];
                ldsm_x4(b, base + i * 64);
                mma16816(a0, wf[2 * i], b[0], b[1]);
                mma16816(a1, wf[2 * i + 1], b[2], b[3]);
            }
            sts64(rp, __float_as_uint(a0[0] + a1[0]), __float_as_uint(a0[1] + a1[1]));
            sts64(rp + 256, __float_as_uint(a0[2] + a1[2]), __float_as_uint(a0[3] + a1[3]));
            bar_arrive(BAR_RED, RT);
            if (s + 2 < NSEG_) xworkA();
            if (s >= 1 && s + 1 < NSEG_) xsignal(s + 1);
            if (s + 1 < NSEG_) bar_sync(BAR_GO, RT);
            if (s + 2 < NSEG_) xwork(s + 2);
        }
    } else {
        asm volatile("setmaxnreg.inc.sync.aligned.u32 176;");
        const int ct = tid - 384, cw = w - 12;
        const int mg = cw >> 1, kh = cw & 1;
        uint32_t wf[20][4];
        {
            uint32_t stg = smem_u32(smem_raw) + 12 * 10240 + cw * 10240;
#pragma unroll 4
            for (int i = lane; i < 640; i += 32) {
                int r = i / 10, ch = i % 10;
                cp_async16(stg + r * 160 + ch * 16, Wo + (size_t)(h * DH_ + kh * 64 + r) * D_ + c * 160 + mg * 80 + ch * 8);
            }
            cp_async_commit(); cp_async_wait<0>(); __syncwarp();
            uint32_t la = stg + ((lane & 7) + ((lane >> 4) & 1) * 8) * 160 + ((lane >> 3) & 1) * 16;
#pragma unroll
            for (int mi = 0; mi < 5; mi++)
#pragma unroll
                for (int ki = 0; ki < 4; ki++) ldsm_x4_t(wf[mi * 4 + ki], la + ki * 16 * 160 + mi * 32);
        }
        bar_sync(BAR_INIT, RT);
        for (int i = ct; i < 2 * 8 * HL; i += 128) {
            int b = i / (8 * HL), r = (i / HL) % 8, cc = i % HL;
            sm.kall[b][40 + r][cc] = __float2bfloat16(0.f);
            sm.vall[b][40 + r][cc] = __float2bfloat16(0.f);
        }
        for (int i = ct; i < 8 * HL; i += 128) sm.qm[8 + i / HL][i % HL] = __float2bfloat16(0.f);
        for (int i = ct; i < 8 * 56; i += 128) sm.p[i / 56][i % 56] = __float2bfloat16(0.f);
        bar_sync(BAR_CTL, 128);
        constexpr uint32_t KV_BUF = 48 * HL * 2;
        const bf16* kv_src = g_qkv + (size_t)(ct >> 4) * (3 * HD_) + HD_ + h * DH_ + (ct & 15) * 8;
        const uint32_t kv_dst0 = smem_u32(&sm.kall[0][MEM_ + (ct >> 4)][(ct & 15) * 8]);
        const uint32_t kv_dst1 = smem_u32(&sm.vall[0][MEM_ + (ct >> 4)][(ct & 15) * 8]);
        auto prefetch_kv = [&](int s, int buf) {
            if (ct == 0) {
                const unsigned* cp = g_xcnt + h * NSEG_ + s;
                unsigned v; int n = 0;
                do { asm volatile("ld.acquire.gpu.global.u32 %0, [%1];" : "=r"(v) : "l"(cp) : "memory"); } while (v < 48u && ++n < SPIN_LIMIT);
            }
            bar_sync(BAR_CTL, 128);
            const bf16* src = kv_src + (size_t)s * SEG_ * (3 * HD_);
#pragma unroll
            for (int j = 0; j < 4; j++) {
                cp_async16(kv_dst0 + buf * KV_BUF + j * (8 * HL * 2), src + (size_t)j * 8 * (3 * HD_));
                cp_async16(kv_dst1 + buf * KV_BUF + j * (8 * HL * 2), src + (size_t)j * 8 * (3 * HD_) + HD_);
            }
            cp_async_commit();
        };
        const float4* acc_src = reinterpret_cast<const float4*>(g_acc) + ct;
        const uint32_t acc_dst = smem_u32(&sm.mem[(ct & 1) * 4][ct >> 1]);
        const uint4* hx_base = reinterpret_cast<const uint4*>(g_hx) + h * 1024;
        const int hx_rq = ct & 63, hx_half = ct >> 6;
        const uint4* hx_src = hx_base + hx_half * 64 + hx_rq;
        const uint32_t hx_col = (hx_rq & 7) * 8, hx_r = hx_rq >> 3;
        const uint32_t hx_dstA = (hx_half == 0 ? smem_u32(&sm.qm[hx_r][0]) : smem_u32(&sm.kall[0][hx_r][0])) + hx_col;
        const uint32_t hx_dstB = smem_u32(&sm.vall[0][hx_r][0]) + hx_col;
        const uint4* hx_probe = hx_base + (lane >> 3) * 256 + ((lane & 7) % 3) * 64 + (lane & 7) * 8 + 3;
        const int pb_r = ct >> 4, pb_pr = ct & 15;
        uint2* pb_dst = g_hx + (h * 1024 + c * 256 + pb_r * 8) * 2 + pb_pr;
        const float* pb_src = &sm.red[pb_pr >> 3][(pb_pr & 7) * 16 + pb_r];
        bf16* pb_k = g_kmem + (size_t)pb_r * HD_ + h * DH_ + c * 32 + pb_pr * 2;
        bf16* pb_v = g_vmem + (size_t)pb_r * HD_ + h * DH_ + c * 32 + pb_pr * 2;
        const uint32_t qa = smem_u32(&sm.qm[lane & 15][(lane >> 4) * 8]);
        const uint32_t kb0 = smem_u32(&sm.kall[0][cw * 8 + (lane & 7)][(lane >> 3) * 8]);
        const uint32_t va0 = smem_u32(&sm.vall[0][(lane & 7) + ((lane >> 4) & 1) * 8][cw * 32 + ((lane >> 3) & 1) * 8]);
        const uint32_t pbaddr = smem_u32(&sm.p[lane & 7][((lane >> 3) & 1) * 8]);
        const uint32_t ob = smem_u32(&sm.om[lane & 7][kh * 64 + (lane >> 3) * 8]);
        float* acc_dst_g = g_acc + (c * 160 + mg * 80 + g) * 8 + 2 * t;

        prefetch_kv(0, 0);
        for (int s = 0; s < NSEG_; s++) {
            const int buf = s & 1;
            const uint32_t flag = s + 1;
            const uint32_t bo = buf * KV_BUF;
            PROF(0);
            if (s == 0) {
                for (int i = ct; i < MEM_ * D_ / 8; i += 128) {
                    int r = i / (D_ / 8), cc = (i % (D_ / 8)) * 8;
                    *reinterpret_cast<uint4*>(&sm.mem[r][cc]) = *reinterpret_cast<const uint4*>(mem0 + r * D_ + cc);
                }
            } else {
                if (ct == 0) {
                    const unsigned* cp = g_cnt + (s - 1) * 32;
                    unsigned v; int n = 0;
                    do { asm volatile("ld.acquire.gpu.global.u32 %0, [%1];" : "=r"(v) : "l"(cp) : "memory"); } while (v < 256u && ++n < SPIN_LIMIT);
                }
                bar_sync(BAR_CTL, 128);
                PROF(1);
                const float4* src = acc_src + (size_t)(s - 1) * (MEM_ * D_ / 4);
                float4 v[10];
#pragma unroll
                for (int j = 0; j < 10; j++)
                    asm volatile("ld.relaxed.gpu.global.v4.f32 {%0,%1,%2,%3}, [%4];" : "=f"(v[j].x), "=f"(v[j].y), "=f"(v[j].z), "=f"(v[j].w) : "l"(src + 128 * j) : "memory");
#pragma unroll
                for (int j = 0; j < 10; j++) {
                    uint32_t lo = pack_bf16(v[j].x, v[j].y), hi = pack_bf16(v[j].z, v[j].w);
                    uint32_t d = acc_dst + j * 128;
                    asm volatile("st.shared.u16 [%0], %1;" ::"r"(d), "h"((uint16_t)(lo & 0xffff)) : "memory");
                    asm volatile("st.shared.u16 [%0], %1;" ::"r"(d + MEMS_LD * 2), "h"((uint16_t)(lo >> 16)) : "memory");
                    asm volatile("st.shared.u16 [%0], %1;" ::"r"(d + MEMS_LD * 4), "h"((uint16_t)(hi & 0xffff)) : "memory");
                    asm volatile("st.shared.u16 [%0], %1;" ::"r"(d + MEMS_LD * 6), "h"((uint16_t)(hi >> 16)) : "memory");
                }
            }
            bar_arrive(BAR_MEM, RT);
            PROF(2);
            bar_sync(BAR_RED, RT);
            PROF(3);
            {
                uint32_t pk0 = pack_bf16(pb_src[0] + pb_src[768], pb_src[8] + pb_src[768 + 8]);
                uint32_t pk1 = pack_bf16(pb_src[256] + pb_src[1024], pb_src[256 + 8] + pb_src[1024 + 8]);
                uint32_t pk2 = pack_bf16(pb_src[512] + pb_src[1280], pb_src[512 + 8] + pb_src[1280 + 8]);
                st_relaxed_v2(pb_dst, pk0, flag);
                st_relaxed_v2(pb_dst + 128, pk1, flag);
                st_relaxed_v2(pb_dst + 256, pk2, flag);
                *reinterpret_cast<uint32_t*>(pb_k + (size_t)s * (MEM_ * HD_)) = pk1;
                *reinterpret_cast<uint32_t*>(pb_v + (size_t)s * (MEM_ * HD_)) = pk2;
            }
            if (s == NSEG_ - 1) break;
            PROF(4);
            if (cw == 0) (void)poll_ll(hx_probe, flag);
            bar_sync(BAR_CTL, 128);
            PROF(5);
            {
                uint4 v[8];
#pragma unroll
                for (int j = 0; j < 4; j++) v[j] = ld_relaxed_v4(hx_src + j * 256);
                if (hx_half == 0) {
#pragma unroll
                    for (int j = 0; j < 4; j++) v[4 + j] = ld_relaxed_v4(hx_src + j * 256 + 128);
                }
#pragma unroll
                for (int j = 0; j < 4; j++) {
                    if (v[j].y != flag || v[j].w != flag) v[j] = poll_ll(hx_src + j * 256, flag);
                    sts64(hx_dstA + j * 64 + (hx_half ? bo : 0), v[j].x, v[j].z);
                }
                if (hx_half == 0) {
#pragma unroll
                    for (int j = 0; j < 4; j++) {
                        if (v[4 + j].y != flag || v[4 + j].w != flag) v[4 + j] = poll_ll(hx_src + j * 256 + 128, flag);
                        sts64(hx_dstB + j * 64 + bo, v[4 + j].x, v[4 + j].z);
                    }
                }
            }
            cp_async_wait<0>();
            bar_sync(BAR_CTL, 128);
            PROF(6);
            {
                uint32_t a[8][4], b[4][4], b2[4][4];
#pragma unroll
                for (int kk = 0; kk < 4; kk++) ldsm_x4(b[kk], kb0 + bo + kk * 64);
                if (cw == 0) {
#pragma unroll
                    for (int kk = 0; kk < 4; kk++) ldsm_x4(b2[kk], kb0 + bo + 32 * HL * 2 + kk * 64);
                }
#pragma unroll
                for (int kk = 0; kk < 8; kk++) ldsm_x4(a[kk], qa + kk * 32);
                float s0[4] = {0.f, 0.f, 0.f, 0.f}, s1[4] = {0.f, 0.f, 0.f, 0.f};
#pragma unroll
                for (int kk = 0; kk < 4; kk++) { mma16816(s0, a[2 * kk], b[kk][0], b[kk][1]); mma16816(s1, a[2 * kk + 1], b[kk][2], b[kk][3]); }
                const float scale = 0.08838834764831845f;
                *reinterpret_cast<float2*>(&sm.sc[g][cw * 8 + 2 * t]) =
                    make_float2(rbf(rbf(s0[0] + s1[0]) * scale), rbf(rbf(s0[1] + s1[1]) * scale));
                if (cw == 0) {
                    float u0[4] = {0.f, 0.f, 0.f, 0.f}, u1[4] = {0.f, 0.f, 0.f, 0.f};
#pragma unroll
                    for (int kk = 0; kk < 4; kk++) { mma16816(u0, a[2 * kk], b2[kk][0], b2[kk][1]); mma16816(u1, a[2 * kk + 1], b2[kk][2], b2[kk][3]); }
                    *reinterpret_cast<float2*>(&sm.sc[g][32 + 2 * t]) =
                        make_float2(rbf(rbf(u0[0] + u1[0]) * scale), rbf(rbf(u0[1] + u1[1]) * scale));
                }
            }
            bar_sync(BAR_CTL, 128);
            {
                float v0 = sm.sc[cw][lane], v1 = (lane < 8) ? sm.sc[cw][32 + lane] : -INFINITY;
                float y0 = sm.sc[cw + 4][lane], y1 = (lane < 8) ? sm.sc[cw + 4][32 + lane] : -INFINITY;
                float mx = fmaxf(v0, v1), my = fmaxf(y0, y1);
#pragma unroll
                for (int o = 16; o; o >>= 1) { mx = fmaxf(mx, __shfl_xor_sync(0xffffffffu, mx, o)); my = fmaxf(my, __shfl_xor_sync(0xffffffffu, my, o)); }
                float e0 = __expf(v0 - mx), e1 = (lane < 8) ? __expf(v1 - mx) : 0.f;
                float f0 = __expf(y0 - my), f1 = (lane < 8) ? __expf(y1 - my) : 0.f;
                float sx = e0 + e1, sy = f0 + f1;
#pragma unroll
                for (int o = 16; o; o >>= 1) { sx += __shfl_xor_sync(0xffffffffu, sx, o); sy += __shfl_xor_sync(0xffffffffu, sy, o); }
                float ix = 1.0f / sx, iy = 1.0f / sy;
                sm.p[cw][lane] = __float2bfloat16_rn(e0 * ix);
                sm.p[cw + 4][lane] = __float2bfloat16_rn(f0 * iy);
                if (lane < 8) { sm.p[cw][32 + lane] = __float2bfloat16_rn(e1 * ix); sm.p[cw + 4][32 + lane] = __float2bfloat16_rn(f1 * iy); }
            }
            bar_sync(BAR_CTL, 128);
            PROF(7);
            {
                uint32_t a[2][3][4], b[3][2];
#pragma unroll
                for (int kt = 0; kt < 3; kt++) {
                    asm volatile("ldmatrix.sync.aligned.m8n8.x2.shared.b16 {%0,%1}, [%2];" : "=r"(b[kt][0]), "=r"(b[kt][1]) : "r"(pbaddr + kt * 32));
                    ldsm_x4_t(a[0][kt], va0 + bo + kt * 16 * HL * 2);
                    ldsm_x4_t(a[1][kt], va0 + bo + kt * 16 * HL * 2 + 32);
                }
#pragma unroll
                for (int m = 0; m < 2; m++) {
                    float o[4] = {0.f, 0.f, 0.f, 0.f};
#pragma unroll
                    for (int kt = 0; kt < 3; kt++) mma16816(o, a[m][kt], b[kt][0], b[kt][1]);
                    int d0 = cw * 32 + m * 16 + g;
                    sm.om[2 * t][d0] = __float2bfloat16_rn(o[0]);
                    sm.om[2 * t + 1][d0] = __float2bfloat16_rn(o[1]);
                    sm.om[2 * t][d0 + 8] = __float2bfloat16_rn(o[2]);
                    sm.om[2 * t + 1][d0 + 8] = __float2bfloat16_rn(o[3]);
                }
            }
            bar_sync(BAR_CTL, 128);
            PROF(8);
            {
                float acc[5][4];
#pragma unroll
                for (int mi = 0; mi < 5; mi++) { acc[mi][0] = acc[mi][1] = acc[mi][2] = acc[mi][3] = 0.f; }
                uint32_t b[2][4];
                ldsm_x4(b[0], ob); ldsm_x4(b[1], ob + 64);
#pragma unroll
                for (int ki = 0; ki < 4; ki++)
#pragma unroll
                    for (int mi = 0; mi < 5; mi++) mma16816(acc[mi], wf[mi * 4 + ki], b[ki >> 1][(ki & 1) * 2], b[ki >> 1][(ki & 1) * 2 + 1]);
                if (kh == 1) {
#pragma unroll
                    for (int mi = 0; mi < 5; mi++)
                        *reinterpret_cast<float4*>(&sm.wred[mg][mi][lane * 4]) = make_float4(acc[mi][0], acc[mi][1], acc[mi][2], acc[mi][3]);
                }
                bar_sync(BAR_WO + mg, 64);
                if (kh == 0) {
                    float* dst = acc_dst_g + (size_t)s * (MEM_ * D_);
#pragma unroll
                    for (int mi = 0; mi < 5; mi++) {
                        float4 o2 = *reinterpret_cast<float4*>(&sm.wred[mg][mi][lane * 4]);
                        asm volatile("red.global.add.v2.f32 [%0], {%1,%2};" ::"l"(dst + mi * 128), "f"(acc[mi][0] + o2.x), "f"(acc[mi][1] + o2.y) : "memory");
                        asm volatile("red.global.add.v2.f32 [%0], {%1,%2};" ::"l"(dst + mi * 128 + 64), "f"(acc[mi][2] + o2.z), "f"(acc[mi][3] + o2.w) : "memory");
                    }
                    __threadfence();
                    __syncwarp();
                    if (lane == 0) atomicAdd(&g_cnt[s * 32], 1u);
                }
            }
            bar_arrive(BAR_GO, RT);
            PROF(9);
            prefetch_kv(s + 1, buf ^ 1);
            PROF(10);
        }
    }
}

__global__ void __launch_bounds__(128)
attn_x_kernel() {
    __shared__ __align__(16) bf16 sq[32][HL], sk[48][HL], sv[48][HL];
    const int s = blockIdx.x >> 5, h = blockIdx.x & 31;
    const int tid = threadIdx.x, lane = tid & 31, w = tid >> 5, g = lane >> 2, t = lane & 3;
    for (int i = tid; i < (32 + 40 + 40) * 16; i += 128) {
        int r = i >> 4, ch = i & 15;
        const bf16* src; bf16* dst;
        if (r < 32) { src = g_qkv + (size_t)(s * SEG_ + r) * (3 * HD_) + h * DH_; dst = sq[r]; }
        else if (r < 72) { int rr = r - 32; dst = sk[rr];
            src = rr < 8 ? g_kmem + ((size_t)s * MEM_ + rr) * HD_ + h * DH_ : g_qkv + (size_t)(s * SEG_ + rr - 8) * (3 * HD_) + HD_ + h * DH_; }
        else { int rr = r - 72; dst = sv[rr];
            src = rr < 8 ? g_vmem + ((size_t)s * MEM_ + rr) * HD_ + h * DH_ : g_qkv + (size_t)(s * SEG_ + rr - 8) * (3 * HD_) + 2 * HD_ + h * DH_; }
        cp_async16(smem_u32(dst + ch * 8), src + ch * 8);
    }
    cp_async_commit();
    for (int i = tid; i < 8 * 16; i += 128) *reinterpret_cast<uint4*>(&sv[40 + (i >> 4)][(i & 15) * 8]) = make_uint4(0, 0, 0, 0);
    cp_async_wait<0>();
    __syncthreads();
    const int rh = w & 1, dhh = w >> 1;
    float sc[5][4];
#pragma unroll
    for (int n = 0; n < 5; n++) sc[n][0] = sc[n][1] = sc[n][2] = sc[n][3] = 0.f;
#pragma unroll
    for (int kk = 0; kk < 8; kk++) {
        uint32_t a[4];
        ldsm_x4(a, smem_u32(&sq[rh * 16 + (lane & 15)][kk * 16 + (lane >> 4) * 8]));
#pragma unroll
        for (int n = 0; n < 5; n++) {
            uint32_t b[2];
            asm volatile("ldmatrix.sync.aligned.m8n8.x2.shared.b16 {%0,%1}, [%2];" : "=r"(b[0]), "=r"(b[1])
                         : "r"(smem_u32(&sk[n * 8 + (lane & 7)][kk * 16 + ((lane >> 3) & 1) * 8])));
            mma16816(sc[n], a, b[0], b[1]);
        }
    }
    const float scale = 0.08838834764831845f;
    float mx[2] = {-INFINITY, -INFINITY};
#pragma unroll
    for (int n = 0; n < 5; n++)
#pragma unroll
        for (int e = 0; e < 4; e++) {
            int row = rh * 16 + g + (e >> 1) * 8, key = n * 8 + 2 * t + (e & 1);
            float v = rbf(rbf(sc[n][e]) * scale);
            if (key > row + MEM_) v = -INFINITY;
            sc[n][e] = v;
            mx[e >> 1] = fmaxf(mx[e >> 1], v);
        }
#pragma unroll
    for (int o = 1; o < 4; o <<= 1) { mx[0] = fmaxf(mx[0], __shfl_xor_sync(0xffffffffu, mx[0], o)); mx[1] = fmaxf(mx[1], __shfl_xor_sync(0xffffffffu, mx[1], o)); }
    float sum[2] = {0.f, 0.f};
#pragma unroll
    for (int n = 0; n < 5; n++)
#pragma unroll
        for (int e = 0; e < 4; e++) { float ev = __expf(sc[n][e] - mx[e >> 1]); sc[n][e] = ev; sum[e >> 1] += ev; }
#pragma unroll
    for (int o = 1; o < 4; o <<= 1) { sum[0] += __shfl_xor_sync(0xffffffffu, sum[0], o); sum[1] += __shfl_xor_sync(0xffffffffu, sum[1], o); }
    float inv[2] = {1.0f / sum[0], 1.0f / sum[1]};
    uint32_t pa[3][4];
#pragma unroll
    for (int kt = 0; kt < 3; kt++) {
        pa[kt][0] = pack_bf16(sc[2 * kt][0] * inv[0], sc[2 * kt][1] * inv[0]);
        pa[kt][1] = pack_bf16(sc[2 * kt][2] * inv[1], sc[2 * kt][3] * inv[1]);
        if (kt < 2) {
            pa[kt][2] = pack_bf16(sc[2 * kt + 1][0] * inv[0], sc[2 * kt + 1][1] * inv[0]);
            pa[kt][3] = pack_bf16(sc[2 * kt + 1][2] * inv[1], sc[2 * kt + 1][3] * inv[1]);
        } else { pa[kt][2] = 0u; pa[kt][3] = 0u; }
    }
#pragma unroll
    for (int n = 0; n < 8; n++) {
        float o[4] = {0.f, 0.f, 0.f, 0.f};
#pragma unroll
        for (int kt = 0; kt < 3; kt++) {
            uint32_t b[2];
            asm volatile("ldmatrix.sync.aligned.m8n8.x2.trans.shared.b16 {%0,%1}, [%2];" : "=r"(b[0]), "=r"(b[1])
                         : "r"(smem_u32(&sv[kt * 16 + (lane & 15)][dhh * 64 + n * 8])));
            mma16816(o, pa[kt], b[0], b[1]);
        }
        int row = s * SEG_ + rh * 16 + g;
        bf16* dst = g_o + (size_t)row * HD_ + h * DH_ + dhh * 64 + n * 8 + 2 * t;
        *reinterpret_cast<uint32_t*>(dst) = pack_bf16(o[0], o[1]);
        *reinterpret_cast<uint32_t*>(dst + 8 * HD_) = pack_bf16(o[2], o[3]);
    }
}

typedef CUresult (*PFN_encodeTiled)(CUtensorMap*, CUtensorMapDataType, cuuint32_t, void*, const cuuint64_t*,
                                    const cuuint64_t*, const cuuint32_t*, const cuuint32_t*, CUtensorMapInterleave,
                                    CUtensorMapSwizzle, CUtensorMapL2promotion, CUtensorMapFloatOOBfill);
static PFN_encodeTiled p_encode = nullptr;

static CUtensorMap make_map(const void* ptr, uint64_t rows, uint64_t cols, uint64_t ld, uint32_t box_rows) {
    CUtensorMap m;
    cuuint64_t dims[2] = {cols, rows};
    cuuint64_t strides[1] = {ld * 2};
    cuuint32_t box[2] = {64, box_rows};
    cuuint32_t es[2] = {1, 1};
    p_encode(&m, CU_TENSOR_MAP_DATA_TYPE_BFLOAT16, 2, const_cast<void*>(ptr), dims, strides, box, es,
             CU_TENSOR_MAP_INTERLEAVE_NONE, CU_TENSOR_MAP_SWIZZLE_128B, CU_TENSOR_MAP_L2_PROMOTION_L2_128B,
             CU_TENSOR_MAP_FLOAT_OOB_FILL_NONE);
    return m;
}

template <int BN, int EPI>
static void launch_gemm(const CUtensorMap& a, const CUtensorMap& b0, const CUtensorMap& b1, const CUtensorMap& b2,
                        int nPerB, int M, int N, int K, EpiParams ep, cudaStream_t st) {
    constexpr int STAGE = 16384 + (BN / 64) * 8192;
    constexpr int NST = (200 * 1024) / STAGE;
    constexpr int SMEM = NST * STAGE + 1024;
    cudaFuncSetAttribute(gemm_kernel<BN, EPI>, cudaFuncAttributeMaxDynamicSharedMemorySize, SMEM);
    dim3 grid((N + BN - 1) / BN, M / 128);
    gemm_kernel<BN, EPI><<<grid, 384, SMEM, st>>>(a, b0, b1, b2, nPerB, N, K, ep);
}

extern "C" void kernel_launch(void* const* d_in, const int* in_sizes, int n_in, void* d_out, int out_size) {
    const bf16* x    = (const bf16*)d_in[0];
    const bf16* mem0 = (const bf16*)d_in[1];
    const bf16* Wq   = (const bf16*)d_in[2];
    const bf16* Wk   = (const bf16*)d_in[3];
    const bf16* Wv   = (const bf16*)d_in[4];
    const bf16* Wo   = (const bf16*)d_in[5];
    const bf16* w_in  = (const bf16*)d_in[8];
    const bf16* w_sp  = (const bf16*)d_in[9];
    const bf16* b_sp  = (const bf16*)d_in[10];
    const bf16* w_out = (const bf16*)d_in[11];
    bf16* out = (bf16*)d_out;
    cudaStream_t st = cudaStreamPerThread;

    if (!p_encode) {
        cudaDriverEntryPointQueryResult qr;
        cudaGetDriverEntryPoint("cuTensorMapEncodeTiled", (void**)&p_encode, cudaEnableDefault, &qr);
    }
    void *p_xn, *p_qkv, *p_z, *p_zg, *p_gate, *p_o, *p_acc, *p_cnt, *p_hx;
    cudaGetSymbolAddress(&p_xn, g_xn); cudaGetSymbolAddress(&p_qkv, g_qkv); cudaGetSymbolAddress(&p_z, g_z);
    cudaGetSymbolAddress(&p_zg, g_zg); cudaGetSymbolAddress(&p_gate, g_gate); cudaGetSymbolAddress(&p_o, g_o);
    cudaGetSymbolAddress(&p_acc, g_acc); cudaGetSymbolAddress(&p_cnt, g_cnt); cudaGetSymbolAddress(&p_hx, g_hx);

    CUtensorMap mA_xn  = make_map(p_xn, S_, D_, D_, 128);
    CUtensorMap mA_wsp = make_map(w_sp, S_, S_, S_, 128);
    CUtensorMap mA_zg  = make_map(p_zg, S_, FH_, FH_, 128);
    CUtensorMap mA_o   = make_map(p_o, S_, HD_, HD_, 128);
    CUtensorMap mB_wq  = make_map(Wq, D_, HD_, HD_, 64);
    CUtensorMap mB_wk  = make_map(Wk, D_, HD_, HD_, 64);
    CUtensorMap mB_wv  = make_map(Wv, D_, HD_, HD_, 64);
    CUtensorMap mB_win = make_map(w_in, D_, F_, F_, 64);
    CUtensorMap mB_z2  = make_map((bf16*)p_z + FH_, S_, FH_, F_, 64);
    CUtensorMap mB_wout = make_map(w_out, FH_, D_, D_, 64);
    CUtensorMap mB_wo  = make_map(Wo, HD_, D_, D_, 64);

    cudaMemsetAsync(p_acc, 0, sizeof(float) * NSEG_ * MEM_ * D_, st);
    cudaMemsetAsync(p_cnt, 0, sizeof(unsigned) * NSEG_ * 32, st);
    void* p_xcnt; cudaGetSymbolAddress(&p_xcnt, g_xcnt);
    cudaMemsetAsync(p_xcnt, 0, sizeof(unsigned) * H_ * NSEG_, st);
    cudaMemsetAsync(p_hx, 0, sizeof(uint2) * H_ * 4 * 256 * 2, st);

    ln_kernel<<<S_ / 8, 256, 0, st>>>(x);
    { EpiParams ep{(bf16*)p_z, F_, nullptr, nullptr}; launch_gemm<128, EPI_GELU>(mA_xn, mB_win, mB_win, mB_win, 1 << 20, S_, F_, D_, ep, st); }
    ln2_kernel<<<S_ / 8, 256, 0, st>>>();
    { EpiParams ep{(bf16*)p_zg, FH_, (const bf16*)p_z, b_sp}; launch_gemm<128, EPI_SP>(mA_wsp, mB_z2, mB_z2, mB_z2, 1 << 20, S_, FH_, S_, ep, st); }
    { EpiParams ep{(bf16*)p_gate, D_, nullptr, nullptr}; launch_gemm<128, EPI_SILU>(mA_zg, mB_wout, mB_wout, mB_wout, 1 << 20, S_, D_, FH_, ep, st); }
    constexpr int RSM = (int)sizeof(RecurSmem) > 16 * 10240 ? (int)sizeof(RecurSmem) : 16 * 10240;
    cudaFuncSetAttribute(recur_kernel, cudaFuncAttributeMaxDynamicSharedMemorySize, RSM);
    recur_kernel<<<128, RT, RSM, st>>>(mem0, Wq, Wk, Wv, Wo);
    attn_x_kernel<<<NSEG_ * H_, 128, 0, st>>>();
    { EpiParams ep{out, D_, x, (const bf16*)p_gate}; launch_gemm<128, EPI_FINAL>(mA_o, mB_wo, mB_wo, mB_wo, 1 << 20, S_, D_, HD_, ep, st); }
}
```

```cpp
#include <cuda_runtime.h>
#include <cuda_bf16.h>
#include <cuda.h>
#include <stdint.h>

typedef __nv_bfloat16 bf16;

constexpr int S_   = 2048;
constexpr int D_   = 640;
constexpr int H_   = 32;
constexpr int DH_  = 128;
constexpr int MEM_ = 8;
constexpr int SEG_ = 32;
constexpr int NSEG_ = S_ / SEG_;
constexpr int HD_  = H_ * DH_;
constexpr int F_   = 1728;
constexpr int FH_  = 864;

__device__ bf16 g_xn[S_ * D_];
__device__ bf16 g_qkv[(size_t)S_ * 3 * HD_];
__device__ bf16 g_z[S_ * F_];
__device__ bf16 g_zg[S_ * FH_];
__device__ bf16 g_gate[S_ * D_];
__device__ bf16 g_kmem[NSEG_ * MEM_ * HD_];
__device__ bf16 g_vmem[NSEG_ * MEM_ * HD_];
__device__ bf16 g_o[(size_t)S_ * HD_];
__device__ float g_acc[NSEG_ * MEM_ * D_];
__device__ unsigned g_cnt[NSEG_ * 32];
__device__ unsigned g_xcnt[H_ * NSEG_];
__device__ uint2 g_hx[H_ * 4 * 256 * 2];

__device__ __forceinline__ uint32_t smem_u32(const void* p) { return (uint32_t)__cvta_generic_to_shared(p); }
__device__ __forceinline__ float bf2f(bf16 v) { return __bfloat162float(v); }
__device__ __forceinline__ float rbf(float v) { return __bfloat162float(__float2bfloat16_rn(v)); }
__device__ __forceinline__ uint32_t pack_bf16(float lo, float hi) {
    __nv_bfloat162 t = __floats2bfloat162_rn(lo, hi);
    return *reinterpret_cast<uint32_t*>(&t);
}
__device__ __forceinline__ float lo_f(uint32_t u) { return __uint_as_float(u << 16); }
__device__ __forceinline__ float hi_f(uint32_t u) { return __uint_as_float(u & 0xffff0000u); }

__device__ __forceinline__ void mbar_init(uint32_t bar, uint32_t cnt) {
    asm volatile("mbarrier.init.shared.b64 [%0], %1;" ::"r"(bar), "r"(cnt));
}
__device__ __forceinline__ void mbar_expect_tx(uint32_t bar, uint32_t bytes) {
    asm volatile("mbarrier.arrive.expect_tx.shared.b64 _, [%0], %1;" ::"r"(bar), "r"(bytes) : "memory");
}
__device__ __forceinline__ void mbar_arrive(uint32_t bar) {
    asm volatile("mbarrier.arrive.shared.b64 _, [%0];" ::"r"(bar) : "memory");
}
__device__ __forceinline__ void mbar_wait(uint32_t bar, uint32_t parity) {
    asm volatile(
        "{\n .reg .pred p;\n"
        "WAIT_%=:\n"
        " mbarrier.try_wait.parity.shared.b64 p, [%0], %1;\n"
        " @p bra DONE_%=;\n"
        " bra WAIT_%=;\n"
        "DONE_%=:\n}\n" ::"r"(bar), "r"(parity) : "memory");
}
__device__ __forceinline__ void tma_load_2d(uint32_t dst, const CUtensorMap* tm, uint32_t bar, int c0, int c1) {
    asm volatile(
        "cp.async.bulk.tensor.2d.shared::cluster.global.mbarrier::complete_tx::bytes [%0], [%1, {%3, %4}], [%2];"
        ::"r"(dst), "l"(tm), "r"(bar), "r"(c0), "r"(c1) : "memory");
}
__device__ __forceinline__ void wgmma_fence() { asm volatile("wgmma.fence.sync.aligned;" ::: "memory"); }
__device__ __forceinline__ void wgmma_commit() { asm volatile("wgmma.commit_group.sync.aligned;" ::: "memory"); }
template <int N> __device__ __forceinline__ void wgmma_wait() { asm volatile("wgmma.wait_group.sync.aligned %0;" ::"n"(N) : "memory"); }

__device__ __forceinline__ uint64_t make_desc(uint32_t addr, uint32_t lbo, uint32_t sbo) {
    return (uint64_t)((addr & 0x3FFFF) >> 4) | ((uint64_t)(lbo >> 4) << 16) | ((uint64_t)(sbo >> 4) << 32) | (1ull << 62);
}

template <int N> struct Wgmma;
template <> struct Wgmma<128> {
    static __device__ __forceinline__ void mma(float* d, uint64_t da, uint64_t db, int sd) {
        asm volatile(
            "{\n.reg .pred p;\nsetp.ne.b32 p, %66, 0;\n"
            "wgmma.mma_async.sync.aligned.m64n128k16.f32.bf16.bf16 "
            "{%0,%1,%2,%3,%4,%5,%6,%7,%8,%9,%10,%11,%12,%13,%14,%15,"
            "%16,%17,%18,%19,%20,%21,%22,%23,%24,%25,%26,%27,%28,%29,%30,%31,"
            "%32,%33,%34,%35,%36,%37,%38,%39,%40,%41,%42,%43,%44,%45,%46,%47,"
            "%48,%49,%50,%51,%52,%53,%54,%55,%56,%57,%58,%59,%60,%61,%62,%63},"
            "%64,%65,p,1,1,0,1;\n}\n"
            : "+f"(d[0]), "+f"(d[1]), "+f"(d[2]), "+f"(d[3]), "+f"(d[4]), "+f"(d[5]), "+f"(d[6]), "+f"(d[7]),
              "+f"(d[8]), "+f"(d[9]), "+f"(d[10]), "+f"(d[11]), "+f"(d[12]), "+f"(d[13]), "+f"(d[14]), "+f"(d[15]),
              "+f"(d[16]), "+f"(d[17]), "+f"(d[18]), "+f"(d[19]), "+f"(d[20]), "+f"(d[21]), "+f"(d[22]), "+f"(d[23]),
              "+f"(d[24]), "+f"(d[25]), "+f"(d[26]), "+f"(d[27]), "+f"(d[28]), "+f"(d[29]), "+f"(d[30]), "+f"(d[31]),
              "+f"(d[32]), "+f"(d[33]), "+f"(d[34]), "+f"(d[35]), "+f"(d[36]), "+f"(d[37]), "+f"(d[38]), "+f"(d[39]),
              "+f"(d[40]), "+f"(d[41]), "+f"(d[42]), "+f"(d[43]), "+f"(d[44]), "+f"(d[45]), "+f"(d[46]), "+f"(d[47]),
              "+f"(d[48]), "+f"(d[49]), "+f"(d[50]), "+f"(d[51]), "+f"(d[52]), "+f"(d[53]), "+f"(d[54]), "+f"(d[55]),
              "+f"(d[56]), "+f"(d[57]), "+f"(d[58]), "+f"(d[59]), "+f"(d[60]), "+f"(d[61]), "+f"(d[62]), "+f"(d[63])
            : "l"(da), "l"(db), "r"(sd));
    }
};
template <> struct Wgmma<192> {
    static __device__ __forceinline__ void mma(float* d, uint64_t da, uint64_t db, int sd) {
        asm volatile(
            "{\n.reg .pred p;\nsetp.ne.b32 p, %98, 0;\n"
            "wgmma.mma_async.sync.aligned.m64n192k16.f32.bf16.bf16 "
            "{%0,%1,%2,%3,%4,%5,%6,%7,%8,%9,%10,%11,%12,%13,%14,%15,"
            "%16,%17,%18,%19,%20,%21,%22,%23,%24,%25,%26,%27,%28,%29,%30,%31,"
            "%32,%33,%34,%35,%36,%37,%38,%39,%40,%41,%42,%43,%44,%45,%46,%47,"
            "%48,%49,%50,%51,%52,%53,%54,%55,%56,%57,%58,%59,%60,%61,%62,%63,"
            "%64,%65,%66,%67,%68,%69,%70,%71,%72,%73,%74,%75,%76,%77,%78,%79,"
            "%80,%81,%82,%83,%84,%85,%86,%87,%88,%89,%90,%91,%92,%93,%94,%95},"
            "%96,%97,p,1,1,0,1;\n}\n"
            : "+f"(d[0]), "+f"(d[1]), "+f"(d[2]), "+f"(d[3]), "+f"(d[4]), "+f"(d[5]), "+f"(d[6]), "+f"(d[7]),
              "+f"(d[8]), "+f"(d[9]), "+f"(d[10]), "+f"(d[11]), "+f"(d[12]), "+f"(d[13]), "+f"(d[14]), "+f"(d[15]),
              "+f"(d[16]), "+f"(d[17]), "+f"(d[18]), "+f"(d[19]), "+f"(d[20]), "+f"(d[21]), "+f"(d[22]), "+f"(d[23]),
              "+f"(d[24]), "+f"(d[25]), "+f"(d[26]), "+f"(d[27]), "+f"(d[28]), "+f"(d[29]), "+f"(d[30]), "+f"(d[31]),
              "+f"(d[32]), "+f"(d[33]), "+f"(d[34]), "+f"(d[35]), "+f"(d[36]), "+f"(d[37]), "+f"(d[38]), "+f"(d[39]),
              "+f"(d[40]), "+f"(d[41]), "+f"(d[42]), "+f"(d[43]), "+f"(d[44]), "+f"(d[45]), "+f"(d[46]), "+f"(d[47]),
              "+f"(d[48]), "+f"(d[49]), "+f"(d[50]), "+f"(d[51]), "+f"(d[52]), "+f"(d[53]), "+f"(d[54]), "+f"(d[55]),
              "+f"(d[56]), "+f"(d[57]), "+f"(d[58]), "+f"(d[59]), "+f"(d[60]), "+f"(d[61]), "+f"(d[62]), "+f"(d[63]),
              "+f"(d[64]), "+f"(d[65]), "+f"(d[66]), "+f"(d[67]), "+f"(d[68]), "+f"(d[69]), "+f"(d[70]), "+f"(d[71]),
              "+f"(d[72]), "+f"(d[73]), "+f"(d[74]), "+f"(d[75]), "+f"(d[76]), "+f"(d[77]), "+f"(d[78]), "+f"(d[79]),
              "+f"(d[80]), "+f"(d[81]), "+f"(d[82]), "+f"(d[83]), "+f"(d[84]), "+f"(d[85]), "+f"(d[86]), "+f"(d[87]),
              "+f"(d[88]), "+f"(d[89]), "+f"(d[90]), "+f"(d[91]), "+f"(d[92]), "+f"(d[93]), "+f"(d[94]), "+f"(d[95])
            : "l"(da), "l"(db), "r"(sd));
    }
};

template <> struct Wgmma<256> {
    static __device__ __forceinline__ void mma(float* d, uint64_t da, uint64_t db, int sd) {
        asm volatile(
            "{\n.reg .pred p;\nsetp.ne.b32 p, %130, 0;\n"
            "wgmma.mma_async.sync.aligned.m64n256k16.f32.bf16.bf16 "
            "{%0,%1,%2,%3,%4,%5,%6,%7,%8,%9,%10,%11,%12,%13,%14,%15,%16,%17,%18,%19,%20,%21,%22,%23,%24,%25,%26,%27,%28,%29,%30,%31,%32,%33,%34,%35,%36,%37,%38,%39,%40,%41,%42,%43,%44,%45,%46,%47,%48,%49,%50,%51,%52,%53,%54,%55,%56,%57,%58,%59,%60,%61,%62,%63,%64,%65,%66,%67,%68,%69,%70,%71,%72,%73,%74,%75,%76,%77,%78,%79,%80,%81,%82,%83,%84,%85,%86,%87,%88,%89,%90,%91,%92,%93,%94,%95,%96,%97,%98,%99,%100,%101,%102,%103,%104,%105,%106,%107,%108,%109,%110,%111,%112,%113,%114,%115,%116,%117,%118,%119,%120,%121,%122,%123,%124,%125,%126,%127},"
            "%128,%129,p,1,1,0,1;\n}\n"
            : "+f"(d[0]), "+f"(d[1]), "+f"(d[2]), "+f"(d[3]), "+f"(d[4]), "+f"(d[5]), "+f"(d[6]), "+f"(d[7]), "+f"(d[8]), "+f"(d[9]), "+f"(d[10]), "+f"(d[11]), "+f"(d[12]), "+f"(d[13]), "+f"(d[14]), "+f"(d[15]), "+f"(d[16]), "+f"(d[17]), "+f"(d[18]), "+f"(d[19]), "+f"(d[20]), "+f"(d[21]), "+f"(d[22]), "+f"(d[23]), "+f"(d[24]), "+f"(d[25]), "+f"(d[26]), "+f"(d[27]), "+f"(d[28]), "+f"(d[29]), "+f"(d[30]), "+f"(d[31]), "+f"(d[32]), "+f"(d[33]), "+f"(d[34]), "+f"(d[35]), "+f"(d[36]), "+f"(d[37]), "+f"(d[38]), "+f"(d[39]), "+f"(d[40]), "+f"(d[41]), "+f"(d[42]), "+f"(d[43]), "+f"(d[44]), "+f"(d[45]), "+f"(d[46]), "+f"(d[47]), "+f"(d[48]), "+f"(d[49]), "+f"(d[50]), "+f"(d[51]), "+f"(d[52]), "+f"(d[53]), "+f"(d[54]), "+f"(d[55]), "+f"(d[56]), "+f"(d[57]), "+f"(d[58]), "+f"(d[59]), "+f"(d[60]), "+f"(d[61]), "+f"(d[62]), "+f"(d[63]), "+f"(d[64]), "+f"(d[65]), "+f"(d[66]), "+f"(d[67]), "+f"(d[68]), "+f"(d[69]), "+f"(d[70]), "+f"(d[71]), "+f"(d[72]), "+f"(d[73]), "+f"(d[74]), "+f"(d[75]), "+f"(d[76]), "+f"(d[77]), "+f"(d[78]), "+f"(d[79]), "+f"(d[80]), "+f"(d[81]), "+f"(d[82]), "+f"(d[83]), "+f"(d[84]), "+f"(d[85]), "+f"(d[86]), "+f"(d[87]), "+f"(d[88]), "+f"(d[89]), "+f"(d[90]), "+f"(d[91]), "+f"(d[92]), "+f"(d[93]), "+f"(d[94]), "+f"(d[95]), "+f"(d[96]), "+f"(d[97]), "+f"(d[98]), "+f"(d[99]), "+f"(d[100]), "+f"(d[101]), "+f"(d[102]), "+f"(d[103]), "+f"(d[104]), "+f"(d[105]), "+f"(d[106]), "+f"(d[107]), "+f"(d[108]), "+f"(d[109]), "+f"(d[110]), "+f"(d[111]), "+f"(d[112]), "+f"(d[113]), "+f"(d[114]), "+f"(d[115]), "+f"(d[116]), "+f"(d[117]), "+f"(d[118]), "+f"(d[119]), "+f"(d[120]), "+f"(d[121]), "+f"(d[122]), "+f"(d[123]), "+f"(d[124]), "+f"(d[125]), "+f"(d[126]), "+f"(d[127])
            : "l"(da), "l"(db), "r"(sd));
    }
};
template <int W>
__device__ __forceinline__ void ln_row(const bf16* __restrict__ src, bf16* __restrict__ dst, int lane) {
    constexpr int NP = W / 64;
    constexpr int REM = (W / 2) % 32;
    uint32_t v[NP + 1];
    const uint32_t* s32 = reinterpret_cast<const uint32_t*>(src);
    float sum = 0.f;
#pragma unroll
    for (int i = 0; i < NP; i++) { v[i] = s32[i * 32 + lane]; sum += lo_f(v[i]) + hi_f(v[i]); }
    if (REM) { v[NP] = (lane < REM) ? s32[NP * 32 + lane] : 0u; if (lane < REM) sum += lo_f(v[NP]) + hi_f(v[NP]); }
#pragma unroll
    for (int o = 16; o; o >>= 1) sum += __shfl_xor_sync(0xffffffffu, sum, o);
    float mean = sum * (1.0f / W);
    float vs = 0.f;
#pragma unroll
    for (int i = 0; i < NP; i++) { float a = lo_f(v[i]) - mean, b = hi_f(v[i]) - mean; vs += a * a + b * b; }
    if (REM && lane < REM) { float a = lo_f(v[NP]) - mean, b = hi_f(v[NP]) - mean; vs += a * a + b * b; }
#pragma unroll
    for (int o = 16; o; o >>= 1) vs += __shfl_xor_sync(0xffffffffu, vs, o);
    float var = rbf(vs * (1.0f / W));
    float mb = rbf(mean);
    float den = rbf(sqrtf(rbf(var + 1e-5f)));
    uint32_t* d32 = reinterpret_cast<uint32_t*>(dst);
#pragma unroll
    for (int i = 0; i < NP; i++) d32[i * 32 + lane] = pack_bf16(rbf(lo_f(v[i]) - mb) / den, rbf(hi_f(v[i]) - mb) / den);
    if (REM && lane < REM) d32[NP * 32 + lane] = pack_bf16(rbf(lo_f(v[NP]) - mb) / den, rbf(hi_f(v[NP]) - mb) / den);
}

__global__ void ln_kernel(const bf16* __restrict__ x) {
    int row = blockIdx.x * 8 + (threadIdx.x >> 5);
    ln_row<D_>(x + (size_t)row * D_, g_xn + (size_t)row * D_, threadIdx.x & 31);
}
__global__ void ln2_kernel() {
    int row = blockIdx.x * 8 + (threadIdx.x >> 5);
    bf16* p = g_z + (size_t)row * F_ + FH_;
    ln_row<FH_>(p, p, threadIdx.x & 31);
}

enum { EPI_STORE = 0, EPI_GELU = 1, EPI_SP = 2, EPI_SILU = 3, EPI_FINAL = 4 };
struct EpiParams {
    bf16* out; int ldo;
    const bf16* aux0;
    const bf16* aux1;
};

__device__ __forceinline__ float gelu_tanh_f(float x) {
    const float k0 = 0.7978845608028654f, k1 = 0.044715f;
    float inner = k0 * (x + k1 * x * x * x);
    return 0.5f * x * (1.0f + tanhf(inner));
}
__device__ __forceinline__ float silu_f(float x) { return x / (1.0f + expf(-x)); }

template <int BN, int EPI>
__global__ void __launch_bounds__(384, 1)
gemm_kernel(const __grid_constant__ CUtensorMap tmA, const __grid_constant__ CUtensorMap tmB0,
            const __grid_constant__ CUtensorMap tmB1, const __grid_constant__ CUtensorMap tmB2,
            int nPerB, int N, int K, EpiParams ep) {
    constexpr int BM = 128, BK = 64;
    constexpr int A_BYTES = BM * BK * 2;
    constexpr int B_BYTES = (BN / 64) * 8192;
    constexpr int STAGE = A_BYTES + B_BYTES;
    constexpr int NST = (200 * 1024) / STAGE;
    constexpr int OLD = BN + 8;
    extern __shared__ __align__(1024) uint8_t smem_raw[];
    uint8_t* smem = (uint8_t*)(((uintptr_t)smem_raw + 1023) & ~(uintptr_t)1023);
    __shared__ __align__(8) uint64_t full_bar[NST], empty_bar[NST];

    const int tid = threadIdx.x, wg = tid >> 7;
    const int m0 = blockIdx.y * BM, n0 = blockIdx.x * BN;
    const int nk = (K + BK - 1) / BK;

    if (tid == 0) {
        for (int i = 0; i < NST; i++) { mbar_init(smem_u32(&full_bar[i]), 1); mbar_init(smem_u32(&empty_bar[i]), 2); }
        asm volatile("fence.mbarrier_init.release.cluster;" ::: "memory");
    }
    __syncthreads();

    if (wg == 0) {
        if (tid == 0) {
            const int bsel = n0 / nPerB;
            const CUtensorMap* tmB = bsel == 0 ? &tmB0 : (bsel == 1 ? &tmB1 : &tmB2);
            const int nb = n0 - bsel * nPerB;
            for (int kt = 0; kt < nk; kt++) {
                int st = kt % NST; uint32_t ph = (kt / NST) & 1;
                mbar_wait(smem_u32(&empty_bar[st]), ph ^ 1);
                uint32_t fb = smem_u32(&full_bar[st]);
                mbar_expect_tx(fb, STAGE);
                uint32_t sa = smem_u32(smem + st * STAGE);
                tma_load_2d(sa, &tmA, fb, kt * BK, m0);
#pragma unroll
                for (int j = 0; j < BN / 64; j++) tma_load_2d(sa + A_BYTES + j * 8192, tmB, fb, nb + j * 64, kt * BK);
            }
        }
    } else {
        const int cw = wg - 1;
        float acc[BN / 2];
        for (int kt = 0; kt < nk; kt++) {
            int st = kt % NST; uint32_t ph = (kt / NST) & 1;
            mbar_wait(smem_u32(&full_bar[st]), ph);
            uint32_t sa = smem_u32(smem + st * STAGE) + cw * 64 * 128;
            uint32_t sb = smem_u32(smem + st * STAGE) + A_BYTES;
            wgmma_fence();
#pragma unroll
            for (int k = 0; k < BK / 16; k++) {
                uint64_t da = make_desc(sa + k * 32, 16, 1024);
                uint64_t db = make_desc(sb + k * 2048, 8192, 1024);
                Wgmma<BN>::mma(acc, da, db, (kt | k) != 0);
            }
            wgmma_commit();
            wgmma_wait<1>();
            if (kt > 0 && (tid & 127) == 0) mbar_arrive(smem_u32(&empty_bar[(kt - 1) % NST]));
        }
        wgmma_wait<0>();
        asm volatile("bar.sync 1, 256;" ::: "memory");
        const int lane = tid & 31, wi = (tid >> 5) & 3, g = lane >> 2, t = lane & 3;
        bf16* stg = reinterpret_cast<bf16*>(smem) + cw * 64 * OLD;
#pragma unroll
        for (int j = 0; j < BN / 8; j++) {
            *reinterpret_cast<uint32_t*>(&stg[(wi * 16 + g) * OLD + j * 8 + 2 * t]) = pack_bf16(acc[4 * j], acc[4 * j + 1]);
            *reinterpret_cast<uint32_t*>(&stg[(wi * 16 + g + 8) * OLD + j * 8 + 2 * t]) = pack_bf16(acc[4 * j + 2], acc[4 * j + 3]);
        }
        asm volatile("bar.sync %0, 128;" ::"r"(2 + cw) : "memory");
        constexpr int CPR = BN / 8;
        const int ltid = tid & 127;
#pragma unroll 4
        for (int i = ltid; i < 64 * CPR; i += 128) {
            int r = i / CPR, ch = i % CPR;
            int row = m0 + cw * 64 + r, col = n0 + ch * 8;
            if (col >= N) continue;
            uint4 v = *reinterpret_cast<const uint4*>(&stg[r * OLD + ch * 8]);
            uint32_t u[4] = {v.x, v.y, v.z, v.w}, o[4];
            if (EPI == EPI_STORE) {
#pragma unroll
                for (int q = 0; q < 4; q++) o[q] = u[q];
            } else if (EPI == EPI_GELU) {
#pragma unroll
                for (int q = 0; q < 4; q++) o[q] = pack_bf16(gelu_tanh_f(lo_f(u[q])), gelu_tanh_f(hi_f(u[q])));
            } else if (EPI == EPI_SP) {
                float bb = bf2f(ep.aux1[row]);
                uint4 z = *reinterpret_cast<const uint4*>(ep.aux0 + (size_t)row * F_ + col);
                uint32_t zz[4] = {z.x, z.y, z.z, z.w};
#pragma unroll
                for (int q = 0; q < 4; q++) o[q] = pack_bf16(lo_f(zz[q]) * rbf(lo_f(u[q]) + bb), hi_f(zz[q]) * rbf(hi_f(u[q]) + bb));
            } else if (EPI == EPI_SILU) {
#pragma unroll
                for (int q = 0; q < 4; q++) o[q] = pack_bf16(silu_f(lo_f(u[q])), silu_f(hi_f(u[q])));
            } else {
                uint4 xv = *reinterpret_cast<const uint4*>(ep.aux0 + (size_t)row * D_ + col);
                uint4 gv = *reinterpret_cast<const uint4*>(ep.aux1 + (size_t)row * D_ + col);
                uint32_t xx[4] = {xv.x, xv.y, xv.z, xv.w}, gg[4] = {gv.x, gv.y, gv.z, gv.w};
#pragma unroll
                for (int q = 0; q < 4; q++)
                    o[q] = pack_bf16(lo_f(xx[q]) + rbf(lo_f(u[q]) * lo_f(gg[q])), hi_f(xx[q]) + rbf(hi_f(u[q]) * hi_f(gg[q])));
            }
            *reinterpret_cast<uint4*>(ep.out + (size_t)row * ep.ldo + col) = make_uint4(o[0], o[1], o[2], o[3]);
        }
    }
}

__device__ __forceinline__ void mma16816(float* c, const uint32_t* a, uint32_t b0, uint32_t b1) {
    asm volatile(
        "mma.sync.aligned.m16n8k16.row.col.f32.bf16.bf16.f32 {%0,%1,%2,%3}, {%4,%5,%6,%7}, {%8,%9}, {%0,%1,%2,%3};"
        : "+f"(c[0]), "+f"(c[1]), "+f"(c[2]), "+f"(c[3])
        : "r"(a[0]), "r"(a[1]), "r"(a[2]), "r"(a[3]), "r"(b0), "r"(b1));
}
__device__ __forceinline__ void ldsm_x4(uint32_t* r, uint32_t addr) {
    asm volatile("ldmatrix.sync.aligned.m8n8.x4.shared.b16 {%0,%1,%2,%3}, [%4];"
                 : "=r"(r[0]), "=r"(r[1]), "=r"(r[2]), "=r"(r[3]) : "r"(addr));
}
__device__ __forceinline__ void ldsm_x4_t(uint32_t* r, uint32_t addr) {
    asm volatile("ldmatrix.sync.aligned.m8n8.x4.trans.shared.b16 {%0,%1,%2,%3}, [%4];"
                 : "=r"(r[0]), "=r"(r[1]), "=r"(r[2]), "=r"(r[3]) : "r"(addr));
}
__device__ __forceinline__ uint4 ld_relaxed_v4(const void* p) {
    uint4 v;
    asm volatile("ld.relaxed.gpu.global.v4.u32 {%0,%1,%2,%3}, [%4];" : "=r"(v.x), "=r"(v.y), "=r"(v.z), "=r"(v.w) : "l"(p) : "memory");
    return v;
}
__device__ __forceinline__ void st_relaxed_v4(void* p, uint32_t a, uint32_t b, uint32_t c, uint32_t d) {
    asm volatile("st.relaxed.gpu.global.v4.u32 [%0], {%1,%2,%3,%4};" ::"l"(p), "r"(a), "r"(b), "r"(c), "r"(d) : "memory");
}
__device__ __forceinline__ void st_relaxed_v2(void* p, uint32_t a, uint32_t b) {
    asm volatile("st.relaxed.gpu.global.v2.u32 [%0], {%1,%2};" ::"l"(p), "r"(a), "r"(b) : "memory");
}
__device__ __forceinline__ void cp_async16(uint32_t dst, const void* src) {
    asm volatile("cp.async.cg.shared.global [%0], [%1], 16;" ::"r"(dst), "l"(src) : "memory");
}
__device__ __forceinline__ void cp_async_commit() { asm volatile("cp.async.commit_group;" ::: "memory"); }
template <int N> __device__ __forceinline__ void cp_async_wait() { asm volatile("cp.async.wait_group %0;" ::"n"(N) : "memory"); }

#define PROF(i) do {} while (0)
constexpr int SPIN_LIMIT = 4000000;

__device__ __forceinline__ uint4 poll_ll(const void* p, uint32_t flag) {
    uint4 v = ld_relaxed_v4(p);
    int n = 0;
    while ((v.y != flag || v.w != flag) && ++n < SPIN_LIMIT) {
        v = ld_relaxed_v4(p);
    }
    return v;
}

constexpr int RT = 512;
constexpr int MEMS_LD = D_ + 8;
constexpr int HL = DH_ + 8;
struct RecurSmem {
    bf16 mem[MEM_][MEMS_LD];
    bf16 kall[2][48][HL];
    bf16 vall[2][48][HL];
    bf16 qm[16][HL];
    float sc[MEM_][40];
    bf16 p[MEM_][48 + 8];
    bf16 om[MEM_][HL];
    float red[12][16 * 8];
    float wred[2][5][16 * 8];
    bf16 xs[2][SEG_][MEMS_LD];
    float redx[6][4][16 * 8];
    bf16 xo[SEG_][96 + 8];
};

__device__ __forceinline__ void bar_sync(int id, int n) { asm volatile("bar.sync %0, %1;" ::"r"(id), "r"(n) : "memory"); }
__device__ __forceinline__ void bar_arrive(int id, int n) { asm volatile("bar.arrive %0, %1;" ::"r"(id), "r"(n) : "memory"); }
__device__ __forceinline__ void sts64(uint32_t a, uint32_t x, uint32_t y) { asm volatile("st.shared.v2.u32 [%0], {%1,%2};" ::"r"(a), "r"(x), "r"(y) : "memory"); }
__device__ __forceinline__ uint32_t ldg_u16x2(const bf16* p0, const bf16* p1) {
    return (uint32_t)*(const uint16_t*)p0 | ((uint32_t)*(const uint16_t*)p1 << 16);
}
enum { BAR_MEM = 1, BAR_RED = 2, BAR_CTL = 3, BAR_WO = 4, BAR_INIT = 6, BAR_X = 7, BAR_GO = 8 };

__global__ void __launch_bounds__(RT, 1)
recur_kernel(const bf16* __restrict__ mem0, const bf16* __restrict__ Wq, const bf16* __restrict__ Wk,
             const bf16* __restrict__ Wv, const bf16* __restrict__ Wo) {
    extern __shared__ __align__(16) uint8_t smem_raw[];
    RecurSmem& sm = *reinterpret_cast<RecurSmem*>(smem_raw);
    const int tid = threadIdx.x, lane = tid & 31, w = tid >> 5;
    const int g = lane >> 2, t = lane & 3;
    const int h = blockIdx.x >> 2, c = blockIdx.x & 3;

    if (w < 12) {
        asm volatile("setmaxnreg.dec.sync.aligned.u32 112;");
        uint32_t wf[20][4];
        const int mt = w % 6, kh = w / 6;
        {
            const bf16* W = (mt < 2) ? Wq : (mt < 4 ? Wk : Wv);
            int f0 = h * DH_ + c * 32 + (mt & 1) * 16;
            uint32_t stg = smem_u32(smem_raw) + w * 10240;
#pragma unroll 4
            for (int i = lane; i < 640; i += 32)
                cp_async16(stg + i * 16, W + (size_t)(kh * 320 + (i >> 1)) * HD_ + f0 + (i & 1) * 8);
            cp_async_commit(); cp_async_wait<0>(); __syncwarp();
            uint32_t la = stg + ((lane & 7) + ((lane >> 4) & 1) * 8) * 32 + ((lane >> 3) & 1) * 16;
#pragma unroll
            for (int i = 0; i < 20; i++) ldsm_x4_t(wf[i], la + i * 512);
        }
        bar_sync(BAR_INIT, RT);
        const uint32_t base = smem_u32(&sm.mem[lane & 7][kh * 320 + (lane >> 3) * 8]);
        const uint32_t rp = smem_u32(&sm.red[w][g * 8 + 2 * t]);
        const uint32_t xbase0 = smem_u32(&sm.xs[0][lane & 7][kh * 320 + (lane >> 3) * 8]);
        uint32_t xbase = xbase0;
        const uint32_t rxp = smem_u32(&sm.redx[mt][0][lane * 4]);
        auto load_x = [&](int seg) {
            for (int i = tid; i < SEG_ * (D_ / 8); i += 384) {
                int r = i / (D_ / 8), ch = i % (D_ / 8);
                cp_async16(smem_u32(&sm.xs[seg & 1][r][ch * 8]), g_xn + (size_t)(seg * SEG_ + r) * D_ + ch * 8);
            }
            cp_async_commit();
        };
        float acc[4][4];
        auto xhalf = [&](int n0) {
#pragma unroll
            for (int nt = 0; nt < 2; nt++) { acc[n0 + nt][0] = acc[n0 + nt][1] = acc[n0 + nt][2] = acc[n0 + nt][3] = 0.f; }
#pragma unroll
            for (int i = 0; i < 10; i++) {
#pragma unroll
                for (int nt = 0; nt < 2; nt++) {
                    uint32_t b[4];
                    ldsm_x4(b, xbase + (n0 + nt) * (8 * MEMS_LD * 2) + i * 64);
                    mma16816(acc[n0 + nt], wf[2 * i], b[0], b[1]);
                    mma16816(acc[n0 + nt], wf[2 * i + 1], b[2], b[3]);
                }
            }
        };
        auto xworkA = [&](int seg) {
            cp_async_wait<0>();
            bar_sync(BAR_X, 384);
            if (seg + 1 < NSEG_) load_x(seg + 1);
            xbase = xbase0 + (seg & 1) * (SEG_ * MEMS_LD * 2);
            xhalf(0);
        };
        auto xwork = [&](int seg) {
            xhalf(2);
            if (kh == 1) {
#pragma unroll
                for (int nt = 0; nt < 4; nt++)
                    asm volatile("st.shared.v4.f32 [%0], {%1,%2,%3,%4};" ::"r"(rxp + nt * 512), "f"(acc[nt][0]), "f"(acc[nt][1]), "f"(acc[nt][2]), "f"(acc[nt][3]) : "memory");
            }
            bar_sync(BAR_X, 384);
            if (kh == 0) {
#pragma unroll
                for (int nt = 0; nt < 4; nt++) {
                    float4 o;
                    asm volatile("ld.shared.v4.f32 {%0,%1,%2,%3}, [%4];" : "=f"(o.x), "=f"(o.y), "=f"(o.z), "=f"(o.w) : "r"(rxp + nt * 512) : "memory");
                    bf16* d = &sm.xo[nt * 8 + 2 * t][mt * 16 + g];
                    d[0] = __float2bfloat16_rn(acc[nt][0] + o.x);
                    d[104] = __float2bfloat16_rn(acc[nt][1] + o.y);
                    d[8] = __float2bfloat16_rn(acc[nt][2] + o.z);
                    d[104 + 8] = __float2bfloat16_rn(acc[nt][3] + o.w);
                }
            }
            bar_sync(BAR_X, 384);
            {
                int r = tid / 12, ch = tid % 12;
                uint4 v = *reinterpret_cast<const uint4*>(&sm.xo[r][ch * 8]);
                *reinterpret_cast<uint4*>(g_qkv + (size_t)(seg * SEG_ + r) * (3 * HD_) + (ch >> 2) * HD_ + h * DH_ + c * 32 + (ch & 3) * 8) = v;
            }
        };
        auto xsignal = [&](int seg) {
            __threadfence();
            __syncwarp();
            if (lane == 0) atomicAdd(&g_xcnt[h * NSEG_ + seg], 1u);
        };
        load_x(0);
        xworkA(0); xwork(0); xsignal(0);
        xworkA(1); xwork(1); xsignal(1);
        for (int s = 0; s < NSEG_; s++) {
            bar_sync(BAR_MEM, RT);
            float a0[4] = {0.f, 0.f, 0.f, 0.f}, a1[4] = {0.f, 0.f, 0.f, 0.f};
#pragma unroll
            for (int i = 0; i < 10; i++) {
                uint32_t b[4];
                ldsm_x4(b, base + i * 64);
                mma16816(a0, wf[2 * i], b[0], b[1]);
                mma16816(a1, wf[2 * i + 1], b[2], b[3]);
            }
            sts64(rp, __float_as_uint(a0[0] + a1[0]), __float_as_uint(a0[1] + a1[1]));
            sts64(rp + 256, __float_as_uint(a0[2] + a1[2]), __float_as_uint(a0[3] + a1[3]));
            bar_arrive(BAR_RED, RT);
            if (s + 2 < NSEG_) xworkA(s + 2);
            if (s >= 1 && s + 1 < NSEG_) xsignal(s + 1);
            if (s + 1 < NSEG_) bar_sync(BAR_GO, RT);
            if (s + 2 < NSEG_) xwork(s + 2);
        }
    } else {
        asm volatile("setmaxnreg.inc.sync.aligned.u32 176;");
        const int ct = tid - 384, cw = w - 12;
        const int mg = cw >> 1, kh = cw & 1;
        uint32_t wf[20][4];
        {
            uint32_t stg = smem_u32(smem_raw) + 12 * 10240 + cw * 10240;
#pragma unroll 4
            for (int i = lane; i < 640; i += 32) {
                int r = i / 10, ch = i % 10;
                cp_async16(stg + r * 160 + ch * 16, Wo + (size_t)(h * DH_ + kh * 64 + r) * D_ + c * 160 + mg * 80 + ch * 8);
            }
            cp_async_commit(); cp_async_wait<0>(); __syncwarp();
            uint32_t la = stg + ((lane & 7) + ((lane >> 4) & 1) * 8) * 160 + ((lane >> 3) & 1) * 16;
#pragma unroll
            for (int mi = 0; mi < 5; mi++)
#pragma unroll
                for (int ki = 0; ki < 4; ki++) ldsm_x4_t(wf[mi * 4 + ki], la + ki * 16 * 160 + mi * 32);
        }
        bar_sync(BAR_INIT, RT);
        for (int i = ct; i < 2 * 8 * HL; i += 128) {
            int b = i / (8 * HL), r = (i / HL) % 8, cc = i % HL;
            sm.kall[b][40 + r][cc] = __float2bfloat16(0.f);
            sm.vall[b][40 + r][cc] = __float2bfloat16(0.f);
        }
        for (int i = ct; i < 8 * HL; i += 128) sm.qm[8 + i / HL][i % HL] = __float2bfloat16(0.f);
        for (int i = ct; i < 8 * 56; i += 128) sm.p[i / 56][i % 56] = __float2bfloat16(0.f);
        bar_sync(BAR_CTL, 128);
        constexpr uint32_t KV_BUF = 48 * HL * 2;
        const bf16* kv_src = g_qkv + (size_t)(ct >> 4) * (3 * HD_) + HD_ + h * DH_ + (ct & 15) * 8;
        const uint32_t kv_dst0 = smem_u32(&sm.kall[0][MEM_ + (ct >> 4)][(ct & 15) * 8]);
        const uint32_t kv_dst1 = smem_u32(&sm.vall[0][MEM_ + (ct >> 4)][(ct & 15) * 8]);
        auto prefetch_kv = [&](int s, int buf) {
            if (ct == 0) {
                const unsigned* cp = g_xcnt + h * NSEG_ + s;
                unsigned v; int n = 0;
                do { asm volatile("ld.acquire.gpu.global.u32 %0, [%1];" : "=r"(v) : "l"(cp) : "memory"); } while (v < 48u && ++n < SPIN_LIMIT);
            }
            bar_sync(BAR_CTL, 128);
            const bf16* src = kv_src + (size_t)s * SEG_ * (3 * HD_);
#pragma unroll
            for (int j = 0; j < 4; j++) {
                cp_async16(kv_dst0 + buf * KV_BUF + j * (8 * HL * 2), src + (size_t)j * 8 * (3 * HD_));
                cp_async16(kv_dst1 + buf * KV_BUF + j * (8 * HL * 2), src + (size_t)j * 8 * (3 * HD_) + HD_);
            }
            cp_async_commit();
        };
        const float4* acc_src = reinterpret_cast<const float4*>(g_acc) + ct;
        const uint32_t acc_dst = smem_u32(&sm.mem[(ct & 1) * 4][ct >> 1]);
        const uint4* hx_base = reinterpret_cast<const uint4*>(g_hx) + h * 1024;
        const int hx_rq = ct & 63, hx_half = ct >> 6;
        const uint4* hx_src = hx_base + hx_half * 64 + hx_rq;
        const uint32_t hx_col = (hx_rq & 7) * 8, hx_r = hx_rq >> 3;
        const uint32_t hx_dstA = (hx_half == 0 ? smem_u32(&sm.qm[hx_r][0]) : smem_u32(&sm.kall[0][hx_r][0])) + hx_col;
        const uint32_t hx_dstB = smem_u32(&sm.vall[0][hx_r][0]) + hx_col;
        const uint4* hx_probe = hx_base + (lane >> 3) * 256 + ((lane & 7) % 3) * 64 + (lane & 7) * 8 + 3;
        const int pb_r = ct >> 4, pb_pr = ct & 15;
        uint2* pb_dst = g_hx + (h * 1024 + c * 256 + pb_r * 8) * 2 + pb_pr;
        const float* pb_src = &sm.red[pb_pr >> 3][(pb_pr & 7) * 16 + pb_r];
        bf16* pb_k = g_kmem + (size_t)pb_r * HD_ + h * DH_ + c * 32 + pb_pr * 2;
        bf16* pb_v = g_vmem + (size_t)pb_r * HD_ + h * DH_ + c * 32 + pb_pr * 2;
        const uint32_t qa = smem_u32(&sm.qm[lane & 15][(lane >> 4) * 8]);
        const uint32_t kb0 = smem_u32(&sm.kall[0][cw * 8 + (lane & 7)][(lane >> 3) * 8]);
        const uint32_t va0 = smem_u32(&sm.vall[0][(lane & 7) + ((lane >> 4) & 1) * 8][cw * 32 + ((lane >> 3) & 1) * 8]);
        const uint32_t pbaddr = smem_u32(&sm.p[lane & 7][((lane >> 3) & 1) * 8]);
        const uint32_t ob = smem_u32(&sm.om[lane & 7][kh * 64 + (lane >> 3) * 8]);
        float* acc_dst_g = g_acc + (c * 160 + mg * 80 + g) * 8 + 2 * t;

        prefetch_kv(0, 0);
        for (int s = 0; s < NSEG_; s++) {
            const int buf = s & 1;
            const uint32_t flag = s + 1;
            const uint32_t bo = buf * KV_BUF;
            PROF(0);
            if (s == 0) {
                for (int i = ct; i < MEM_ * D_ / 8; i += 128) {
                    int r = i / (D_ / 8), cc = (i % (D_ / 8)) * 8;
                    *reinterpret_cast<uint4*>(&sm.mem[r][cc]) = *reinterpret_cast<const uint4*>(mem0 + r * D_ + cc);
                }
            } else {
                if (ct == 0) {
                    const unsigned* cp = g_cnt + (s - 1) * 32;
                    unsigned v; int n = 0;
                    do { asm volatile("ld.acquire.gpu.global.u32 %0, [%1];" : "=r"(v) : "l"(cp) : "memory"); } while (v < 256u && ++n < SPIN_LIMIT);
                }
                bar_sync(BAR_CTL, 128);
                PROF(1);
                const float4* src = acc_src + (size_t)(s - 1) * (MEM_ * D_ / 4);
                float4 v[10];
#pragma unroll
                for (int j = 0; j < 10; j++)
                    asm volatile("ld.relaxed.gpu.global.v4.f32 {%0,%1,%2,%3}, [%4];" : "=f"(v[j].x), "=f"(v[j].y), "=f"(v[j].z), "=f"(v[j].w) : "l"(src + 128 * j) : "memory");
#pragma unroll
                for (int j = 0; j < 10; j++) {
                    uint32_t lo = pack_bf16(v[j].x, v[j].y), hi = pack_bf16(v[j].z, v[j].w);
                    uint32_t d = acc_dst + j * 128;
                    asm volatile("st.shared.u16 [%0], %1;" ::"r"(d), "h"((uint16_t)(lo & 0xffff)) : "memory");
                    asm volatile("st.shared.u16 [%0], %1;" ::"r"(d + MEMS_LD * 2), "h"((uint16_t)(lo >> 16)) : "memory");
                    asm volatile("st.shared.u16 [%0], %1;" ::"r"(d + MEMS_LD * 4), "h"((uint16_t)(hi & 0xffff)) : "memory");
                    asm volatile("st.shared.u16 [%0], %1;" ::"r"(d + MEMS_LD * 6), "h"((uint16_t)(hi >> 16)) : "memory");
                }
            }
            bar_arrive(BAR_MEM, RT);
            PROF(2);
            bar_sync(BAR_RED, RT);
            PROF(3);
            {
                uint32_t pk0 = pack_bf16(pb_src[0] + pb_src[768], pb_src[8] + pb_src[768 + 8]);
                uint32_t pk1 = pack_bf16(pb_src[256] + pb_src[1024], pb_src[256 + 8] + pb_src[1024 + 8]);
                uint32_t pk2 = pack_bf16(pb_src[512] + pb_src[1280], pb_src[512 + 8] + pb_src[1280 + 8]);
                st_relaxed_v2(pb_dst, pk0, flag);
                st_relaxed_v2(pb_dst + 128, pk1, flag);
                st_relaxed_v2(pb_dst + 256, pk2, flag);
                *reinterpret_cast<uint32_t*>(pb_k + (size_t)s * (MEM_ * HD_)) = pk1;
                *reinterpret_cast<uint32_t*>(pb_v + (size_t)s * (MEM_ * HD_)) = pk2;
            }
            if (s == NSEG_ - 1) break;
            PROF(4);
            if (cw == 0) (void)poll_ll(hx_probe, flag);
            bar_sync(BAR_CTL, 128);
            PROF(5);
            {
                uint4 v[8];
#pragma unroll
                for (int j = 0; j < 4; j++) v[j] = ld_relaxed_v4(hx_src + j * 256);
                if (hx_half == 0) {
#pragma unroll
                    for (int j = 0; j < 4; j++) v[4 + j] = ld_relaxed_v4(hx_src + j * 256 + 128);
                }
#pragma unroll
                for (int j = 0; j < 4; j++) {
                    if (v[j].y != flag || v[j].w != flag) v[j] = poll_ll(hx_src + j * 256, flag);
                    sts64(hx_dstA + j * 64 + (hx_half ? bo : 0), v[j].x, v[j].z);
                }
                if (hx_half == 0) {
#pragma unroll
                    for (int j = 0; j < 4; j++) {
                        if (v[4 + j].y != flag || v[4 + j].w != flag) v[4 + j] = poll_ll(hx_src + j * 256 + 128, flag);
                        sts64(hx_dstB + j * 64 + bo, v[4 + j].x, v[4 + j].z);
                    }
                }
            }
            cp_async_wait<0>();
            bar_sync(BAR_CTL, 128);
            PROF(6);
            {
                uint32_t a[8][4], b[4][4], b2[4][4];
#pragma unroll
                for (int kk = 0; kk < 4; kk++) ldsm_x4(b[kk], kb0 + bo + kk * 64);
                if (cw == 0) {
#pragma unroll
                    for (int kk = 0; kk < 4; kk++) ldsm_x4(b2[kk], kb0 + bo + 32 * HL * 2 + kk * 64);
                }
#pragma unroll
                for (int kk = 0; kk < 8; kk++) ldsm_x4(a[kk], qa + kk * 32);
                float s0[4] = {0.f, 0.f, 0.f, 0.f}, s1[4] = {0.f, 0.f, 0.f, 0.f};
#pragma unroll
                for (int kk = 0; kk < 4; kk++) { mma16816(s0, a[2 * kk], b[kk][0], b[kk][1]); mma16816(s1, a[2 * kk + 1], b[kk][2], b[kk][3]); }
                const float scale = 0.08838834764831845f;
                *reinterpret_cast<float2*>(&sm.sc[g][cw * 8 + 2 * t]) =
                    make_float2(rbf(rbf(s0[0] + s1[0]) * scale), rbf(rbf(s0[1] + s1[1]) * scale));
                if (cw == 0) {
                    float u0[4] = {0.f, 0.f, 0.f, 0.f}, u1[4] = {0.f, 0.f, 0.f, 0.f};
#pragma unroll
                    for (int kk = 0; kk < 4; kk++) { mma16816(u0, a[2 * kk], b2[kk][0], b2[kk][1]); mma16816(u1, a[2 * kk + 1], b2[kk][2], b2[kk][3]); }
                    *reinterpret_cast<float2*>(&sm.sc[g][32 + 2 * t]) =
                        make_float2(rbf(rbf(u0[0] + u1[0]) * scale), rbf(rbf(u0[1] + u1[1]) * scale));
                }
            }
            bar_sync(BAR_CTL, 128);
            {
                float v0 = sm.sc[cw][lane], v1 = (lane < 8) ? sm.sc[cw][32 + lane] : -INFINITY;
                float y0 = sm.sc[cw + 4][lane], y1 = (lane < 8) ? sm.sc[cw + 4][32 + lane] : -INFINITY;
                float mx = fmaxf(v0, v1), my = fmaxf(y0, y1);
#pragma unroll
                for (int o = 16; o; o >>= 1) { mx = fmaxf(mx, __shfl_xor_sync(0xffffffffu, mx, o)); my = fmaxf(my, __shfl_xor_sync(0xffffffffu, my, o)); }
                float e0 = __expf(v0 - mx), e1 = (lane < 8) ? __expf(v1 - mx) : 0.f;
                float f0 = __expf(y0 - my), f1 = (lane < 8) ? __expf(y1 - my) : 0.f;
                float sx = e0 + e1, sy = f0 + f1;
#pragma unroll
                for (int o = 16; o; o >>= 1) { sx += __shfl_xor_sync(0xffffffffu, sx, o); sy += __shfl_xor_sync(0xffffffffu, sy, o); }
                float ix = 1.0f / sx, iy = 1.0f / sy;
                sm.p[cw][lane] = __float2bfloat16_rn(e0 * ix);
                sm.p[cw + 4][lane] = __float2bfloat16_rn(f0 * iy);
                if (lane < 8) { sm.p[cw][32 + lane] = __float2bfloat16_rn(e1 * ix); sm.p[cw + 4][32 + lane] = __float2bfloat16_rn(f1 * iy); }
            }
            bar_sync(BAR_CTL, 128);
            PROF(7);
            {
                uint32_t a[2][3][4], b[3][2];
#pragma unroll
                for (int kt = 0; kt < 3; kt++) {
                    asm volatile("ldmatrix.sync.aligned.m8n8.x2.shared.b16 {%0,%1}, [%2];" : "=r"(b[kt][0]), "=r"(b[kt][1]) : "r"(pbaddr + kt * 32));
                    ldsm_x4_t(a[0][kt], va0 + bo + kt * 16 * HL * 2);
                    ldsm_x4_t(a[1][kt], va0 + bo + kt * 16 * HL * 2 + 32);
                }
#pragma unroll
                for (int m = 0; m < 2; m++) {
                    float o[4] = {0.f, 0.f, 0.f, 0.f};
#pragma unroll
                    for (int kt = 0; kt < 3; kt++) mma16816(o, a[m][kt], b[kt][0], b[kt][1]);
                    int d0 = cw * 32 + m * 16 + g;
                    sm.om[2 * t][d0] = __float2bfloat16_rn(o[0]);
                    sm.om[2 * t + 1][d0] = __float2bfloat16_rn(o[1]);
                    sm.om[2 * t][d0 + 8] = __float2bfloat16_rn(o[2]);
                    sm.om[2 * t + 1][d0 + 8] = __float2bfloat16_rn(o[3]);
                }
            }
            bar_sync(BAR_CTL, 128);
            PROF(8);
            {
                float acc[5][4];
#pragma unroll
                for (int mi = 0; mi < 5; mi++) { acc[mi][0] = acc[mi][1] = acc[mi][2] = acc[mi][3] = 0.f; }
                uint32_t b[2][4];
                ldsm_x4(b[0], ob); ldsm_x4(b[1], ob + 64);
#pragma unroll
                for (int ki = 0; ki < 4; ki++)
#pragma unroll
                    for (int mi = 0; mi < 5; mi++) mma16816(acc[mi], wf[mi * 4 + ki], b[ki >> 1][(ki & 1) * 2], b[ki >> 1][(ki & 1) * 2 + 1]);
                if (kh == 1) {
#pragma unroll
                    for (int mi = 0; mi < 5; mi++)
                        *reinterpret_cast<float4*>(&sm.wred[mg][mi][lane * 4]) = make_float4(acc[mi][0], acc[mi][1], acc[mi][2], acc[mi][3]);
                }
                bar_sync(BAR_WO + mg, 64);
                if (kh == 0) {
                    float* dst = acc_dst_g + (size_t)s * (MEM_ * D_);
#pragma unroll
                    for (int mi = 0; mi < 5; mi++) {
                        float4 o2 = *reinterpret_cast<float4*>(&sm.wred[mg][mi][lane * 4]);
                        asm volatile("red.global.add.v2.f32 [%0], {%1,%2};" ::"l"(dst + mi * 128), "f"(acc[mi][0] + o2.x), "f"(acc[mi][1] + o2.y) : "memory");
                        asm volatile("red.global.add.v2.f32 [%0], {%1,%2};" ::"l"(dst + mi * 128 + 64), "f"(acc[mi][2] + o2.z), "f"(acc[mi][3] + o2.w) : "memory");
                    }
                    __threadfence();
                    __syncwarp();
                    if (lane == 0) atomicAdd(&g_cnt[s * 32], 1u);
                }
            }
            bar_arrive(BAR_GO, RT);
            PROF(9);
            prefetch_kv(s + 1, buf ^ 1);
            PROF(10);
        }
    }
}

__global__ void __launch_bounds__(128)
attn_x_kernel() {
    __shared__ __align__(16) bf16 sq[32][HL], sk[48][HL], sv[48][HL];
    const int s = blockIdx.x >> 5, h = blockIdx.x & 31;
    const int tid = threadIdx.x, lane = tid & 31, w = tid >> 5, g = lane >> 2, t = lane & 3;
    for (int i = tid; i < (32 + 40 + 40) * 16; i += 128) {
        int r = i >> 4, ch = i & 15;
        const bf16* src; bf16* dst;
        if (r < 32) { src = g_qkv + (size_t)(s * SEG_ + r) * (3 * HD_) + h * DH_; dst = sq[r]; }
        else if (r < 72) { int rr = r - 32; dst = sk[rr];
            src = rr < 8 ? g_kmem + ((size_t)s * MEM_ + rr) * HD_ + h * DH_ : g_qkv + (size_t)(s * SEG_ + rr - 8) * (3 * HD_) + HD_ + h * DH_; }
        else { int rr = r - 72; dst = sv[rr];
            src = rr < 8 ? g_vmem + ((size_t)s * MEM_ + rr) * HD_ + h * DH_ : g_qkv + (size_t)(s * SEG_ + rr - 8) * (3 * HD_) + 2 * HD_ + h * DH_; }
        cp_async16(smem_u32(dst + ch * 8), src + ch * 8);
    }
    cp_async_commit();
    for (int i = tid; i < 8 * 16; i += 128) *reinterpret_cast<uint4*>(&sv[40 + (i >> 4)][(i & 15) * 8]) = make_uint4(0, 0, 0, 0);
    cp_async_wait<0>();
    __syncthreads();
    const int rh = w & 1, dhh = w >> 1;
    float sc[5][4];
#pragma unroll
    for (int n = 0; n < 5; n++) sc[n][0] = sc[n][1] = sc[n][2] = sc[n][3] = 0.f;
#pragma unroll
    for (int kk = 0; kk < 8; kk++) {
        uint32_t a[4];
        ldsm_x4(a, smem_u32(&sq[rh * 16 + (lane & 15)][kk * 16 + (lane >> 4) * 8]));
#pragma unroll
        for (int n = 0; n < 5; n++) {
            uint32_t b[2];
            asm volatile("ldmatrix.sync.aligned.m8n8.x2.shared.b16 {%0,%1}, [%2];" : "=r"(b[0]), "=r"(b[1])
                         : "r"(smem_u32(&sk[n * 8 + (lane & 7)][kk * 16 + ((lane >> 3) & 1) * 8])));
            mma16816(sc[n], a, b[0], b[1]);
        }
    }
    const float scale = 0.08838834764831845f;
    float mx[2] = {-INFINITY, -INFINITY};
#pragma unroll
    for (int n = 0; n < 5; n++)
#pragma unroll
        for (int e = 0; e < 4; e++) {
            int row = rh * 16 + g + (e >> 1) * 8, key = n * 8 + 2 * t + (e & 1);
            float v = rbf(rbf(sc[n][e]) * scale);
            if (key > row + MEM_) v = -INFINITY;
            sc[n][e] = v;
            mx[e >> 1] = fmaxf(mx[e >> 1], v);
        }
#pragma unroll
    for (int o = 1; o < 4; o <<= 1) { mx[0] = fmaxf(mx[0], __shfl_xor_sync(0xffffffffu, mx[0], o)); mx[1] = fmaxf(mx[1], __shfl_xor_sync(0xffffffffu, mx[1], o)); }
    float sum[2] = {0.f, 0.f};
#pragma unroll
    for (int n = 0; n < 5; n++)
#pragma unroll
        for (int e = 0; e < 4; e++) { float ev = __expf(sc[n][e] - mx[e >> 1]); sc[n][e] = ev; sum[e >> 1] += ev; }
#pragma unroll
    for (int o = 1; o < 4; o <<= 1) { sum[0] += __shfl_xor_sync(0xffffffffu, sum[0], o); sum[1] += __shfl_xor_sync(0xffffffffu, sum[1], o); }
    float inv[2] = {1.0f / sum[0], 1.0f / sum[1]};
    uint32_t pa[3][4];
#pragma unroll
    for (int kt = 0; kt < 3; kt++) {
        pa[kt][0] = pack_bf16(sc[2 * kt][0] * inv[0], sc[2 * kt][1] * inv[0]);
        pa[kt][1] = pack_bf16(sc[2 * kt][2] * inv[1], sc[2 * kt][3] * inv[1]);
        if (kt < 2) {
            pa[kt][2] = pack_bf16(sc[2 * kt + 1][0] * inv[0], sc[2 * kt + 1][1] * inv[0]);
            pa[kt][3] = pack_bf16(sc[2 * kt + 1][2] * inv[1], sc[2 * kt + 1][3] * inv[1]);
        } else { pa[kt][2] = 0u; pa[kt][3] = 0u; }
    }
#pragma unroll
    for (int n = 0; n < 8; n++) {
        float o[4] = {0.f, 0.f, 0.f, 0.f};
#pragma unroll
        for (int kt = 0; kt < 3; kt++) {
            uint32_t b[2];
            asm volatile("ldmatrix.sync.aligned.m8n8.x2.trans.shared.b16 {%0,%1}, [%2];" : "=r"(b[0]), "=r"(b[1])
                         : "r"(smem_u32(&sv[kt * 16 + (lane & 15)][dhh * 64 + n * 8])));
            mma16816(o, pa[kt], b[0], b[1]);
        }
        int row = s * SEG_ + rh * 16 + g;
        bf16* dst = g_o + (size_t)row * HD_ + h * DH_ + dhh * 64 + n * 8 + 2 * t;
        *reinterpret_cast<uint32_t*>(dst) = pack_bf16(o[0], o[1]);
        *reinterpret_cast<uint32_t*>(dst + 8 * HD_) = pack_bf16(o[2], o[3]);
    }
}

typedef CUresult (*PFN_encodeTiled)(CUtensorMap*, CUtensorMapDataType, cuuint32_t, void*, const cuuint64_t*,
                                    const cuuint64_t*, const cuuint32_t*, const cuuint32_t*, CUtensorMapInterleave,
                                    CUtensorMapSwizzle, CUtensorMapL2promotion, CUtensorMapFloatOOBfill);
static PFN_encodeTiled p_encode = nullptr;

static CUtensorMap make_map(const void* ptr, uint64_t rows, uint64_t cols, uint64_t ld, uint32_t box_rows) {
    CUtensorMap m;
    cuuint64_t dims[2] = {cols, rows};
    cuuint64_t strides[1] = {ld * 2};
    cuuint32_t box[2] = {64, box_rows};
    cuuint32_t es[2] = {1, 1};
    p_encode(&m, CU_TENSOR_MAP_DATA_TYPE_BFLOAT16, 2, const_cast<void*>(ptr), dims, strides, box, es,
             CU_TENSOR_MAP_INTERLEAVE_NONE, CU_TENSOR_MAP_SWIZZLE_128B, CU_TENSOR_MAP_L2_PROMOTION_L2_128B,
             CU_TENSOR_MAP_FLOAT_OOB_FILL_NONE);
    return m;
}

template <int BN, int EPI>
static void launch_gemm(const CUtensorMap& a, const CUtensorMap& b0, const CUtensorMap& b1, const CUtensorMap& b2,
                        int nPerB, int M, int N, int K, EpiParams ep, cudaStream_t st) {
    constexpr int STAGE = 16384 + (BN / 64) * 8192;
    constexpr int NST = (200 * 1024) / STAGE;
    constexpr int SMEM = NST * STAGE + 1024;
    cudaFuncSetAttribute(gemm_kernel<BN, EPI>, cudaFuncAttributeMaxDynamicSharedMemorySize, SMEM);
    dim3 grid((N + BN - 1) / BN, M / 128);
    gemm_kernel<BN, EPI><<<grid, 384, SMEM, st>>>(a, b0, b1, b2, nPerB, N, K, ep);
}

extern "C" void kernel_launch(void* const* d_in, const int* in_sizes, int n_in, void* d_out, int out_size) {
    const bf16* x    = (const bf16*)d_in[0];
    const bf16* mem0 = (const bf16*)d_in[1];
    const bf16* Wq   = (const bf16*)d_in[2];
    const bf16* Wk   = (const bf16*)d_in[3];
    const bf16* Wv   = (const bf16*)d_in[4];
    const bf16* Wo   = (const bf16*)d_in[5];
    const bf16* w_in  = (const bf16*)d_in[8];
    const bf16* w_sp  = (const bf16*)d_in[9];
    const bf16* b_sp  = (const bf16*)d_in[10];
    const bf16* w_out = (const bf16*)d_in[11];
    bf16* out = (bf16*)d_out;
    cudaStream_t st = cudaStreamPerThread;

    if (!p_encode) {
        cudaDriverEntryPointQueryResult qr;
        cudaGetDriverEntryPoint("cuTensorMapEncodeTiled", (void**)&p_encode, cudaEnableDefault, &qr);
    }
    void *p_xn, *p_qkv, *p_z, *p_zg, *p_gate, *p_o, *p_acc, *p_cnt, *p_hx;
    cudaGetSymbolAddress(&p_xn, g_xn); cudaGetSymbolAddress(&p_qkv, g_qkv); cudaGetSymbolAddress(&p_z, g_z);
    cudaGetSymbolAddress(&p_zg, g_zg); cudaGetSymbolAddress(&p_gate, g_gate); cudaGetSymbolAddress(&p_o, g_o);
    cudaGetSymbolAddress(&p_acc, g_acc); cudaGetSymbolAddress(&p_cnt, g_cnt); cudaGetSymbolAddress(&p_hx, g_hx);

    CUtensorMap mA_xn  = make_map(p_xn, S_, D_, D_, 128);
    CUtensorMap mA_wsp = make_map(w_sp, S_, S_, S_, 128);
    CUtensorMap mA_zg  = make_map(p_zg, S_, FH_, FH_, 128);
    CUtensorMap mA_o   = make_map(p_o, S_, HD_, HD_, 128);
    CUtensorMap mB_wq  = make_map(Wq, D_, HD_, HD_, 64);
    CUtensorMap mB_wk  = make_map(Wk, D_, HD_, HD_, 64);
    CUtensorMap mB_wv  = make_map(Wv, D_, HD_, HD_, 64);
    CUtensorMap mB_win = make_map(w_in, D_, F_, F_, 64);
    CUtensorMap mB_z2  = make_map((bf16*)p_z + FH_, S_, FH_, F_, 64);
    CUtensorMap mB_wout = make_map(w_out, FH_, D_, D_, 64);
    CUtensorMap mB_wo  = make_map(Wo, HD_, D_, D_, 64);

    cudaMemsetAsync(p_acc, 0, sizeof(float) * NSEG_ * MEM_ * D_, st);
    cudaMemsetAsync(p_cnt, 0, sizeof(unsigned) * NSEG_ * 32, st);
    void* p_xcnt; cudaGetSymbolAddress(&p_xcnt, g_xcnt);
    cudaMemsetAsync(p_xcnt, 0, sizeof(unsigned) * H_ * NSEG_, st);
    cudaMemsetAsync(p_hx, 0, sizeof(uint2) * H_ * 4 * 256 * 2, st);

    ln_kernel<<<S_ / 8, 256, 0, st>>>(x);
    { EpiParams ep{(bf16*)p_z, F_, nullptr, nullptr}; launch_gemm<128, EPI_GELU>(mA_xn, mB_win, mB_win, mB_win, 1 << 20, S_, F_, D_, ep, st); }
    ln2_kernel<<<S_ / 8, 256, 0, st>>>();
    { EpiParams ep{(bf16*)p_zg, FH_, (const bf16*)p_z, b_sp}; launch_gemm<128, EPI_SP>(mA_wsp, mB_z2, mB_z2, mB_z2, 1 << 20, S_, FH_, S_, ep, st); }
    { EpiParams ep{(bf16*)p_gate, D_, nullptr, nullptr}; launch_gemm<128, EPI_SILU>(mA_zg, mB_wout, mB_wout, mB_wout, 1 << 20, S_, D_, FH_, ep, st); }
    constexpr int RSM = (int)sizeof(RecurSmem) > 16 * 10240 ? (int)sizeof(RecurSmem) : 16 * 10240;
    cudaFuncSetAttribute(recur_kernel, cudaFuncAttributeMaxDynamicSharedMemorySize, RSM);
    recur_kernel<<<128, RT, RSM, st>>>(mem0, Wq, Wk, Wv, Wo);
    attn_x_kernel<<<NSEG_ * H_, 128, 0, st>>>();
    { EpiParams ep{out, D_, x, (const bf16*)p_gate}; launch_gemm<128, EPI_FINAL>(mA_o, mB_wo, mB_wo, mB_wo, 1 << 20, S_, D_, HD_, ep, st); }
}
```

```cpp
#include <cuda_runtime.h>
#include <cuda_bf16.h>
#include <cuda.h>
#include <stdint.h>

typedef __nv_bfloat16 bf16;

constexpr int S_   = 2048;
constexpr int D_   = 640;
constexpr int H_   = 32;
constexpr int DH_  = 128;
constexpr int MEM_ = 8;
constexpr int SEG_ = 32;
constexpr int NSEG_ = S_ / SEG_;
constexpr int HD_  = H_ * DH_;
constexpr int F_   = 1728;
constexpr int FH_  = 864;

__device__ bf16 g_xn[S_ * D_];
__device__ bf16 g_qkv[(size_t)S_ * 3 * HD_];
__device__ bf16 g_z[S_ * F_];
__device__ bf16 g_zg[S_ * FH_];
__device__ bf16 g_gate[S_ * D_];
__device__ bf16 g_kmem[NSEG_ * MEM_ * HD_];
__device__ bf16 g_vmem[NSEG_ * MEM_ * HD_];
__device__ bf16 g_o[(size_t)S_ * HD_];
__device__ float g_acc[NSEG_ * MEM_ * D_];
__device__ unsigned g_cnt[NSEG_ * 32];
__device__ unsigned g_xcnt[H_ * NSEG_];
__device__ uint2 g_hx[H_ * 4 * 256 * 2];

__device__ __forceinline__ uint32_t smem_u32(const void* p) { return (uint32_t)__cvta_generic_to_shared(p); }
__device__ __forceinline__ float bf2f(bf16 v) { return __bfloat162float(v); }
__device__ __forceinline__ float rbf(float v) { return __bfloat162float(__float2bfloat16_rn(v)); }
__device__ __forceinline__ uint32_t pack_bf16(float lo, float hi) {
    __nv_bfloat162 t = __floats2bfloat162_rn(lo, hi);
    return *reinterpret_cast<uint32_t*>(&t);
}
__device__ __forceinline__ float lo_f(uint32_t u) { return __uint_as_float(u << 16); }
__device__ __forceinline__ float hi_f(uint32_t u) { return __uint_as_float(u & 0xffff0000u); }

__device__ __forceinline__ void mbar_init(uint32_t bar, uint32_t cnt) {
    asm volatile("mbarrier.init.shared.b64 [%0], %1;" ::"r"(bar), "r"(cnt));
}
__device__ __forceinline__ void mbar_expect_tx(uint32_t bar, uint32_t bytes) {
    asm volatile("mbarrier.arrive.expect_tx.shared.b64 _, [%0], %1;" ::"r"(bar), "r"(bytes) : "memory");
}
__device__ __forceinline__ void mbar_arrive(uint32_t bar) {
    asm volatile("mbarrier.arrive.shared.b64 _, [%0];" ::"r"(bar) : "memory");
}
__device__ __forceinline__ void mbar_wait(uint32_t bar, uint32_t parity) {
    asm volatile(
        "{\n .reg .pred p;\n"
        "WAIT_%=:\n"
        " mbarrier.try_wait.parity.shared.b64 p, [%0], %1;\n"
        " @p bra DONE_%=;\n"
        " bra WAIT_%=;\n"
        "DONE_%=:\n}\n" ::"r"(bar), "r"(parity) : "memory");
}
__device__ __forceinline__ void tma_load_2d(uint32_t dst, const CUtensorMap* tm, uint32_t bar, int c0, int c1) {
    asm volatile(
        "cp.async.bulk.tensor.2d.shared::cluster.global.mbarrier::complete_tx::bytes [%0], [%1, {%3, %4}], [%2];"
        ::"r"(dst), "l"(tm), "r"(bar), "r"(c0), "r"(c1) : "memory");
}
__device__ __forceinline__ void wgmma_fence() { asm volatile("wgmma.fence.sync.aligned;" ::: "memory"); }
__device__ __forceinline__ void wgmma_commit() { asm volatile("wgmma.commit_group.sync.aligned;" ::: "memory"); }
template <int N> __device__ __forceinline__ void wgmma_wait() { asm volatile("wgmma.wait_group.sync.aligned %0;" ::"n"(N) : "memory"); }

__device__ __forceinline__ uint64_t make_desc(uint32_t addr, uint32_t lbo, uint32_t sbo) {
    return (uint64_t)((addr & 0x3FFFF) >> 4) | ((uint64_t)(lbo >> 4) << 16) | ((uint64_t)(sbo >> 4) << 32) | (1ull << 62);
}

template <int N> struct Wgmma;
template <> struct Wgmma<128> {
    static __device__ __forceinline__ void mma(float* d, uint64_t da, uint64_t db, int sd) {
        asm volatile(
            "{\n.reg .pred p;\nsetp.ne.b32 p, %66, 0;\n"
            "wgmma.mma_async.sync.aligned.m64n128k16.f32.bf16.bf16 "
            "{%0,%1,%2,%3,%4,%5,%6,%7,%8,%9,%10,%11,%12,%13,%14,%15,"
            "%16,%17,%18,%19,%20,%21,%22,%23,%24,%25,%26,%27,%28,%29,%30,%31,"
            "%32,%33,%34,%35,%36,%37,%38,%39,%40,%41,%42,%43,%44,%45,%46,%47,"
            "%48,%49,%50,%51,%52,%53,%54,%55,%56,%57,%58,%59,%60,%61,%62,%63},"
            "%64,%65,p,1,1,0,1;\n}\n"
            : "+f"(d[0]), "+f"(d[1]), "+f"(d[2]), "+f"(d[3]), "+f"(d[4]), "+f"(d[5]), "+f"(d[6]), "+f"(d[7]),
              "+f"(d[8]), "+f"(d[9]), "+f"(d[10]), "+f"(d[11]), "+f"(d[12]), "+f"(d[13]), "+f"(d[14]), "+f"(d[15]),
              "+f"(d[16]), "+f"(d[17]), "+f"(d[18]), "+f"(d[19]), "+f"(d[20]), "+f"(d[21]), "+f"(d[22]), "+f"(d[23]),
              "+f"(d[24]), "+f"(d[25]), "+f"(d[26]), "+f"(d[27]), "+f"(d[28]), "+f"(d[29]), "+f"(d[30]), "+f"(d[31]),
              "+f"(d[32]), "+f"(d[33]), "+f"(d[34]), "+f"(d[35]), "+f"(d[36]), "+f"(d[37]), "+f"(d[38]), "+f"(d[39]),
              "+f"(d[40]), "+f"(d[41]), "+f"(d[42]), "+f"(d[43]), "+f"(d[44]), "+f"(d[45]), "+f"(d[46]), "+f"(d[47]),
              "+f"(d[48]), "+f"(d[49]), "+f"(d[50]), "+f"(d[51]), "+f"(d[52]), "+f"(d[53]), "+f"(d[54]), "+f"(d[55]),
              "+f"(d[56]), "+f"(d[57]), "+f"(d[58]), "+f"(d[59]), "+f"(d[60]), "+f"(d[61]), "+f"(d[62]), "+f"(d[63])
            : "l"(da), "l"(db), "r"(sd));
    }
};
template <> struct Wgmma<192> {
    static __device__ __forceinline__ void mma(float* d, uint64_t da, uint64_t db, int sd) {
        asm volatile(
            "{\n.reg .pred p;\nsetp.ne.b32 p, %98, 0;\n"
            "wgmma.mma_async.sync.aligned.m64n192k16.f32.bf16.bf16 "
            "{%0,%1,%2,%3,%4,%5,%6,%7,%8,%9,%10,%11,%12,%13,%14,%15,"
            "%16,%17,%18,%19,%20,%21,%22,%23,%24,%25,%26,%27,%28,%29,%30,%31,"
            "%32,%33,%34,%35,%36,%37,%38,%39,%40,%41,%42,%43,%44,%45,%46,%47,"
            "%48,%49,%50,%51,%52,%53,%54,%55,%56,%57,%58,%59,%60,%61,%62,%63,"
            "%64,%65,%66,%67,%68,%69,%70,%71,%72,%73,%74,%75,%76,%77,%78,%79,"
            "%80,%81,%82,%83,%84,%85,%86,%87,%88,%89,%90,%91,%92,%93,%94,%95},"
            "%96,%97,p,1,1,0,1;\n}\n"
            : "+f"(d[0]), "+f"(d[1]), "+f"(d[2]), "+f"(d[3]), "+f"(d[4]), "+f"(d[5]), "+f"(d[6]), "+f"(d[7]),
              "+f"(d[8]), "+f"(d[9]), "+f"(d[10]), "+f"(d[11]), "+f"(d[12]), "+f"(d[13]), "+f"(d[14]), "+f"(d[15]),
              "+f"(d[16]), "+f"(d[17]), "+f"(d[18]), "+f"(d[19]), "+f"(d[20]), "+f"(d[21]), "+f"(d[22]), "+f"(d[23]),
              "+f"(d[24]), "+f"(d[25]), "+f"(d[26]), "+f"(d[27]), "+f"(d[28]), "+f"(d[29]), "+f"(d[30]), "+f"(d[31]),
              "+f"(d[32]), "+f"(d[33]), "+f"(d[34]), "+f"(d[35]), "+f"(d[36]), "+f"(d[37]), "+f"(d[38]), "+f"(d[39]),
              "+f"(d[40]), "+f"(d[41]), "+f"(d[42]), "+f"(d[43]), "+f"(d[44]), "+f"(d[45]), "+f"(d[46]), "+f"(d[47]),
              "+f"(d[48]), "+f"(d[49]), "+f"(d[50]), "+f"(d[51]), "+f"(d[52]), "+f"(d[53]), "+f"(d[54]), "+f"(d[55]),
              "+f"(d[56]), "+f"(d[57]), "+f"(d[58]), "+f"(d[59]), "+f"(d[60]), "+f"(d[61]), "+f"(d[62]), "+f"(d[63]),
              "+f"(d[64]), "+f"(d[65]), "+f"(d[66]), "+f"(d[67]), "+f"(d[68]), "+f"(d[69]), "+f"(d[70]), "+f"(d[71]),
              "+f"(d[72]), "+f"(d[73]), "+f"(d[74]), "+f"(d[75]), "+f"(d[76]), "+f"(d[77]), "+f"(d[78]), "+f"(d[79]),
              "+f"(d[80]), "+f"(d[81]), "+f"(d[82]), "+f"(d[83]), "+f"(d[84]), "+f"(d[85]), "+f"(d[86]), "+f"(d[87]),
              "+f"(d[88]), "+f"(d[89]), "+f"(d[90]), "+f"(d[91]), "+f"(d[92]), "+f"(d[93]), "+f"(d[94]), "+f"(d[95])
            : "l"(da), "l"(db), "r"(sd));
    }
};

template <> struct Wgmma<256> {
    static __device__ __forceinline__ void mma(float* d, uint64_t da, uint64_t db, int sd) {
        asm volatile(
            "{\n.reg .pred p;\nsetp.ne.b32 p, %130, 0;\n"
            "wgmma.mma_async.sync.aligned.m64n256k16.f32.bf16.bf16 "
            "{%0,%1,%2,%3,%4,%5,%6,%7,%8,%9,%10,%11,%12,%13,%14,%15,%16,%17,%18,%19,%20,%21,%22,%23,%24,%25,%26,%27,%28,%29,%30,%31,%32,%33,%34,%35,%36,%37,%38,%39,%40,%41,%42,%43,%44,%45,%46,%47,%48,%49,%50,%51,%52,%53,%54,%55,%56,%57,%58,%59,%60,%61,%62,%63,%64,%65,%66,%67,%68,%69,%70,%71,%72,%73,%74,%75,%76,%77,%78,%79,%80,%81,%82,%83,%84,%85,%86,%87,%88,%89,%90,%91,%92,%93,%94,%95,%96,%97,%98,%99,%100,%101,%102,%103,%104,%105,%106,%107,%108,%109,%110,%111,%112,%113,%114,%115,%116,%117,%118,%119,%120,%121,%122,%123,%124,%125,%126,%127},"
            "%128,%129,p,1,1,0,1;\n}\n"
            : "+f"(d[0]), "+f"(d[1]), "+f"(d[2]), "+f"(d[3]), "+f"(d[4]), "+f"(d[5]), "+f"(d[6]), "+f"(d[7]), "+f"(d[8]), "+f"(d[9]), "+f"(d[10]), "+f"(d[11]), "+f"(d[12]), "+f"(d[13]), "+f"(d[14]), "+f"(d[15]), "+f"(d[16]), "+f"(d[17]), "+f"(d[18]), "+f"(d[19]), "+f"(d[20]), "+f"(d[21]), "+f"(d[22]), "+f"(d[23]), "+f"(d[24]), "+f"(d[25]), "+f"(d[26]), "+f"(d[27]), "+f"(d[28]), "+f"(d[29]), "+f"(d[30]), "+f"(d[31]), "+f"(d[32]), "+f"(d[33]), "+f"(d[34]), "+f"(d[35]), "+f"(d[36]), "+f"(d[37]), "+f"(d[38]), "+f"(d[39]), "+f"(d[40]), "+f"(d[41]), "+f"(d[42]), "+f"(d[43]), "+f"(d[44]), "+f"(d[45]), "+f"(d[46]), "+f"(d[47]), "+f"(d[48]), "+f"(d[49]), "+f"(d[50]), "+f"(d[51]), "+f"(d[52]), "+f"(d[53]), "+f"(d[54]), "+f"(d[55]), "+f"(d[56]), "+f"(d[57]), "+f"(d[58]), "+f"(d[59]), "+f"(d[60]), "+f"(d[61]), "+f"(d[62]), "+f"(d[63]), "+f"(d[64]), "+f"(d[65]), "+f"(d[66]), "+f"(d[67]), "+f"(d[68]), "+f"(d[69]), "+f"(d[70]), "+f"(d[71]), "+f"(d[72]), "+f"(d[73]), "+f"(d[74]), "+f"(d[75]), "+f"(d[76]), "+f"(d[77]), "+f"(d[78]), "+f"(d[79]), "+f"(d[80]), "+f"(d[81]), "+f"(d[82]), "+f"(d[83]), "+f"(d[84]), "+f"(d[85]), "+f"(d[86]), "+f"(d[87]), "+f"(d[88]), "+f"(d[89]), "+f"(d[90]), "+f"(d[91]), "+f"(d[92]), "+f"(d[93]), "+f"(d[94]), "+f"(d[95]), "+f"(d[96]), "+f"(d[97]), "+f"(d[98]), "+f"(d[99]), "+f"(d[100]), "+f"(d[101]), "+f"(d[102]), "+f"(d[103]), "+f"(d[104]), "+f"(d[105]), "+f"(d[106]), "+f"(d[107]), "+f"(d[108]), "+f"(d[109]), "+f"(d[110]), "+f"(d[111]), "+f"(d[112]), "+f"(d[113]), "+f"(d[114]), "+f"(d[115]), "+f"(d[116]), "+f"(d[117]), "+f"(d[118]), "+f"(d[119]), "+f"(d[120]), "+f"(d[121]), "+f"(d[122]), "+f"(d[123]), "+f"(d[124]), "+f"(d[125]), "+f"(d[126]), "+f"(d[127])
            : "l"(da), "l"(db), "r"(sd));
    }
};
template <int W>
__device__ __forceinline__ void ln_row(const bf16* __restrict__ src, bf16* __restrict__ dst, int lane) {
    constexpr int NP = W / 64;
    constexpr int REM = (W / 2) % 32;
    uint32_t v[NP + 1];
    const uint32_t* s32 = reinterpret_cast<const uint32_t*>(src);
    float sum = 0.f;
#pragma unroll
    for (int i = 0; i < NP; i++) { v[i] = s32[i * 32 + lane]; sum += lo_f(v[i]) + hi_f(v[i]); }
    if (REM) { v[NP] = (lane < REM) ? s32[NP * 32 + lane] : 0u; if (lane < REM) sum += lo_f(v[NP]) + hi_f(v[NP]); }
#pragma unroll
    for (int o = 16; o; o >>= 1) sum += __shfl_xor_sync(0xffffffffu, sum, o);
    float mean = sum * (1.0f / W);
    float vs = 0.f;
#pragma unroll
    for (int i = 0; i < NP; i++) { float a = lo_f(v[i]) - mean, b = hi_f(v[i]) - mean; vs += a * a + b * b; }
    if (REM && lane < REM) { float a = lo_f(v[NP]) - mean, b = hi_f(v[NP]) - mean; vs += a * a + b * b; }
#pragma unroll
    for (int o = 16; o; o >>= 1) vs += __shfl_xor_sync(0xffffffffu, vs, o);
    float var = rbf(vs * (1.0f / W));
    float mb = rbf(mean);
    float den = rbf(sqrtf(rbf(var + 1e-5f)));
    uint32_t* d32 = reinterpret_cast<uint32_t*>(dst);
#pragma unroll
    for (int i = 0; i < NP; i++) d32[i * 32 + lane] = pack_bf16(rbf(lo_f(v[i]) - mb) / den, rbf(hi_f(v[i]) - mb) / den);
    if (REM && lane < REM) d32[NP * 32 + lane] = pack_bf16(rbf(lo_f(v[NP]) - mb) / den, rbf(hi_f(v[NP]) - mb) / den);
}

__global__ void ln_kernel(const bf16* __restrict__ x) {
    int row = blockIdx.x * 8 + (threadIdx.x >> 5);
    ln_row<D_>(x + (size_t)row * D_, g_xn + (size_t)row * D_, threadIdx.x & 31);
}
__global__ void ln2_kernel() {
    int row = blockIdx.x * 8 + (threadIdx.x >> 5);
    bf16* p = g_z + (size_t)row * F_ + FH_;
    ln_row<FH_>(p, p, threadIdx.x & 31);
}

enum { EPI_STORE = 0, EPI_GELU = 1, EPI_SP = 2, EPI_SILU = 3, EPI_FINAL = 4 };
struct EpiParams {
    bf16* out; int ldo;
    const bf16* aux0;
    const bf16* aux1;
};

__device__ __forceinline__ float gelu_tanh_f(float x) {
    const float k0 = 0.7978845608028654f, k1 = 0.044715f;
    float inner = k0 * (x + k1 * x * x * x);
    return 0.5f * x * (1.0f + tanhf(inner));
}
__device__ __forceinline__ float silu_f(float x) { return x / (1.0f + expf(-x)); }

template <int BN, int EPI>
__global__ void __launch_bounds__(384, 1)
gemm_kernel(const __grid_constant__ CUtensorMap tmA, const __grid_constant__ CUtensorMap tmB0,
            const __grid_constant__ CUtensorMap tmB1, const __grid_constant__ CUtensorMap tmB2,
            int nPerB, int N, int K, EpiParams ep) {
    constexpr int BM = 128, BK = 64;
    constexpr int A_BYTES = BM * BK * 2;
    constexpr int B_BYTES = (BN / 64) * 8192;
    constexpr int STAGE = A_BYTES + B_BYTES;
    constexpr int NST = (200 * 1024) / STAGE;
    constexpr int OLD = BN + 8;
    extern __shared__ __align__(1024) uint8_t smem_raw[];
    uint8_t* smem = (uint8_t*)(((uintptr_t)smem_raw + 1023) & ~(uintptr_t)1023);
    __shared__ __align__(8) uint64_t full_bar[NST], empty_bar[NST];

    const int tid = threadIdx.x, wg = tid >> 7;
    const int m0 = blockIdx.y * BM, n0 = blockIdx.x * BN;
    const int nk = (K + BK - 1) / BK;

    if (tid == 0) {
        for (int i = 0; i < NST; i++) { mbar_init(smem_u32(&full_bar[i]), 1); mbar_init(smem_u32(&empty_bar[i]), 2); }
        asm volatile("fence.mbarrier_init.release.cluster;" ::: "memory");
    }
    __syncthreads();

    if (wg == 0) {
        if (tid == 0) {
            const int bsel = n0 / nPerB;
            const CUtensorMap* tmB = bsel == 0 ? &tmB0 : (bsel == 1 ? &tmB1 : &tmB2);
            const int nb = n0 - bsel * nPerB;
            for (int kt = 0; kt < nk; kt++) {
                int st = kt % NST; uint32_t ph = (kt / NST) & 1;
                mbar_wait(smem_u32(&empty_bar[st]), ph ^ 1);
                uint32_t fb = smem_u32(&full_bar[st]);
                mbar_expect_tx(fb, STAGE);
                uint32_t sa = smem_u32(smem + st * STAGE);
                tma_load_2d(sa, &tmA, fb, kt * BK, m0);
#pragma unroll
                for (int j = 0; j < BN / 64; j++) tma_load_2d(sa + A_BYTES + j * 8192, tmB, fb, nb + j * 64, kt * BK);
            }
        }
    } else {
        const int cw = wg - 1;
        float acc[BN / 2];
        for (int kt = 0; kt < nk; kt++) {
            int st = kt % NST; uint32_t ph = (kt / NST) & 1;
            mbar_wait(smem_u32(&full_bar[st]), ph);
            uint32_t sa = smem_u32(smem + st * STAGE) + cw * 64 * 128;
            uint32_t sb = smem_u32(smem + st * STAGE) + A_BYTES;
            wgmma_fence();
#pragma unroll
            for (int k = 0; k < BK / 16; k++) {
                uint64_t da = make_desc(sa + k * 32, 16, 1024);
                uint64_t db = make_desc(sb + k * 2048, 8192, 1024);
                Wgmma<BN>::mma(acc, da, db, (kt | k) != 0);
            }
            wgmma_commit();
            wgmma_wait<1>();
            if (kt > 0 && (tid & 127) == 0) mbar_arrive(smem_u32(&empty_bar[(kt - 1) % NST]));
        }
        wgmma_wait<0>();
        asm volatile("bar.sync 1, 256;" ::: "memory");
        const int lane = tid & 31, wi = (tid >> 5) & 3, g = lane >> 2, t = lane & 3;
        bf16* stg = reinterpret_cast<bf16*>(smem) + cw * 64 * OLD;
#pragma unroll
        for (int j = 0; j < BN / 8; j++) {
            *reinterpret_cast<uint32_t*>(&stg[(wi * 16 + g) * OLD + j * 8 + 2 * t]) = pack_bf16(acc[4 * j], acc[4 * j + 1]);
            *reinterpret_cast<uint32_t*>(&stg[(wi * 16 + g + 8) * OLD + j * 8 + 2 * t]) = pack_bf16(acc[4 * j + 2], acc[4 * j + 3]);
        }
        asm volatile("bar.sync %0, 128;" ::"r"(2 + cw) : "memory");
        constexpr int CPR = BN / 8;
        const int ltid = tid & 127;
#pragma unroll 4
        for (int i = ltid; i < 64 * CPR; i += 128) {
            int r = i / CPR, ch = i % CPR;
            int row = m0 + cw * 64 + r, col = n0 + ch * 8;
            if (col >= N) continue;
            uint4 v = *reinterpret_cast<const uint4*>(&stg[r * OLD + ch * 8]);
            uint32_t u[4] = {v.x, v.y, v.z, v.w}, o[4];
            if (EPI == EPI_STORE) {
#pragma unroll
                for (int q = 0; q < 4; q++) o[q] = u[q];
            } else if (EPI == EPI_GELU) {
#pragma unroll
                for (int q = 0; q < 4; q++) o[q] = pack_bf16(gelu_tanh_f(lo_f(u[q])), gelu_tanh_f(hi_f(u[q])));
            } else if (EPI == EPI_SP) {
                float bb = bf2f(ep.aux1[row]);
                uint4 z = *reinterpret_cast<const uint4*>(ep.aux0 + (size_t)row * F_ + col);
                uint32_t zz[4] = {z.x, z.y, z.z, z.w};
#pragma unroll
                for (int q = 0; q < 4; q++) o[q] = pack_bf16(lo_f(zz[q]) * rbf(lo_f(u[q]) + bb), hi_f(zz[q]) * rbf(hi_f(u[q]) + bb));
            } else if (EPI == EPI_SILU) {
#pragma unroll
                for (int q = 0; q < 4; q++) o[q] = pack_bf16(silu_f(lo_f(u[q])), silu_f(hi_f(u[q])));
            } else {
                uint4 xv = *reinterpret_cast<const uint4*>(ep.aux0 + (size_t)row * D_ + col);
                uint4 gv = *reinterpret_cast<const uint4*>(ep.aux1 + (size_t)row * D_ + col);
                uint32_t xx[4] = {xv.x, xv.y, xv.z, xv.w}, gg[4] = {gv.x, gv.y, gv.z, gv.w};
#pragma unroll
                for (int q = 0; q < 4; q++)
                    o[q] = pack_bf16(lo_f(xx[q]) + rbf(lo_f(u[q]) * lo_f(gg[q])), hi_f(xx[q]) + rbf(hi_f(u[q]) * hi_f(gg[q])));
            }
            *reinterpret_cast<uint4*>(ep.out + (size_t)row * ep.ldo + col) = make_uint4(o[0], o[1], o[2], o[3]);
        }
    }
}

__device__ __forceinline__ void mma16816(float* c, const uint32_t* a, uint32_t b0, uint32_t b1) {
    asm volatile(
        "mma.sync.aligned.m16n8k16.row.col.f32.bf16.bf16.f32 {%0,%1,%2,%3}, {%4,%5,%6,%7}, {%8,%9}, {%0,%1,%2,%3};"
        : "+f"(c[0]), "+f"(c[1]), "+f"(c[2]), "+f"(c[3])
        : "r"(a[0]), "r"(a[1]), "r"(a[2]), "r"(a[3]), "r"(b0), "r"(b1));
}
__device__ __forceinline__ void ldsm_x4(uint32_t* r, uint32_t addr) {
    asm volatile("ldmatrix.sync.aligned.m8n8.x4.shared.b16 {%0,%1,%2,%3}, [%4];"
                 : "=r"(r[0]), "=r"(r[1]), "=r"(r[2]), "=r"(r[3]) : "r"(addr));
}
__device__ __forceinline__ void ldsm_x4_t(uint32_t* r, uint32_t addr) {
    asm volatile("ldmatrix.sync.aligned.m8n8.x4.trans.shared.b16 {%0,%1,%2,%3}, [%4];"
                 : "=r"(r[0]), "=r"(r[1]), "=r"(r[2]), "=r"(r[3]) : "r"(addr));
}
__device__ __forceinline__ uint4 ld_relaxed_v4(const void* p) {
    uint4 v;
    asm volatile("ld.relaxed.gpu.global.v4.u32 {%0,%1,%2,%3}, [%4];" : "=r"(v.x), "=r"(v.y), "=r"(v.z), "=r"(v.w) : "l"(p) : "memory");
    return v;
}
__device__ __forceinline__ void st_relaxed_v4(void* p, uint32_t a, uint32_t b, uint32_t c, uint32_t d) {
    asm volatile("st.relaxed.gpu.global.v4.u32 [%0], {%1,%2,%3,%4};" ::"l"(p), "r"(a), "r"(b), "r"(c), "r"(d) : "memory");
}
__device__ __forceinline__ void st_relaxed_v2(void* p, uint32_t a, uint32_t b) {
    asm volatile("st.relaxed.gpu.global.v2.u32 [%0], {%1,%2};" ::"l"(p), "r"(a), "r"(b) : "memory");
}
__device__ __forceinline__ void cp_async16(uint32_t dst, const void* src) {
    asm volatile("cp.async.cg.shared.global [%0], [%1], 16;" ::"r"(dst), "l"(src) : "memory");
}
__device__ __forceinline__ void cp_async_commit() { asm volatile("cp.async.commit_group;" ::: "memory"); }
template <int N> __device__ __forceinline__ void cp_async_wait() { asm volatile("cp.async.wait_group %0;" ::"n"(N) : "memory"); }

#define PROF(i) do {} while (0)
constexpr int SPIN_LIMIT = 4000000;

__device__ __forceinline__ uint4 poll_ll(const void* p, uint32_t flag) {
    uint4 v = ld_relaxed_v4(p);
    int n = 0;
    while ((v.y != flag || v.w != flag) && ++n < SPIN_LIMIT) {
        v = ld_relaxed_v4(p);
    }
    return v;
}

constexpr int RT = 512;
constexpr bool FUSE_X = false;
constexpr int MEMS_LD = D_ + 8;
constexpr int HL = DH_ + 8;
struct RecurSmem {
    bf16 mem[MEM_][MEMS_LD];
    bf16 kall[2][48][HL];
    bf16 vall[2][48][HL];
    bf16 qm[16][HL];
    float sc[MEM_][40];
    bf16 p[MEM_][48 + 8];
    bf16 om[MEM_][HL];
    float red[12][16 * 8];
    float wred[2][5][16 * 8];
    bf16 xs[2][SEG_][MEMS_LD];
    float redx[6][4][16 * 8];
    bf16 xo[SEG_][96 + 8];
};

__device__ __forceinline__ void bar_sync(int id, int n) { asm volatile("bar.sync %0, %1;" ::"r"(id), "r"(n) : "memory"); }
__device__ __forceinline__ void bar_arrive(int id, int n) { asm volatile("bar.arrive %0, %1;" ::"r"(id), "r"(n) : "memory"); }
__device__ __forceinline__ void sts64(uint32_t a, uint32_t x, uint32_t y) { asm volatile("st.shared.v2.u32 [%0], {%1,%2};" ::"r"(a), "r"(x), "r"(y) : "memory"); }
__device__ __forceinline__ uint32_t ldg_u16x2(const bf16* p0, const bf16* p1) {
    return (uint32_t)*(const uint16_t*)p0 | ((uint32_t)*(const uint16_t*)p1 << 16);
}
enum { BAR_MEM = 1, BAR_RED = 2, BAR_CTL = 3, BAR_WO = 4, BAR_INIT = 6, BAR_X = 7, BAR_GO = 8 };

__global__ void __launch_bounds__(RT, 1)
recur_kernel(const bf16* __restrict__ mem0, const bf16* __restrict__ Wq, const bf16* __restrict__ Wk,
             const bf16* __restrict__ Wv, const bf16* __restrict__ Wo) {
    extern __shared__ __align__(16) uint8_t smem_raw[];
    RecurSmem& sm = *reinterpret_cast<RecurSmem*>(smem_raw);
    const int tid = threadIdx.x, lane = tid & 31, w = tid >> 5;
    const int g = lane >> 2, t = lane & 3;
    const int h = blockIdx.x >> 2, c = blockIdx.x & 3;

    if (w < 12) {
        asm volatile("setmaxnreg.dec.sync.aligned.u32 104;");
        uint32_t wf[20][4];
        const int mt = w % 6, kh = w / 6;
        {
            const bf16* W = (mt < 2) ? Wq : (mt < 4 ? Wk : Wv);
            int f0 = h * DH_ + c * 32 + (mt & 1) * 16;
            uint32_t stg = smem_u32(smem_raw) + w * 10240;
#pragma unroll 4
            for (int i = lane; i < 640; i += 32)
                cp_async16(stg + i * 16, W + (size_t)(kh * 320 + (i >> 1)) * HD_ + f0 + (i & 1) * 8);
            cp_async_commit(); cp_async_wait<0>(); __syncwarp();
            uint32_t la = stg + ((lane & 7) + ((lane >> 4) & 1) * 8) * 32 + ((lane >> 3) & 1) * 16;
#pragma unroll
            for (int i = 0; i < 20; i++) ldsm_x4_t(wf[i], la + i * 512);
        }
        bar_sync(BAR_INIT, RT);
        const uint32_t base = smem_u32(&sm.mem[lane & 7][kh * 320 + (lane >> 3) * 8]);
        const uint32_t rp = smem_u32(&sm.red[w][g * 8 + 2 * t]);
        const uint32_t xbase0 = smem_u32(&sm.xs[0][lane & 7][kh * 320 + (lane >> 3) * 8]);
        uint32_t xbase = xbase0;
        const uint32_t rxp = smem_u32(&sm.redx[mt][0][lane * 4]);
        auto load_x = [&](int seg) {
            for (int i = tid; i < SEG_ * (D_ / 8); i += 384) {
                int r = i / (D_ / 8), ch = i % (D_ / 8);
                cp_async16(smem_u32(&sm.xs[seg & 1][r][ch * 8]), g_xn + (size_t)(seg * SEG_ + r) * D_ + ch * 8);
            }
            cp_async_commit();
        };
        float acc[4][4];
        auto xhalf = [&](int n0) {
#pragma unroll
            for (int nt = 0; nt < 2; nt++) { acc[n0 + nt][0] = acc[n0 + nt][1] = acc[n0 + nt][2] = acc[n0 + nt][3] = 0.f; }
#pragma unroll
            for (int i = 0; i < 10; i++) {
#pragma unroll
                for (int nt = 0; nt < 2; nt++) {
                    uint32_t b[4];
                    ldsm_x4(b, xbase + (n0 + nt) * (8 * MEMS_LD * 2) + i * 64);
                    mma16816(acc[n0 + nt], wf[2 * i], b[0], b[1]);
                    mma16816(acc[n0 + nt], wf[2 * i + 1], b[2], b[3]);
                }
            }
        };
        auto xworkA = [&](int seg) {
            cp_async_wait<0>();
            bar_sync(BAR_X, 384);
            if (seg + 1 < NSEG_) load_x(seg + 1);
            xbase = xbase0 + (seg & 1) * (SEG_ * MEMS_LD * 2);
            xhalf(0);
        };
        auto xwork = [&](int seg) {
            xhalf(2);
            if (kh == 1) {
#pragma unroll
                for (int nt = 0; nt < 4; nt++)
                    asm volatile("st.shared.v4.f32 [%0], {%1,%2,%3,%4};" ::"r"(rxp + nt * 512), "f"(acc[nt][0]), "f"(acc[nt][1]), "f"(acc[nt][2]), "f"(acc[nt][3]) : "memory");
            }
            bar_sync(BAR_X, 384);
            if (kh == 0) {
#pragma unroll
                for (int nt = 0; nt < 4; nt++) {
                    float4 o;
                    asm volatile("ld.shared.v4.f32 {%0,%1,%2,%3}, [%4];" : "=f"(o.x), "=f"(o.y), "=f"(o.z), "=f"(o.w) : "r"(rxp + nt * 512) : "memory");
                    bf16* d = &sm.xo[nt * 8 + 2 * t][mt * 16 + g];
                    d[0] = __float2bfloat16_rn(acc[nt][0] + o.x);
                    d[104] = __float2bfloat16_rn(acc[nt][1] + o.y);
                    d[8] = __float2bfloat16_rn(acc[nt][2] + o.z);
                    d[104 + 8] = __float2bfloat16_rn(acc[nt][3] + o.w);
                }
            }
            bar_sync(BAR_X, 384);
            {
                int r = tid / 12, ch = tid % 12;
                uint4 v = *reinterpret_cast<const uint4*>(&sm.xo[r][ch * 8]);
                *reinterpret_cast<uint4*>(g_qkv + (size_t)(seg * SEG_ + r) * (3 * HD_) + (ch >> 2) * HD_ + h * DH_ + c * 32 + (ch & 3) * 8) = v;
            }
        };
        auto xsignal = [&](int seg) {
            __threadfence();
            __syncwarp();
            if (lane == 0) atomicAdd(&g_xcnt[h * NSEG_ + seg], 1u);
        };
        if (FUSE_X) {
            load_x(0);
            xworkA(0); xwork(0); xsignal(0);
            xworkA(1); xwork(1); xsignal(1);
        }
        for (int s = 0; s < NSEG_; s++) {
            bar_sync(BAR_MEM, RT);
            float a0[4] = {0.f, 0.f, 0.f, 0.f}, a1[4] = {0.f, 0.f, 0.f, 0.f};
#pragma unroll
            for (int i = 0; i < 10; i++) {
                uint32_t b[4];
                ldsm_x4(b, base + i * 64);
                mma16816(a0, wf[2 * i], b[0], b[1]);
                mma16816(a1, wf[2 * i + 1], b[2], b[3]);
            }
            sts64(rp, __float_as_uint(a0[0] + a1[0]), __float_as_uint(a0[1] + a1[1]));
            sts64(rp + 256, __float_as_uint(a0[2] + a1[2]), __float_as_uint(a0[3] + a1[3]));
            bar_arrive(BAR_RED, RT);
            if (FUSE_X) {
                if (s + 2 < NSEG_) xworkA(s + 2);
                if (s >= 1 && s + 1 < NSEG_) xsignal(s + 1);
                if (s + 1 < NSEG_) bar_sync(BAR_GO, RT);
                if (s + 2 < NSEG_) xwork(s + 2);
            }
        }
    } else {
        asm volatile("setmaxnreg.inc.sync.aligned.u32 200;");
        const int ct = tid - 384, cw = w - 12;
        const int mg = cw >> 1, kh = cw & 1;
        uint32_t wf[20][4];
        {
            uint32_t stg = smem_u32(smem_raw) + 12 * 10240 + cw * 10240;
#pragma unroll 4
            for (int i = lane; i < 640; i += 32) {
                int r = i / 10, ch = i % 10;
                cp_async16(stg + r * 160 + ch * 16, Wo + (size_t)(h * DH_ + kh * 64 + r) * D_ + c * 160 + mg * 80 + ch * 8);
            }
            cp_async_commit(); cp_async_wait<0>(); __syncwarp();
            uint32_t la = stg + ((lane & 7) + ((lane >> 4) & 1) * 8) * 160 + ((lane >> 3) & 1) * 16;
#pragma unroll
            for (int mi = 0; mi < 5; mi++)
#pragma unroll
                for (int ki = 0; ki < 4; ki++) ldsm_x4_t(wf[mi * 4 + ki], la + ki * 16 * 160 + mi * 32);
        }
        bar_sync(BAR_INIT, RT);
        for (int i = ct; i < 2 * 8 * HL; i += 128) {
            int b = i / (8 * HL), r = (i / HL) % 8, cc = i % HL;
            sm.kall[b][40 + r][cc] = __float2bfloat16(0.f);
            sm.vall[b][40 + r][cc] = __float2bfloat16(0.f);
        }
        for (int i = ct; i < 8 * HL; i += 128) sm.qm[8 + i / HL][i % HL] = __float2bfloat16(0.f);
        for (int i = ct; i < 8 * 56; i += 128) sm.p[i / 56][i % 56] = __float2bfloat16(0.f);
        bar_sync(BAR_CTL, 128);
        constexpr uint32_t KV_BUF = 48 * HL * 2;
        const bf16* kv_src = g_qkv + (size_t)(ct >> 4) * (3 * HD_) + HD_ + h * DH_ + (ct & 15) * 8;
        const uint32_t kv_dst0 = smem_u32(&sm.kall[0][MEM_ + (ct >> 4)][(ct & 15) * 8]);
        const uint32_t kv_dst1 = smem_u32(&sm.vall[0][MEM_ + (ct >> 4)][(ct & 15) * 8]);
        auto prefetch_kv = [&](int s, int buf) {
            if (FUSE_X) {
                if (ct == 0) {
                    const unsigned* cp = g_xcnt + h * NSEG_ + s;
                    unsigned v; int n = 0;
                    do { asm volatile("ld.acquire.gpu.global.u32 %0, [%1];" : "=r"(v) : "l"(cp) : "memory"); } while (v < 48u && ++n < SPIN_LIMIT);
                }
                bar_sync(BAR_CTL, 128);
            }
            const bf16* src = kv_src + (size_t)s * SEG_ * (3 * HD_);
#pragma unroll
            for (int j = 0; j < 4; j++) {
                cp_async16(kv_dst0 + buf * KV_BUF + j * (8 * HL * 2), src + (size_t)j * 8 * (3 * HD_));
                cp_async16(kv_dst1 + buf * KV_BUF + j * (8 * HL * 2), src + (size_t)j * 8 * (3 * HD_) + HD_);
            }
            cp_async_commit();
        };
        const float4* acc_src = reinterpret_cast<const float4*>(g_acc) + ct;
        const uint32_t acc_dst = smem_u32(&sm.mem[(ct & 1) * 4][ct >> 1]);
        const uint4* hx_base = reinterpret_cast<const uint4*>(g_hx) + h * 1024;
        const int hx_rq = ct & 63, hx_half = ct >> 6;
        const uint4* hx_src = hx_base + hx_half * 64 + hx_rq;
        const uint32_t hx_col = (hx_rq & 7) * 8, hx_r = hx_rq >> 3;
        const uint32_t hx_dstA = (hx_half == 0 ? smem_u32(&sm.qm[hx_r][0]) : smem_u32(&sm.kall[0][hx_r][0])) + hx_col;
        const uint32_t hx_dstB = smem_u32(&sm.vall[0][hx_r][0]) + hx_col;
        const uint4* hx_probe = hx_base + (lane >> 3) * 256 + ((lane & 7) % 3) * 64 + (lane & 7) * 8 + 3;
        const int pb_r = ct >> 4, pb_pr = ct & 15;
        uint2* pb_dst = g_hx + (h * 1024 + c * 256 + pb_r * 8) * 2 + pb_pr;
        const float* pb_src = &sm.red[pb_pr >> 3][(pb_pr & 7) * 16 + pb_r];
        bf16* pb_k = g_kmem + (size_t)pb_r * HD_ + h * DH_ + c * 32 + pb_pr * 2;
        bf16* pb_v = g_vmem + (size_t)pb_r * HD_ + h * DH_ + c * 32 + pb_pr * 2;
        const uint32_t qb = smem_u32(&sm.qm[lane & 7][(lane >> 3) * 8]);
        const uint32_t ka0 = smem_u32(&sm.kall[0][lane & 15][(lane >> 4) * 8]);
        const uint32_t va0 = smem_u32(&sm.vall[0][(lane & 7) + ((lane >> 4) & 1) * 8][cw * 32 + ((lane >> 3) & 1) * 8]);
        const uint32_t ob = smem_u32(&sm.om[lane & 7][kh * 64 + (lane >> 3) * 8]);
        float* acc_dst_g = g_acc + (c * 160 + mg * 80 + g) * 8 + 2 * t;

        prefetch_kv(0, 0);
        for (int s = 0; s < NSEG_; s++) {
            const int buf = s & 1;
            const uint32_t flag = s + 1;
            const uint32_t bo = buf * KV_BUF;
            PROF(0);
            if (s == 0) {
                for (int i = ct; i < MEM_ * D_ / 8; i += 128) {
                    int r = i / (D_ / 8), cc = (i % (D_ / 8)) * 8;
                    *reinterpret_cast<uint4*>(&sm.mem[r][cc]) = *reinterpret_cast<const uint4*>(mem0 + r * D_ + cc);
                }
            } else {
                if (ct == 0) {
                    const unsigned* cp = g_cnt + (s - 1) * 32;
                    unsigned v; int n = 0;
                    do { asm volatile("ld.acquire.gpu.global.u32 %0, [%1];" : "=r"(v) : "l"(cp) : "memory"); } while (v < 256u && ++n < SPIN_LIMIT);
                }
                bar_sync(BAR_CTL, 128);
                PROF(1);
                const float4* src = acc_src + (size_t)(s - 1) * (MEM_ * D_ / 4);
                float4 v[10];
#pragma unroll
                for (int j = 0; j < 10; j++)
                    asm volatile("ld.relaxed.gpu.global.v4.f32 {%0,%1,%2,%3}, [%4];" : "=f"(v[j].x), "=f"(v[j].y), "=f"(v[j].z), "=f"(v[j].w) : "l"(src + 128 * j) : "memory");
#pragma unroll
                for (int j = 0; j < 10; j++) {
                    uint32_t lo = pack_bf16(v[j].x, v[j].y), hi = pack_bf16(v[j].z, v[j].w);
                    uint32_t d = acc_dst + j * 128;
                    asm volatile("st.shared.u16 [%0], %1;" ::"r"(d), "h"((uint16_t)(lo & 0xffff)) : "memory");
                    asm volatile("st.shared.u16 [%0], %1;" ::"r"(d + MEMS_LD * 2), "h"((uint16_t)(lo >> 16)) : "memory");
                    asm volatile("st.shared.u16 [%0], %1;" ::"r"(d + MEMS_LD * 4), "h"((uint16_t)(hi & 0xffff)) : "memory");
                    asm volatile("st.shared.u16 [%0], %1;" ::"r"(d + MEMS_LD * 6), "h"((uint16_t)(hi >> 16)) : "memory");
                }
            }
            bar_arrive(BAR_MEM, RT);
            PROF(2);
            bar_sync(BAR_RED, RT);
            PROF(3);
            {
                uint32_t pk0 = pack_bf16(pb_src[0] + pb_src[768], pb_src[8] + pb_src[768 + 8]);
                uint32_t pk1 = pack_bf16(pb_src[256] + pb_src[1024], pb_src[256 + 8] + pb_src[1024 + 8]);
                uint32_t pk2 = pack_bf16(pb_src[512] + pb_src[1280], pb_src[512 + 8] + pb_src[1280 + 8]);
                st_relaxed_v2(pb_dst, pk0, flag);
                st_relaxed_v2(pb_dst + 128, pk1, flag);
                st_relaxed_v2(pb_dst + 256, pk2, flag);
                *reinterpret_cast<uint32_t*>(pb_k + (size_t)s * (MEM_ * HD_)) = pk1;
                *reinterpret_cast<uint32_t*>(pb_v + (size_t)s * (MEM_ * HD_)) = pk2;
            }
            if (s == NSEG_ - 1) break;
            PROF(4);
            if (cw == 0) (void)poll_ll(hx_probe, flag);
            bar_sync(BAR_CTL, 128);
            PROF(5);
            {
                uint4 v[8];
#pragma unroll
                for (int j = 0; j < 4; j++) v[j] = ld_relaxed_v4(hx_src + j * 256);
                if (hx_half == 0) {
#pragma unroll
                    for (int j = 0; j < 4; j++) v[4 + j] = ld_relaxed_v4(hx_src + j * 256 + 128);
                }
#pragma unroll
                for (int j = 0; j < 4; j++) {
                    if (v[j].y != flag || v[j].w != flag) v[j] = poll_ll(hx_src + j * 256, flag);
                    sts64(hx_dstA + j * 64 + (hx_half ? bo : 0), v[j].x, v[j].z);
                }
                if (hx_half == 0) {
#pragma unroll
                    for (int j = 0; j < 4; j++) {
                        if (v[4 + j].y != flag || v[4 + j].w != flag) v[4 + j] = poll_ll(hx_src + j * 256 + 128, flag);
                        sts64(hx_dstB + j * 64 + bo, v[4 + j].x, v[4 + j].z);
                    }
                }
            }
            cp_async_wait<0>();
            bar_sync(BAR_CTL, 128);
            PROF(6);
            {
                uint32_t bq[4][4];
#pragma unroll
                for (int kk = 0; kk < 4; kk++) ldsm_x4(bq[kk], qb + kk * 64);
                float sc[3][4];
#pragma unroll
                for (int m = 0; m < 3; m++) {
                    uint32_t a[8][4];
#pragma unroll
                    for (int kk = 0; kk < 8; kk++) ldsm_x4(a[kk], ka0 + bo + m * (16 * HL * 2) + kk * 32);
                    float s0[4] = {0.f, 0.f, 0.f, 0.f}, s1[4] = {0.f, 0.f, 0.f, 0.f};
#pragma unroll
                    for (int kk = 0; kk < 4; kk++) { mma16816(s0, a[2 * kk], bq[kk][0], bq[kk][1]); mma16816(s1, a[2 * kk + 1], bq[kk][2], bq[kk][3]); }
#pragma unroll
                    for (int e = 0; e < 4; e++) sc[m][e] = rbf(rbf(s0[e] + s1[e]) * 0.08838834764831845f);
                }
                uint32_t av[2][3][4];
#pragma unroll
                for (int kt = 0; kt < 3; kt++) { ldsm_x4_t(av[0][kt], va0 + bo + kt * 16 * HL * 2); ldsm_x4_t(av[1][kt], va0 + bo + kt * 16 * HL * 2 + 32); }
                float mx0 = fmaxf(fmaxf(fmaxf(sc[0][0], sc[0][2]), fmaxf(sc[1][0], sc[1][2])), sc[2][0]);
                float mx1 = fmaxf(fmaxf(fmaxf(sc[0][1], sc[0][3]), fmaxf(sc[1][1], sc[1][3])), sc[2][1]);
#pragma unroll
                for (int o = 4; o < 32; o <<= 1) { mx0 = fmaxf(mx0, __shfl_xor_sync(0xffffffffu, mx0, o)); mx1 = fmaxf(mx1, __shfl_xor_sync(0xffffffffu, mx1, o)); }
                float sum0 = 0.f, sum1 = 0.f;
#pragma unroll
                for (int m = 0; m < 3; m++) {
#pragma unroll
                    for (int e = 0; e < 4; e++) {
                        if (m == 2 && e >= 2) { sc[m][e] = 0.f; continue; }
                        float ev = __expf(sc[m][e] - ((e & 1) ? mx1 : mx0));
                        sc[m][e] = ev;
                        if (e & 1) sum1 += ev; else sum0 += ev;
                    }
                }
#pragma unroll
                for (int o = 4; o < 32; o <<= 1) { sum0 += __shfl_xor_sync(0xffffffffu, sum0, o); sum1 += __shfl_xor_sync(0xffffffffu, sum1, o); }
                float i0 = 1.0f / sum0, i1 = 1.0f / sum1;
                uint32_t pb[3][2];
#pragma unroll
                for (int m = 0; m < 3; m++) {
#pragma unroll
                    for (int hh = 0; hh < 2; hh++) {
                        uint32_t pk = pack_bf16(sc[m][2 * hh] * i0, sc[m][2 * hh + 1] * i1);
                        asm volatile("movmatrix.sync.aligned.m8n8.trans.b16 %0, %1;" : "=r"(pb[m][hh]) : "r"(pk));
                    }
                }
                PROF(7);
#pragma unroll
                for (int m = 0; m < 2; m++) {
                    float o[4] = {0.f, 0.f, 0.f, 0.f};
#pragma unroll
                    for (int kt = 0; kt < 3; kt++) mma16816(o, av[m][kt], pb[kt][0], pb[kt][1]);
                    int d0 = cw * 32 + m * 16 + g;
                    sm.om[2 * t][d0] = __float2bfloat16_rn(o[0]);
                    sm.om[2 * t + 1][d0] = __float2bfloat16_rn(o[1]);
                    sm.om[2 * t][d0 + 8] = __float2bfloat16_rn(o[2]);
                    sm.om[2 * t + 1][d0 + 8] = __float2bfloat16_rn(o[3]);
                }
            }
            bar_sync(BAR_CTL, 128);
            PROF(8);
            {
                float acc[5][4];
#pragma unroll
                for (int mi = 0; mi < 5; mi++) { acc[mi][0] = acc[mi][1] = acc[mi][2] = acc[mi][3] = 0.f; }
                uint32_t b[2][4];
                ldsm_x4(b[0], ob); ldsm_x4(b[1], ob + 64);
#pragma unroll
                for (int ki = 0; ki < 4; ki++)
#pragma unroll
                    for (int mi = 0; mi < 5; mi++) mma16816(acc[mi], wf[mi * 4 + ki], b[ki >> 1][(ki & 1) * 2], b[ki >> 1][(ki & 1) * 2 + 1]);
                if (kh == 1) {
#pragma unroll
                    for (int mi = 0; mi < 5; mi++)
                        *reinterpret_cast<float4*>(&sm.wred[mg][mi][lane * 4]) = make_float4(acc[mi][0], acc[mi][1], acc[mi][2], acc[mi][3]);
                }
                bar_sync(BAR_WO + mg, 64);
                if (kh == 0) {
                    float* dst = acc_dst_g + (size_t)s * (MEM_ * D_);
#pragma unroll
                    for (int mi = 0; mi < 5; mi++) {
                        float4 o2 = *reinterpret_cast<float4*>(&sm.wred[mg][mi][lane * 4]);
                        asm volatile("red.global.add.v2.f32 [%0], {%1,%2};" ::"l"(dst + mi * 128), "f"(acc[mi][0] + o2.x), "f"(acc[mi][1] + o2.y) : "memory");
                        asm volatile("red.global.add.v2.f32 [%0], {%1,%2};" ::"l"(dst + mi * 128 + 64), "f"(acc[mi][2] + o2.z), "f"(acc[mi][3] + o2.w) : "memory");
                    }
                    __threadfence();
                    __syncwarp();
                    if (lane == 0) atomicAdd(&g_cnt[s * 32], 1u);
                }
            }
            if (FUSE_X) bar_arrive(BAR_GO, RT);
            PROF(9);
            prefetch_kv(s + 1, buf ^ 1);
            PROF(10);
        }
    }
}

__global__ void __launch_bounds__(128)
attn_x_kernel() {
    __shared__ __align__(16) bf16 sq[32][HL], sk[48][HL], sv[48][HL];
    const int s = blockIdx.x >> 5, h = blockIdx.x & 31;
    const int tid = threadIdx.x, lane = tid & 31, w = tid >> 5, g = lane >> 2, t = lane & 3;
    for (int i = tid; i < (32 + 40 + 40) * 16; i += 128) {
        int r = i >> 4, ch = i & 15;
        const bf16* src; bf16* dst;
        if (r < 32) { src = g_qkv + (size_t)(s * SEG_ + r) * (3 * HD_) + h * DH_; dst = sq[r]; }
        else if (r < 72) { int rr = r - 32; dst = sk[rr];
            src = rr < 8 ? g_kmem + ((size_t)s * MEM_ + rr) * HD_ + h * DH_ : g_qkv + (size_t)(s * SEG_ + rr - 8) * (3 * HD_) + HD_ + h * DH_; }
        else { int rr = r - 72; dst = sv[rr];
            src = rr < 8 ? g_vmem + ((size_t)s * MEM_ + rr) * HD_ + h * DH_ : g_qkv + (size_t)(s * SEG_ + rr - 8) * (3 * HD_) + 2 * HD_ + h * DH_; }
        cp_async16(smem_u32(dst + ch * 8), src + ch * 8);
    }
    cp_async_commit();
    for (int i = tid; i < 8 * 16; i += 128) *reinterpret_cast<uint4*>(&sv[40 + (i >> 4)][(i & 15) * 8]) = make_uint4(0, 0, 0, 0);
    cp_async_wait<0>();
    __syncthreads();
    const int rh = w & 1, dhh = w >> 1;
    float sc[5][4];
#pragma unroll
    for (int n = 0; n < 5; n++) sc[n][0] = sc[n][1] = sc[n][2] = sc[n][3] = 0.f;
#pragma unroll
    for (int kk = 0; kk < 8; kk++) {
        uint32_t a[4];
        ldsm_x4(a, smem_u32(&sq[rh * 16 + (lane & 15)][kk * 16 + (lane >> 4) * 8]));
#pragma unroll
        for (int n = 0; n < 5; n++) {
            uint32_t b[2];
            asm volatile("ldmatrix.sync.aligned.m8n8.x2.shared.b16 {%0,%1}, [%2];" : "=r"(b[0]), "=r"(b[1])
                         : "r"(smem_u32(&sk[n * 8 + (lane & 7)][kk * 16 + ((lane >> 3) & 1) * 8])));
            mma16816(sc[n], a, b[0], b[1]);
        }
    }
    const float scale = 0.08838834764831845f;
    float mx[2] = {-INFINITY, -INFINITY};
#pragma unroll
    for (int n = 0; n < 5; n++)
#pragma unroll
        for (int e = 0; e < 4; e++) {
            int row = rh * 16 + g + (e >> 1) * 8, key = n * 8 + 2 * t + (e & 1);
            float v = rbf(rbf(sc[n][e]) * scale);
            if (key > row + MEM_) v = -INFINITY;
            sc[n][e] = v;
            mx[e >> 1] = fmaxf(mx[e >> 1], v);
        }
#pragma unroll
    for (int o = 1; o < 4; o <<= 1) { mx[0] = fmaxf(mx[0], __shfl_xor_sync(0xffffffffu, mx[0], o)); mx[1] = fmaxf(mx[1], __shfl_xor_sync(0xffffffffu, mx[1], o)); }
    float sum[2] = {0.f, 0.f};
#pragma unroll
    for (int n = 0; n < 5; n++)
#pragma unroll
        for (int e = 0; e < 4; e++) { float ev = __expf(sc[n][e] - mx[e >> 1]); sc[n][e] = ev; sum[e >> 1] += ev; }
#pragma unroll
    for (int o = 1; o < 4; o <<= 1) { sum[0] += __shfl_xor_sync(0xffffffffu, sum[0], o); sum[1] += __shfl_xor_sync(0xffffffffu, sum[1], o); }
    float inv[2] = {1.0f / sum[0], 1.0f / sum[1]};
    uint32_t pa[3][4];
#pragma unroll
    for (int kt = 0; kt < 3; kt++) {
        pa[kt][0] = pack_bf16(sc[2 * kt][0] * inv[0], sc[2 * kt][1] * inv[0]);
        pa[kt][1] = pack_bf16(sc[2 * kt][2] * inv[1], sc[2 * kt][3] * inv[1]);
        if (kt < 2) {
            pa[kt][2] = pack_bf16(sc[2 * kt + 1][0] * inv[0], sc[2 * kt + 1][1] * inv[0]);
            pa[kt][3] = pack_bf16(sc[2 * kt + 1][2] * inv[1], sc[2 * kt + 1][3] * inv[1]);
        } else { pa[kt][2] = 0u; pa[kt][3] = 0u; }
    }
#pragma unroll
    for (int n = 0; n < 8; n++) {
        float o[4] = {0.f, 0.f, 0.f, 0.f};
#pragma unroll
        for (int kt = 0; kt < 3; kt++) {
            uint32_t b[2];
            asm volatile("ldmatrix.sync.aligned.m8n8.x2.trans.shared.b16 {%0,%1}, [%2];" : "=r"(b[0]), "=r"(b[1])
                         : "r"(smem_u32(&sv[kt * 16 + (lane & 15)][dhh * 64 + n * 8])));
            mma16816(o, pa[kt], b[0], b[1]);
        }
        int row = s * SEG_ + rh * 16 + g;
        bf16* dst = g_o + (size_t)row * HD_ + h * DH_ + dhh * 64 + n * 8 + 2 * t;
        *reinterpret_cast<uint32_t*>(dst) = pack_bf16(o[0], o[1]);
        *reinterpret_cast<uint32_t*>(dst + 8 * HD_) = pack_bf16(o[2], o[3]);
    }
}

typedef CUresult (*PFN_encodeTiled)(CUtensorMap*, CUtensorMapDataType, cuuint32_t, void*, const cuuint64_t*,
                                    const cuuint64_t*, const cuuint32_t*, const cuuint32_t*, CUtensorMapInterleave,
                                    CUtensorMapSwizzle, CUtensorMapL2promotion, CUtensorMapFloatOOBfill);
static PFN_encodeTiled p_encode = nullptr;

static CUtensorMap make_map(const void* ptr, uint64_t rows, uint64_t cols, uint64_t ld, uint32_t box_rows) {
    CUtensorMap m;
    cuuint64_t dims[2] = {cols, rows};
    cuuint64_t strides[1] = {ld * 2};
    cuuint32_t box[2] = {64, box_rows};
    cuuint32_t es[2] = {1, 1};
    p_encode(&m, CU_TENSOR_MAP_DATA_TYPE_BFLOAT16, 2, const_cast<void*>(ptr), dims, strides, box, es,
             CU_TENSOR_MAP_INTERLEAVE_NONE, CU_TENSOR_MAP_SWIZZLE_128B, CU_TENSOR_MAP_L2_PROMOTION_L2_128B,
             CU_TENSOR_MAP_FLOAT_OOB_FILL_NONE);
    return m;
}

template <int BN, int EPI>
static void launch_gemm(const CUtensorMap& a, const CUtensorMap& b0, const CUtensorMap& b1, const CUtensorMap& b2,
                        int nPerB, int M, int N, int K, EpiParams ep, cudaStream_t st) {
    constexpr int STAGE = 16384 + (BN / 64) * 8192;
    constexpr int NST = (200 * 1024) / STAGE;
    constexpr int SMEM = NST * STAGE + 1024;
    cudaFuncSetAttribute(gemm_kernel<BN, EPI>, cudaFuncAttributeMaxDynamicSharedMemorySize, SMEM);
    dim3 grid((N + BN - 1) / BN, M / 128);
    gemm_kernel<BN, EPI><<<grid, 384, SMEM, st>>>(a, b0, b1, b2, nPerB, N, K, ep);
}

extern "C" void kernel_launch(void* const* d_in, const int* in_sizes, int n_in, void* d_out, int out_size) {
    const bf16* x    = (const bf16*)d_in[0];
    const bf16* mem0 = (const bf16*)d_in[1];
    const bf16* Wq   = (const bf16*)d_in[2];
    const bf16* Wk   = (const bf16*)d_in[3];
    const bf16* Wv   = (const bf16*)d_in[4];
    const bf16* Wo   = (const bf16*)d_in[5];
    const bf16* w_in  = (const bf16*)d_in[8];
    const bf16* w_sp  = (const bf16*)d_in[9];
    const bf16* b_sp  = (const bf16*)d_in[10];
    const bf16* w_out = (const bf16*)d_in[11];
    bf16* out = (bf16*)d_out;
    cudaStream_t st = cudaStreamPerThread;

    if (!p_encode) {
        cudaDriverEntryPointQueryResult qr;
        cudaGetDriverEntryPoint("cuTensorMapEncodeTiled", (void**)&p_encode, cudaEnableDefault, &qr);
    }
    void *p_xn, *p_qkv, *p_z, *p_zg, *p_gate, *p_o, *p_acc, *p_cnt, *p_hx;
    cudaGetSymbolAddress(&p_xn, g_xn); cudaGetSymbolAddress(&p_qkv, g_qkv); cudaGetSymbolAddress(&p_z, g_z);
    cudaGetSymbolAddress(&p_zg, g_zg); cudaGetSymbolAddress(&p_gate, g_gate); cudaGetSymbolAddress(&p_o, g_o);
    cudaGetSymbolAddress(&p_acc, g_acc); cudaGetSymbolAddress(&p_cnt, g_cnt); cudaGetSymbolAddress(&p_hx, g_hx);

    CUtensorMap mA_xn  = make_map(p_xn, S_, D_, D_, 128);
    CUtensorMap mA_wsp = make_map(w_sp, S_, S_, S_, 128);
    CUtensorMap mA_zg  = make_map(p_zg, S_, FH_, FH_, 128);
    CUtensorMap mA_o   = make_map(p_o, S_, HD_, HD_, 128);
    CUtensorMap mB_wq  = make_map(Wq, D_, HD_, HD_, 64);
    CUtensorMap mB_wk  = make_map(Wk, D_, HD_, HD_, 64);
    CUtensorMap mB_wv  = make_map(Wv, D_, HD_, HD_, 64);
    CUtensorMap mB_win = make_map(w_in, D_, F_, F_, 64);
    CUtensorMap mB_z2  = make_map((bf16*)p_z + FH_, S_, FH_, F_, 64);
    CUtensorMap mB_wout = make_map(w_out, FH_, D_, D_, 64);
    CUtensorMap mB_wo  = make_map(Wo, HD_, D_, D_, 64);

    cudaMemsetAsync(p_acc, 0, sizeof(float) * NSEG_ * MEM_ * D_, st);
    cudaMemsetAsync(p_cnt, 0, sizeof(unsigned) * NSEG_ * 32, st);
    void* p_xcnt; cudaGetSymbolAddress(&p_xcnt, g_xcnt);
    cudaMemsetAsync(p_xcnt, 0, sizeof(unsigned) * H_ * NSEG_, st);
    cudaMemsetAsync(p_hx, 0, sizeof(uint2) * H_ * 4 * 256 * 2, st);

    ln_kernel<<<S_ / 8, 256, 0, st>>>(x);
    if (!FUSE_X) { EpiParams ep{(bf16*)p_qkv, 3 * HD_, nullptr, nullptr}; launch_gemm<256, EPI_STORE>(mA_xn, mB_wq, mB_wk, mB_wv, HD_, S_, 3 * HD_, D_, ep, st); }
    { EpiParams ep{(bf16*)p_z, F_, nullptr, nullptr}; launch_gemm<128, EPI_GELU>(mA_xn, mB_win, mB_win, mB_win, 1 << 20, S_, F_, D_, ep, st); }
    ln2_kernel<<<S_ / 8, 256, 0, st>>>();
    { EpiParams ep{(bf16*)p_zg, FH_, (const bf16*)p_z, b_sp}; launch_gemm<128, EPI_SP>(mA_wsp, mB_z2, mB_z2, mB_z2, 1 << 20, S_, FH_, S_, ep, st); }
    { EpiParams ep{(bf16*)p_gate, D_, nullptr, nullptr}; launch_gemm<128, EPI_SILU>(mA_zg, mB_wout, mB_wout, mB_wout, 1 << 20, S_, D_, FH_, ep, st); }
    constexpr int RSM = (int)sizeof(RecurSmem) > 16 * 10240 ? (int)sizeof(RecurSmem) : 16 * 10240;
    cudaFuncSetAttribute(recur_kernel, cudaFuncAttributeMaxDynamicSharedMemorySize, RSM);
    recur_kernel<<<128, RT, RSM, st>>>(mem0, Wq, Wk, Wv, Wo);
    attn_x_kernel<<<NSEG_ * H_, 128, 0, st>>>();
    { EpiParams ep{out, D_, x, (const bf16*)p_gate}; launch_gemm<128, EPI_FINAL>(mA_o, mB_wo, mB_wo, mB_wo, 1 << 20, S_, D_, HD_, ep, st); }
}
```

```cpp
#include <cuda_runtime.h>
#include <cuda_bf16.h>
#include <cuda.h>
#include <stdint.h>
#define NO_PROBE_HX 1

typedef __nv_bfloat16 bf16;

constexpr int S_   = 2048;
constexpr int D_   = 640;
constexpr int H_   = 32;
constexpr int DH_  = 128;
constexpr int MEM_ = 8;
constexpr int SEG_ = 32;
constexpr int NSEG_ = S_ / SEG_;
constexpr int HD_  = H_ * DH_;
constexpr int F_   = 1728;
constexpr int FH_  = 864;

__device__ bf16 g_xn[S_ * D_];
__device__ bf16 g_qkv[(size_t)S_ * 3 * HD_];
__device__ bf16 g_z[S_ * F_];
__device__ bf16 g_zg[S_ * FH_];
__device__ bf16 g_gate[S_ * D_];
__device__ bf16 g_kmem[NSEG_ * MEM_ * HD_];
__device__ bf16 g_vmem[NSEG_ * MEM_ * HD_];
__device__ bf16 g_o[(size_t)S_ * HD_];
__device__ float g_acc[NSEG_ * MEM_ * D_];
__device__ unsigned g_cnt[NSEG_ * 32];
__device__ unsigned g_xcnt[H_ * NSEG_];
__device__ uint2 g_hx[H_ * 4 * 256 * 2];

__device__ __forceinline__ uint32_t smem_u32(const void* p) { return (uint32_t)__cvta_generic_to_shared(p); }
__device__ __forceinline__ float bf2f(bf16 v) { return __bfloat162float(v); }
__device__ __forceinline__ float rbf(float v) { return __bfloat162float(__float2bfloat16_rn(v)); }
__device__ __forceinline__ uint32_t pack_bf16(float lo, float hi) {
    __nv_bfloat162 t = __floats2bfloat162_rn(lo, hi);
    return *reinterpret_cast<uint32_t*>(&t);
}
__device__ __forceinline__ float lo_f(uint32_t u) { return __uint_as_float(u << 16); }
__device__ __forceinline__ float hi_f(uint32_t u) { return __uint_as_float(u & 0xffff0000u); }

__device__ __forceinline__ void mbar_init(uint32_t bar, uint32_t cnt) {
    asm volatile("mbarrier.init.shared.b64 [%0], %1;" ::"r"(bar), "r"(cnt));
}
__device__ __forceinline__ void mbar_expect_tx(uint32_t bar, uint32_t bytes) {
    asm volatile("mbarrier.arrive.expect_tx.shared.b64 _, [%0], %1;" ::"r"(bar), "r"(bytes) : "memory");
}
__device__ __forceinline__ void mbar_arrive(uint32_t bar) {
    asm volatile("mbarrier.arrive.shared.b64 _, [%0];" ::"r"(bar) : "memory");
}
__device__ __forceinline__ void mbar_wait(uint32_t bar, uint32_t parity) {
    asm volatile(
        "{\n .reg .pred p;\n"
        "WAIT_%=:\n"
        " mbarrier.try_wait.parity.shared.b64 p, [%0], %1;\n"
        " @p bra DONE_%=;\n"
        " bra WAIT_%=;\n"
        "DONE_%=:\n}\n" ::"r"(bar), "r"(parity) : "memory");
}
__device__ __forceinline__ void tma_load_2d(uint32_t dst, const CUtensorMap* tm, uint32_t bar, int c0, int c1) {
    asm volatile(
        "cp.async.bulk.tensor.2d.shared::cluster.global.mbarrier::complete_tx::bytes [%0], [%1, {%3, %4}], [%2];"
        ::"r"(dst), "l"(tm), "r"(bar), "r"(c0), "r"(c1) : "memory");
}
__device__ __forceinline__ void wgmma_fence() { asm volatile("wgmma.fence.sync.aligned;" ::: "memory"); }
__device__ __forceinline__ void wgmma_commit() { asm volatile("wgmma.commit_group.sync.aligned;" ::: "memory"); }
template <int N> __device__ __forceinline__ void wgmma_wait() { asm volatile("wgmma.wait_group.sync.aligned %0;" ::"n"(N) : "memory"); }

__device__ __forceinline__ uint64_t make_desc(uint32_t addr, uint32_t lbo, uint32_t sbo) {
    return (uint64_t)((addr & 0x3FFFF) >> 4) | ((uint64_t)(lbo >> 4) << 16) | ((uint64_t)(sbo >> 4) << 32) | (1ull << 62);
}

template <int N> struct Wgmma;
template <> struct Wgmma<128> {
    static __device__ __forceinline__ void mma(float* d, uint64_t da, uint64_t db, int sd) {
        asm volatile(
            "{\n.reg .pred p;\nsetp.ne.b32 p, %66, 0;\n"
            "wgmma.mma_async.sync.aligned.m64n128k16.f32.bf16.bf16 "
            "{%0,%1,%2,%3,%4,%5,%6,%7,%8,%9,%10,%11,%12,%13,%14,%15,"
            "%16,%17,%18,%19,%20,%21,%22,%23,%24,%25,%26,%27,%28,%29,%30,%31,"
            "%32,%33,%34,%35,%36,%37,%38,%39,%40,%41,%42,%43,%44,%45,%46,%47,"
            "%48,%49,%50,%51,%52,%53,%54,%55,%56,%57,%58,%59,%60,%61,%62,%63},"
            "%64,%65,p,1,1,0,1;\n}\n"
            : "+f"(d[0]), "+f"(d[1]), "+f"(d[2]), "+f"(d[3]), "+f"(d[4]), "+f"(d[5]), "+f"(d[6]), "+f"(d[7]),
              "+f"(d[8]), "+f"(d[9]), "+f"(d[10]), "+f"(d[11]), "+f"(d[12]), "+f"(d[13]), "+f"(d[14]), "+f"(d[15]),
              "+f"(d[16]), "+f"(d[17]), "+f"(d[18]), "+f"(d[19]), "+f"(d[20]), "+f"(d[21]), "+f"(d[22]), "+f"(d[23]),
              "+f"(d[24]), "+f"(d[25]), "+f"(d[26]), "+f"(d[27]), "+f"(d[28]), "+f"(d[29]), "+f"(d[30]), "+f"(d[31]),
              "+f"(d[32]), "+f"(d[33]), "+f"(d[34]), "+f"(d[35]), "+f"(d[36]), "+f"(d[37]), "+f"(d[38]), "+f"(d[39]),
              "+f"(d[40]), "+f"(d[41]), "+f"(d[42]), "+f"(d[43]), "+f"(d[44]), "+f"(d[45]), "+f"(d[46]), "+f"(d[47]),
              "+f"(d[48]), "+f"(d[49]), "+f"(d[50]), "+f"(d[51]), "+f"(d[52]), "+f"(d[53]), "+f"(d[54]), "+f"(d[55]),
              "+f"(d[56]), "+f"(d[57]), "+f"(d[58]), "+f"(d[59]), "+f"(d[60]), "+f"(d[61]), "+f"(d[62]), "+f"(d[63])
            : "l"(da), "l"(db), "r"(sd));
    }
};
template <> struct Wgmma<192> {
    static __device__ __forceinline__ void mma(float* d, uint64_t da, uint64_t db, int sd) {
        asm volatile(
            "{\n.reg .pred p;\nsetp.ne.b32 p, %98, 0;\n"
            "wgmma.mma_async.sync.aligned.m64n192k16.f32.bf16.bf16 "
            "{%0,%1,%2,%3,%4,%5,%6,%7,%8,%9,%10,%11,%12,%13,%14,%15,"
            "%16,%17,%18,%19,%20,%21,%22,%23,%24,%25,%26,%27,%28,%29,%30,%31,"
            "%32,%33,%34,%35,%36,%37,%38,%39,%40,%41,%42,%43,%44,%45,%46,%47,"
            "%48,%49,%50,%51,%52,%53,%54,%55,%56,%57,%58,%59,%60,%61,%62,%63,"
            "%64,%65,%66,%67,%68,%69,%70,%71,%72,%73,%74,%75,%76,%77,%78,%79,"
            "%80,%81,%82,%83,%84,%85,%86,%87,%88,%89,%90,%91,%92,%93,%94,%95},"
            "%96,%97,p,1,1,0,1;\n}\n"
            : "+f"(d[0]), "+f"(d[1]), "+f"(d[2]), "+f"(d[3]), "+f"(d[4]), "+f"(d[5]), "+f"(d[6]), "+f"(d[7]),
              "+f"(d[8]), "+f"(d[9]), "+f"(d[10]), "+f"(d[11]), "+f"(d[12]), "+f"(d[13]), "+f"(d[14]), "+f"(d[15]),
              "+f"(d[16]), "+f"(d[17]), "+f"(d[18]), "+f"(d[19]), "+f"(d[20]), "+f"(d[21]), "+f"(d[22]), "+f"(d[23]),
              "+f"(d[24]), "+f"(d[25]), "+f"(d[26]), "+f"(d[27]), "+f"(d[28]), "+f"(d[29]), "+f"(d[30]), "+f"(d[31]),
              "+f"(d[32]), "+f"(d[33]), "+f"(d[34]), "+f"(d[35]), "+f"(d[36]), "+f"(d[37]), "+f"(d[38]), "+f"(d[39]),
              "+f"(d[40]), "+f"(d[41]), "+f"(d[42]), "+f"(d[43]), "+f"(d[44]), "+f"(d[45]), "+f"(d[46]), "+f"(d[47]),
              "+f"(d[48]), "+f"(d[49]), "+f"(d[50]), "+f"(d[51]), "+f"(d[52]), "+f"(d[53]), "+f"(d[54]), "+f"(d[55]),
              "+f"(d[56]), "+f"(d[57]), "+f"(d[58]), "+f"(d[59]), "+f"(d[60]), "+f"(d[61]), "+f"(d[62]), "+f"(d[63]),
              "+f"(d[64]), "+f"(d[65]), "+f"(d[66]), "+f"(d[67]), "+f"(d[68]), "+f"(d[69]), "+f"(d[70]), "+f"(d[71]),
              "+f"(d[72]), "+f"(d[73]), "+f"(d[74]), "+f"(d[75]), "+f"(d[76]), "+f"(d[77]), "+f"(d[78]), "+f"(d[79]),
              "+f"(d[80]), "+f"(d[81]), "+f"(d[82]), "+f"(d[83]), "+f"(d[84]), "+f"(d[85]), "+f"(d[86]), "+f"(d[87]),
              "+f"(d[88]), "+f"(d[89]), "+f"(d[90]), "+f"(d[91]), "+f"(d[92]), "+f"(d[93]), "+f"(d[94]), "+f"(d[95])
            : "l"(da), "l"(db), "r"(sd));
    }
};

template <> struct Wgmma<256> {
    static __device__ __forceinline__ void mma(float* d, uint64_t da, uint64_t db, int sd) {
        asm volatile(
            "{\n.reg .pred p;\nsetp.ne.b32 p, %130, 0;\n"
            "wgmma.mma_async.sync.aligned.m64n256k16.f32.bf16.bf16 "
            "{%0,%1,%2,%3,%4,%5,%6,%7,%8,%9,%10,%11,%12,%13,%14,%15,%16,%17,%18,%19,%20,%21,%22,%23,%24,%25,%26,%27,%28,%29,%30,%31,%32,%33,%34,%35,%36,%37,%38,%39,%40,%41,%42,%43,%44,%45,%46,%47,%48,%49,%50,%51,%52,%53,%54,%55,%56,%57,%58,%59,%60,%61,%62,%63,%64,%65,%66,%67,%68,%69,%70,%71,%72,%73,%74,%75,%76,%77,%78,%79,%80,%81,%82,%83,%84,%85,%86,%87,%88,%89,%90,%91,%92,%93,%94,%95,%96,%97,%98,%99,%100,%101,%102,%103,%104,%105,%106,%107,%108,%109,%110,%111,%112,%113,%114,%115,%116,%117,%118,%119,%120,%121,%122,%123,%124,%125,%126,%127},"
            "%128,%129,p,1,1,0,1;\n}\n"
            : "+f"(d[0]), "+f"(d[1]), "+f"(d[2]), "+f"(d[3]), "+f"(d[4]), "+f"(d[5]), "+f"(d[6]), "+f"(d[7]), "+f"(d[8]), "+f"(d[9]), "+f"(d[10]), "+f"(d[11]), "+f"(d[12]), "+f"(d[13]), "+f"(d[14]), "+f"(d[15]), "+f"(d[16]), "+f"(d[17]), "+f"(d[18]), "+f"(d[19]), "+f"(d[20]), "+f"(d[21]), "+f"(d[22]), "+f"(d[23]), "+f"(d[24]), "+f"(d[25]), "+f"(d[26]), "+f"(d[27]), "+f"(d[28]), "+f"(d[29]), "+f"(d[30]), "+f"(d[31]), "+f"(d[32]), "+f"(d[33]), "+f"(d[34]), "+f"(d[35]), "+f"(d[36]), "+f"(d[37]), "+f"(d[38]), "+f"(d[39]), "+f"(d[40]), "+f"(d[41]), "+f"(d[42]), "+f"(d[43]), "+f"(d[44]), "+f"(d[45]), "+f"(d[46]), "+f"(d[47]), "+f"(d[48]), "+f"(d[49]), "+f"(d[50]), "+f"(d[51]), "+f"(d[52]), "+f"(d[53]), "+f"(d[54]), "+f"(d[55]), "+f"(d[56]), "+f"(d[57]), "+f"(d[58]), "+f"(d[59]), "+f"(d[60]), "+f"(d[61]), "+f"(d[62]), "+f"(d[63]), "+f"(d[64]), "+f"(d[65]), "+f"(d[66]), "+f"(d[67]), "+f"(d[68]), "+f"(d[69]), "+f"(d[70]), "+f"(d[71]), "+f"(d[72]), "+f"(d[73]), "+f"(d[74]), "+f"(d[75]), "+f"(d[76]), "+f"(d[77]), "+f"(d[78]), "+f"(d[79]), "+f"(d[80]), "+f"(d[81]), "+f"(d[82]), "+f"(d[83]), "+f"(d[84]), "+f"(d[85]), "+f"(d[86]), "+f"(d[87]), "+f"(d[88]), "+f"(d[89]), "+f"(d[90]), "+f"(d[91]), "+f"(d[92]), "+f"(d[93]), "+f"(d[94]), "+f"(d[95]), "+f"(d[96]), "+f"(d[97]), "+f"(d[98]), "+f"(d[99]), "+f"(d[100]), "+f"(d[101]), "+f"(d[102]), "+f"(d[103]), "+f"(d[104]), "+f"(d[105]), "+f"(d[106]), "+f"(d[107]), "+f"(d[108]), "+f"(d[109]), "+f"(d[110]), "+f"(d[111]), "+f"(d[112]), "+f"(d[113]), "+f"(d[114]), "+f"(d[115]), "+f"(d[116]), "+f"(d[117]), "+f"(d[118]), "+f"(d[119]), "+f"(d[120]), "+f"(d[121]), "+f"(d[122]), "+f"(d[123]), "+f"(d[124]), "+f"(d[125]), "+f"(d[126]), "+f"(d[127])
            : "l"(da), "l"(db), "r"(sd));
    }
};
template <int W>
__device__ __forceinline__ void ln_row(const bf16* __restrict__ src, bf16* __restrict__ dst, int lane) {
    constexpr int NP = W / 64;
    constexpr int REM = (W / 2) % 32;
    uint32_t v[NP + 1];
    const uint32_t* s32 = reinterpret_cast<const uint32_t*>(src);
    float sum = 0.f;
#pragma unroll
    for (int i = 0; i < NP; i++) { v[i] = s32[i * 32 + lane]; sum += lo_f(v[i]) + hi_f(v[i]); }
    if (REM) { v[NP] = (lane < REM) ? s32[NP * 32 + lane] : 0u; if (lane < REM) sum += lo_f(v[NP]) + hi_f(v[NP]); }
#pragma unroll
    for (int o = 16; o; o >>= 1) sum += __shfl_xor_sync(0xffffffffu, sum, o);
    float mean = sum * (1.0f / W);
    float vs = 0.f;
#pragma unroll
    for (int i = 0; i < NP; i++) { float a = lo_f(v[i]) - mean, b = hi_f(v[i]) - mean; vs += a * a + b * b; }
    if (REM && lane < REM) { float a = lo_f(v[NP]) - mean, b = hi_f(v[NP]) - mean; vs += a * a + b * b; }
#pragma unroll
    for (int o = 16; o; o >>= 1) vs += __shfl_xor_sync(0xffffffffu, vs, o);
    float var = rbf(vs * (1.0f / W));
    float mb = rbf(mean);
    float den = rbf(sqrtf(rbf(var + 1e-5f)));
    uint32_t* d32 = reinterpret_cast<uint32_t*>(dst);
#pragma unroll
    for (int i = 0; i < NP; i++) d32[i * 32 + lane] = pack_bf16(rbf(lo_f(v[i]) - mb) / den, rbf(hi_f(v[i]) - mb) / den);
    if (REM && lane < REM) d32[NP * 32 + lane] = pack_bf16(rbf(lo_f(v[NP]) - mb) / den, rbf(hi_f(v[NP]) - mb) / den);
}

__global__ void ln_kernel(const bf16* __restrict__ x) {
    int row = blockIdx.x * 8 + (threadIdx.x >> 5);
    ln_row<D_>(x + (size_t)row * D_, g_xn + (size_t)row * D_, threadIdx.x & 31);
}
__global__ void ln2_kernel() {
    int row = blockIdx.x * 8 + (threadIdx.x >> 5);
    bf16* p = g_z + (size_t)row * F_ + FH_;
    ln_row<FH_>(p, p, threadIdx.x & 31);
}

enum { EPI_STORE = 0, EPI_GELU = 1, EPI_SP = 2, EPI_SILU = 3, EPI_FINAL = 4, EPI_PART = 5 };
__device__ float g_part[2 * S_ * D_];
struct EpiParams {
    bf16* out; int ldo;
    const bf16* aux0;
    const bf16* aux1;
};

__device__ __forceinline__ float gelu_tanh_f(float x) {
    const float k0 = 0.7978845608028654f, k1 = 0.044715f;
    float inner = k0 * (x + k1 * x * x * x);
    return 0.5f * x * (1.0f + tanhf(inner));
}
__device__ __forceinline__ float silu_f(float x) { return x / (1.0f + expf(-x)); }

template <int BN, int EPI>
__global__ void __launch_bounds__(384, 1)
gemm_kernel(const __grid_constant__ CUtensorMap tmA, const __grid_constant__ CUtensorMap tmB0,
            const __grid_constant__ CUtensorMap tmB1, const __grid_constant__ CUtensorMap tmB2,
            int nPerB, int N, int K, EpiParams ep) {
    constexpr int BM = 128, BK = 64;
    constexpr int A_BYTES = BM * BK * 2;
    constexpr int B_BYTES = (BN / 64) * 8192;
    constexpr int STAGE = A_BYTES + B_BYTES;
    constexpr int NST = (200 * 1024) / STAGE;
    constexpr int OLD = BN + 8;
    extern __shared__ __align__(1024) uint8_t smem_raw[];
    uint8_t* smem = (uint8_t*)(((uintptr_t)smem_raw + 1023) & ~(uintptr_t)1023);
    __shared__ __align__(8) uint64_t full_bar[NST], empty_bar[NST];

    const int tid = threadIdx.x, wg = tid >> 7;
    const int m0 = blockIdx.y * BM, n0 = blockIdx.x * BN;
    const int nk = (K + BK - 1) / BK / gridDim.z;
    const int kbase = blockIdx.z * nk;

    if (tid == 0) {
        for (int i = 0; i < NST; i++) { mbar_init(smem_u32(&full_bar[i]), 1); mbar_init(smem_u32(&empty_bar[i]), 2); }
        asm volatile("fence.mbarrier_init.release.cluster;" ::: "memory");
    }
    __syncthreads();

    if (wg == 0) {
        if (tid == 0) {
            const int bsel = n0 / nPerB;
            const CUtensorMap* tmB = bsel == 0 ? &tmB0 : (bsel == 1 ? &tmB1 : &tmB2);
            const int nb = n0 - bsel * nPerB;
            for (int kt = 0; kt < nk; kt++) {
                int st = kt % NST; uint32_t ph = (kt / NST) & 1;
                mbar_wait(smem_u32(&empty_bar[st]), ph ^ 1);
                uint32_t fb = smem_u32(&full_bar[st]);
                mbar_expect_tx(fb, STAGE);
                uint32_t sa = smem_u32(smem + st * STAGE);
                tma_load_2d(sa, &tmA, fb, (kbase + kt) * BK, m0);
#pragma unroll
                for (int j = 0; j < BN / 64; j++) tma_load_2d(sa + A_BYTES + j * 8192, tmB, fb, nb + j * 64, (kbase + kt) * BK);
            }
        }
    } else {
        const int cw = wg - 1;
        float acc[BN / 2];
        for (int kt = 0; kt < nk; kt++) {
            int st = kt % NST; uint32_t ph = (kt / NST) & 1;
            mbar_wait(smem_u32(&full_bar[st]), ph);
            uint32_t sa = smem_u32(smem + st * STAGE) + cw * 64 * 128;
            uint32_t sb = smem_u32(smem + st * STAGE) + A_BYTES;
            wgmma_fence();
#pragma unroll
            for (int k = 0; k < BK / 16; k++) {
                uint64_t da = make_desc(sa + k * 32, 16, 1024);
                uint64_t db = make_desc(sb + k * 2048, 8192, 1024);
                Wgmma<BN>::mma(acc, da, db, (kt | k) != 0);
            }
            wgmma_commit();
            wgmma_wait<1>();
            if (kt > 0 && (tid & 127) == 0) mbar_arrive(smem_u32(&empty_bar[(kt - 1) % NST]));
        }
        wgmma_wait<0>();
        if (EPI == EPI_PART) {
            const int lane = tid & 31, wi = (tid >> 5) & 3, g = lane >> 2, t = lane & 3;
            float* dst = g_part + (size_t)blockIdx.z * (S_ * D_) + (size_t)(m0 + cw * 64 + wi * 16 + g) * D_ + n0 + 2 * t;
#pragma unroll
            for (int j = 0; j < BN / 8; j++) {
                *reinterpret_cast<float2*>(dst + j * 8) = make_float2(acc[4 * j], acc[4 * j + 1]);
                *reinterpret_cast<float2*>(dst + 8 * D_ + j * 8) = make_float2(acc[4 * j + 2], acc[4 * j + 3]);
            }
            return;
        }
        asm volatile("bar.sync 1, 256;" ::: "memory");
        const int lane = tid & 31, wi = (tid >> 5) & 3, g = lane >> 2, t = lane & 3;
        bf16* stg = reinterpret_cast<bf16*>(smem) + cw * 64 * OLD;
#pragma unroll
        for (int j = 0; j < BN / 8; j++) {
            *reinterpret_cast<uint32_t*>(&stg[(wi * 16 + g) * OLD + j * 8 + 2 * t]) = pack_bf16(acc[4 * j], acc[4 * j + 1]);
            *reinterpret_cast<uint32_t*>(&stg[(wi * 16 + g + 8) * OLD + j * 8 + 2 * t]) = pack_bf16(acc[4 * j + 2], acc[4 * j + 3]);
        }
        asm volatile("bar.sync %0, 128;" ::"r"(2 + cw) : "memory");
        constexpr int CPR = BN / 8;
        const int ltid = tid & 127;
#pragma unroll 4
        for (int i = ltid; i < 64 * CPR; i += 128) {
            int r = i / CPR, ch = i % CPR;
            int row = m0 + cw * 64 + r, col = n0 + ch * 8;
            if (col >= N) continue;
            uint4 v = *reinterpret_cast<const uint4*>(&stg[r * OLD + ch * 8]);
            uint32_t u[4] = {v.x, v.y, v.z, v.w}, o[4];
            if (EPI == EPI_STORE) {
#pragma unroll
                for (int q = 0; q < 4; q++) o[q] = u[q];
            } else if (EPI == EPI_GELU) {
#pragma unroll
                for (int q = 0; q < 4; q++) o[q] = pack_bf16(gelu_tanh_f(lo_f(u[q])), gelu_tanh_f(hi_f(u[q])));
            } else if (EPI == EPI_SP) {
                float bb = bf2f(ep.aux1[row]);
                uint4 z = *reinterpret_cast<const uint4*>(ep.aux0 + (size_t)row * F_ + col);
                uint32_t zz[4] = {z.x, z.y, z.z, z.w};
#pragma unroll
                for (int q = 0; q < 4; q++) o[q] = pack_bf16(lo_f(zz[q]) * rbf(lo_f(u[q]) + bb), hi_f(zz[q]) * rbf(hi_f(u[q]) + bb));
            } else if (EPI == EPI_SILU) {
#pragma unroll
                for (int q = 0; q < 4; q++) o[q] = pack_bf16(silu_f(lo_f(u[q])), silu_f(hi_f(u[q])));
            } else {
                uint4 xv = *reinterpret_cast<const uint4*>(ep.aux0 + (size_t)row * D_ + col);
                uint4 gv = *reinterpret_cast<const uint4*>(ep.aux1 + (size_t)row * D_ + col);
                uint32_t xx[4] = {xv.x, xv.y, xv.z, xv.w}, gg[4] = {gv.x, gv.y, gv.z, gv.w};
#pragma unroll
                for (int q = 0; q < 4; q++)
                    o[q] = pack_bf16(lo_f(xx[q]) + rbf(lo_f(u[q]) * lo_f(gg[q])), hi_f(xx[q]) + rbf(hi_f(u[q]) * hi_f(gg[q])));
            }
            *reinterpret_cast<uint4*>(ep.out + (size_t)row * ep.ldo + col) = make_uint4(o[0], o[1], o[2], o[3]);
        }
    }
}

__global__ void final_combine_kernel(const bf16* __restrict__ x, bf16* __restrict__ out) {
    int i = (blockIdx.x * blockDim.x + threadIdx.x) * 4;
    float4 a = *reinterpret_cast<const float4*>(g_part + i), b = *reinterpret_cast<const float4*>(g_part + S_ * D_ + i);
    uint2 xv = *reinterpret_cast<const uint2*>(x + i), gv = *reinterpret_cast<const uint2*>(g_gate + i);
    float s0 = rbf(a.x + b.x), s1 = rbf(a.y + b.y), s2 = rbf(a.z + b.z), s3 = rbf(a.w + b.w);
    uint2 o;
    o.x = pack_bf16(lo_f(xv.x) + rbf(s0 * lo_f(gv.x)), hi_f(xv.x) + rbf(s1 * hi_f(gv.x)));
    o.y = pack_bf16(lo_f(xv.y) + rbf(s2 * lo_f(gv.y)), hi_f(xv.y) + rbf(s3 * hi_f(gv.y)));
    *reinterpret_cast<uint2*>(out + i) = o;
}

__device__ __forceinline__ void mma16816(float* c, const uint32_t* a, uint32_t b0, uint32_t b1) {
    asm volatile(
        "mma.sync.aligned.m16n8k16.row.col.f32.bf16.bf16.f32 {%0,%1,%2,%3}, {%4,%5,%6,%7}, {%8,%9}, {%0,%1,%2,%3};"
        : "+f"(c[0]), "+f"(c[1]), "+f"(c[2]), "+f"(c[3])
        : "r"(a[0]), "r"(a[1]), "r"(a[2]), "r"(a[3]), "r"(b0), "r"(b1));
}
__device__ __forceinline__ void ldsm_x4(uint32_t* r, uint32_t addr) {
    asm volatile("ldmatrix.sync.aligned.m8n8.x4.shared.b16 {%0,%1,%2,%3}, [%4];"
                 : "=r"(r[0]), "=r"(r[1]), "=r"(r[2]), "=r"(r[3]) : "r"(addr));
}
__device__ __forceinline__ void ldsm_x4_t(uint32_t* r, uint32_t addr) {
    asm volatile("ldmatrix.sync.aligned.m8n8.x4.trans.shared.b16 {%0,%1,%2,%3}, [%4];"
                 : "=r"(r[0]), "=r"(r[1]), "=r"(r[2]), "=r"(r[3]) : "r"(addr));
}
__device__ __forceinline__ uint4 ld_relaxed_v4(const void* p) {
    uint4 v;
    asm volatile("ld.relaxed.gpu.global.v4.u32 {%0,%1,%2,%3}, [%4];" : "=r"(v.x), "=r"(v.y), "=r"(v.z), "=r"(v.w) : "l"(p) : "memory");
    return v;
}
__device__ __forceinline__ void st_relaxed_v4(void* p, uint32_t a, uint32_t b, uint32_t c, uint32_t d) {
    asm volatile("st.relaxed.gpu.global.v4.u32 [%0], {%1,%2,%3,%4};" ::"l"(p), "r"(a), "r"(b), "r"(c), "r"(d) : "memory");
}
__device__ __forceinline__ void st_relaxed_v2(void* p, uint32_t a, uint32_t b) {
    asm volatile("st.relaxed.gpu.global.v2.u32 [%0], {%1,%2};" ::"l"(p), "r"(a), "r"(b) : "memory");
}
__device__ __forceinline__ void cp_async16(uint32_t dst, const void* src) {
    asm volatile("cp.async.cg.shared.global [%0], [%1], 16;" ::"r"(dst), "l"(src) : "memory");
}
__device__ __forceinline__ void cp_async_commit() { asm volatile("cp.async.commit_group;" ::: "memory"); }
template <int N> __device__ __forceinline__ void cp_async_wait() { asm volatile("cp.async.wait_group %0;" ::"n"(N) : "memory"); }

#define PROF(i) do {} while (0)
constexpr int SPIN_LIMIT = 4000000;

__device__ __forceinline__ uint4 poll_ll(const void* p, uint32_t flag) {
    uint4 v = ld_relaxed_v4(p);
    int n = 0;
    while ((v.y != flag || v.w != flag) && ++n < SPIN_LIMIT) {
        v = ld_relaxed_v4(p);
    }
    return v;
}

constexpr int RT = 512;
constexpr bool FUSE_X = false;
constexpr int MEMS_LD = D_ + 8;
constexpr int HL = DH_ + 8;
struct RecurSmem {
    bf16 mem[MEM_][MEMS_LD];
    bf16 kall[2][48][HL];
    bf16 vall[2][48][HL];
    bf16 qm[16][HL];
    float sc[MEM_][40];
    bf16 p[MEM_][48 + 8];
    bf16 om[MEM_][HL];
    float red[12][16 * 8];
    float wred[2][5][16 * 8];
    bf16 xs[2][SEG_][MEMS_LD];
    float redx[6][4][16 * 8];
    bf16 xo[SEG_][96 + 8];
};

__device__ __forceinline__ void bar_sync(int id, int n) { asm volatile("bar.sync %0, %1;" ::"r"(id), "r"(n) : "memory"); }
__device__ __forceinline__ void bar_arrive(int id, int n) { asm volatile("bar.arrive %0, %1;" ::"r"(id), "r"(n) : "memory"); }
__device__ __forceinline__ void sts64(uint32_t a, uint32_t x, uint32_t y) { asm volatile("st.shared.v2.u32 [%0], {%1,%2};" ::"r"(a), "r"(x), "r"(y) : "memory"); }
__device__ __forceinline__ uint32_t ldg_u16x2(const bf16* p0, const bf16* p1) {
    return (uint32_t)*(const uint16_t*)p0 | ((uint32_t)*(const uint16_t*)p1 << 16);
}
enum { BAR_MEM = 1, BAR_RED = 2, BAR_CTL = 3, BAR_WO = 4, BAR_INIT = 6, BAR_X = 7, BAR_GO = 8 };

__global__ void __launch_bounds__(RT, 1)
recur_kernel(const bf16* __restrict__ mem0, const bf16* __restrict__ Wq, const bf16* __restrict__ Wk,
             const bf16* __restrict__ Wv, const bf16* __restrict__ Wo) {
    extern __shared__ __align__(16) uint8_t smem_raw[];
    RecurSmem& sm = *reinterpret_cast<RecurSmem*>(smem_raw);
    const int tid = threadIdx.x, lane = tid & 31, w = tid >> 5;
    const int g = lane >> 2, t = lane & 3;
    const int h = blockIdx.x >> 2, c = blockIdx.x & 3;

    if (w < 12) {
        asm volatile("setmaxnreg.dec.sync.aligned.u32 104;");
        uint32_t wf[20][4];
        const int mt = w % 6, kh = w / 6;
        {
            const bf16* W = (mt < 2) ? Wq : (mt < 4 ? Wk : Wv);
            int f0 = h * DH_ + c * 32 + (mt & 1) * 16;
            uint32_t stg = smem_u32(smem_raw) + w * 10240;
#pragma unroll 4
            for (int i = lane; i < 640; i += 32)
                cp_async16(stg + i * 16, W + (size_t)(kh * 320 + (i >> 1)) * HD_ + f0 + (i & 1) * 8);
            cp_async_commit(); cp_async_wait<0>(); __syncwarp();
            uint32_t la = stg + ((lane & 7) + ((lane >> 4) & 1) * 8) * 32 + ((lane >> 3) & 1) * 16;
#pragma unroll
            for (int i = 0; i < 20; i++) ldsm_x4_t(wf[i], la + i * 512);
        }
        bar_sync(BAR_INIT, RT);
        const uint32_t base = smem_u32(&sm.mem[lane & 7][kh * 320 + (lane >> 3) * 8]);
        const uint32_t rp = smem_u32(&sm.red[w][g * 8 + 2 * t]);
        const uint32_t xbase0 = smem_u32(&sm.xs[0][lane & 7][kh * 320 + (lane >> 3) * 8]);
        uint32_t xbase = xbase0;
        const uint32_t rxp = smem_u32(&sm.redx[mt][0][lane * 4]);
        auto load_x = [&](int seg) {
            for (int i = tid; i < SEG_ * (D_ / 8); i += 384) {
                int r = i / (D_ / 8), ch = i % (D_ / 8);
                cp_async16(smem_u32(&sm.xs[seg & 1][r][ch * 8]), g_xn + (size_t)(seg * SEG_ + r) * D_ + ch * 8);
            }
            cp_async_commit();
        };
        float acc[4][4];
        auto xhalf = [&](int n0) {
#pragma unroll
            for (int nt = 0; nt < 2; nt++) { acc[n0 + nt][0] = acc[n0 + nt][1] = acc[n0 + nt][2] = acc[n0 + nt][3] = 0.f; }
#pragma unroll
            for (int i = 0; i < 10; i++) {
#pragma unroll
                for (int nt = 0; nt < 2; nt++) {
                    uint32_t b[4];
                    ldsm_x4(b, xbase + (n0 + nt) * (8 * MEMS_LD * 2) + i * 64);
                    mma16816(acc[n0 + nt], wf[2 * i], b[0], b[1]);
                    mma16816(acc[n0 + nt], wf[2 * i + 1], b[2], b[3]);
                }
            }
        };
        auto xworkA = [&](int seg) {
            cp_async_wait<0>();
            bar_sync(BAR_X, 384);
            if (seg + 1 < NSEG_) load_x(seg + 1);
            xbase = xbase0 + (seg & 1) * (SEG_ * MEMS_LD * 2);
            xhalf(0);
        };
        auto xwork = [&](int seg) {
            xhalf(2);
            if (kh == 1) {
#pragma unroll
                for (int nt = 0; nt < 4; nt++)
                    asm volatile("st.shared.v4.f32 [%0], {%1,%2,%3,%4};" ::"r"(rxp + nt * 512), "f"(acc[nt][0]), "f"(acc[nt][1]), "f"(acc[nt][2]), "f"(acc[nt][3]) : "memory");
            }
            bar_sync(BAR_X, 384);
            if (kh == 0) {
#pragma unroll
                for (int nt = 0; nt < 4; nt++) {
                    float4 o;
                    asm volatile("ld.shared.v4.f32 {%0,%1,%2,%3}, [%4];" : "=f"(o.x), "=f"(o.y), "=f"(o.z), "=f"(o.w) : "r"(rxp + nt * 512) : "memory");
                    bf16* d = &sm.xo[nt * 8 + 2 * t][mt * 16 + g];
                    d[0] = __float2bfloat16_rn(acc[nt][0] + o.x);
                    d[104] = __float2bfloat16_rn(acc[nt][1] + o.y);
                    d[8] = __float2bfloat16_rn(acc[nt][2] + o.z);
                    d[104 + 8] = __float2bfloat16_rn(acc[nt][3] + o.w);
                }
            }
            bar_sync(BAR_X, 384);
            {
                int r = tid / 12, ch = tid % 12;
                uint4 v = *reinterpret_cast<const uint4*>(&sm.xo[r][ch * 8]);
                *reinterpret_cast<uint4*>(g_qkv + (size_t)(seg * SEG_ + r) * (3 * HD_) + (ch >> 2) * HD_ + h * DH_ + c * 32 + (ch & 3) * 8) = v;
            }
        };
        auto xsignal = [&](int seg) {
            __threadfence();
            __syncwarp();
            if (lane == 0) atomicAdd(&g_xcnt[h * NSEG_ + seg], 1u);
        };
        if (FUSE_X) {
            load_x(0);
            xworkA(0); xwork(0); xsignal(0);
            xworkA(1); xwork(1); xsignal(1);
        }
        for (int s = 0; s < NSEG_; s++) {
            bar_sync(BAR_MEM, RT);
            float a0[4] = {0.f, 0.f, 0.f, 0.f}, a1[4] = {0.f, 0.f, 0.f, 0.f};
#pragma unroll
            for (int i = 0; i < 10; i++) {
                uint32_t b[4];
                ldsm_x4(b, base + i * 64);
                mma16816(a0, wf[2 * i], b[0], b[1]);
                mma16816(a1, wf[2 * i + 1], b[2], b[3]);
            }
            sts64(rp, __float_as_uint(a0[0] + a1[0]), __float_as_uint(a0[1] + a1[1]));
            sts64(rp + 256, __float_as_uint(a0[2] + a1[2]), __float_as_uint(a0[3] + a1[3]));
            bar_arrive(BAR_RED, RT);
            if (FUSE_X) {
                if (s + 2 < NSEG_) xworkA(s + 2);
                if (s >= 1 && s + 1 < NSEG_) xsignal(s + 1);
                if (s + 1 < NSEG_) bar_sync(BAR_GO, RT);
                if (s + 2 < NSEG_) xwork(s + 2);
            }
        }
    } else {
        asm volatile("setmaxnreg.inc.sync.aligned.u32 200;");
        const int ct = tid - 384, cw = w - 12;
        const int mg = cw >> 1, kh = cw & 1;
        uint32_t wf[20][4];
        {
            uint32_t stg = smem_u32(smem_raw) + 12 * 10240 + cw * 10240;
#pragma unroll 4
            for (int i = lane; i < 640; i += 32) {
                int r = i / 10, ch = i % 10;
                cp_async16(stg + r * 160 + ch * 16, Wo + (size_t)(h * DH_ + kh * 64 + r) * D_ + c * 160 + mg * 80 + ch * 8);
            }
            cp_async_commit(); cp_async_wait<0>(); __syncwarp();
            uint32_t la = stg + ((lane & 7) + ((lane >> 4) & 1) * 8) * 160 + ((lane >> 3) & 1) * 16;
#pragma unroll
            for (int mi = 0; mi < 5; mi++)
#pragma unroll
                for (int ki = 0; ki < 4; ki++) ldsm_x4_t(wf[mi * 4 + ki], la + ki * 16 * 160 + mi * 32);
        }
        bar_sync(BAR_INIT, RT);
        for (int i = ct; i < 2 * 8 * HL; i += 128) {
            int b = i / (8 * HL), r = (i / HL) % 8, cc = i % HL;
            sm.kall[b][40 + r][cc] = __float2bfloat16(0.f);
            sm.vall[b][40 + r][cc] = __float2bfloat16(0.f);
        }
        for (int i = ct; i < 8 * HL; i += 128) sm.qm[8 + i / HL][i % HL] = __float2bfloat16(0.f);
        for (int i = ct; i < 8 * 56; i += 128) sm.p[i / 56][i % 56] = __float2bfloat16(0.f);
        bar_sync(BAR_CTL, 128);
        constexpr uint32_t KV_BUF = 48 * HL * 2;
        const bf16* kv_src = g_qkv + (size_t)(ct >> 4) * (3 * HD_) + HD_ + h * DH_ + (ct & 15) * 8;
        const uint32_t kv_dst0 = smem_u32(&sm.kall[0][MEM_ + (ct >> 4)][(ct & 15) * 8]);
        const uint32_t kv_dst1 = smem_u32(&sm.vall[0][MEM_ + (ct >> 4)][(ct & 15) * 8]);
        auto prefetch_kv = [&](int s, int buf) {
            if (FUSE_X) {
                if (ct == 0) {
                    const unsigned* cp = g_xcnt + h * NSEG_ + s;
                    unsigned v; int n = 0;
                    do { asm volatile("ld.acquire.gpu.global.u32 %0, [%1];" : "=r"(v) : "l"(cp) : "memory"); } while (v < 48u && ++n < SPIN_LIMIT);
                }
                bar_sync(BAR_CTL, 128);
            }
            const bf16* src = kv_src + (size_t)s * SEG_ * (3 * HD_);
#pragma unroll
            for (int j = 0; j < 4; j++) {
                cp_async16(kv_dst0 + buf * KV_BUF + j * (8 * HL * 2), src + (size_t)j * 8 * (3 * HD_));
                cp_async16(kv_dst1 + buf * KV_BUF + j * (8 * HL * 2), src + (size_t)j * 8 * (3 * HD_) + HD_);
            }
            cp_async_commit();
        };
        const float4* acc_src = reinterpret_cast<const float4*>(g_acc) + ct;
        const uint32_t acc_dst = smem_u32(&sm.mem[(ct & 1) * 4][ct >> 1]);
        const uint4* hx_base = reinterpret_cast<const uint4*>(g_hx) + h * 1024;
        const int hx_rq = ct & 63, hx_half = ct >> 6;
        const uint4* hx_src = hx_base + hx_half * 64 + hx_rq;
        const uint32_t hx_col = (hx_rq & 7) * 8, hx_r = hx_rq >> 3;
        const uint32_t hx_dstA = (hx_half == 0 ? smem_u32(&sm.qm[hx_r][0]) : smem_u32(&sm.kall[0][hx_r][0])) + hx_col;
        const uint32_t hx_dstB = smem_u32(&sm.vall[0][hx_r][0]) + hx_col;
        const uint4* hx_probe = hx_base + (lane >> 3) * 256 + ((lane & 7) % 3) * 64 + (lane & 7) * 8 + 3;
        const int pb_r = ct >> 4, pb_pr = ct & 15;
        uint2* pb_dst = g_hx + (h * 1024 + c * 256 + pb_r * 8) * 2 + pb_pr;
        const float* pb_src = &sm.red[pb_pr >> 3][(pb_pr & 7) * 16 + pb_r];
        bf16* pb_k = g_kmem + (size_t)pb_r * HD_ + h * DH_ + c * 32 + pb_pr * 2;
        bf16* pb_v = g_vmem + (size_t)pb_r * HD_ + h * DH_ + c * 32 + pb_pr * 2;
        const uint32_t qb = smem_u32(&sm.qm[lane & 7][(lane >> 3) * 8]);
        const uint32_t ka0 = smem_u32(&sm.kall[0][lane & 15][(lane >> 4) * 8]);
        const uint32_t va0 = smem_u32(&sm.vall[0][(lane & 7) + ((lane >> 4) & 1) * 8][cw * 32 + ((lane >> 3) & 1) * 8]);
        const uint32_t ob = smem_u32(&sm.om[lane & 7][kh * 64 + (lane >> 3) * 8]);
        float* acc_dst_g = g_acc + (c * 160 + mg * 80 + g) * 8 + 2 * t;

        prefetch_kv(0, 0);
        for (int s = 0; s < NSEG_; s++) {
            const int buf = s & 1;
            const uint32_t flag = s + 1;
            const uint32_t bo = buf * KV_BUF;
            PROF(0);
            if (s == 0) {
                for (int i = ct; i < MEM_ * D_ / 8; i += 128) {
                    int r = i / (D_ / 8), cc = (i % (D_ / 8)) * 8;
                    *reinterpret_cast<uint4*>(&sm.mem[r][cc]) = *reinterpret_cast<const uint4*>(mem0 + r * D_ + cc);
                }
            } else {
                if (ct == 0) {
                    const unsigned* cp = g_cnt + (s - 1) * 32;
                    unsigned v; int n = 0;
                    do { asm volatile("ld.acquire.gpu.global.u32 %0, [%1];" : "=r"(v) : "l"(cp) : "memory"); } while (v < 256u && ++n < SPIN_LIMIT);
                }
                bar_sync(BAR_CTL, 128);
                PROF(1);
                const float4* src = acc_src + (size_t)(s - 1) * (MEM_ * D_ / 4);
                float4 v[10];
#pragma unroll
                for (int j = 0; j < 10; j++)
                    asm volatile("ld.relaxed.gpu.global.v4.f32 {%0,%1,%2,%3}, [%4];" : "=f"(v[j].x), "=f"(v[j].y), "=f"(v[j].z), "=f"(v[j].w) : "l"(src + 128 * j) : "memory");
#pragma unroll
                for (int j = 0; j < 10; j++) {
                    uint32_t lo = pack_bf16(v[j].x, v[j].y), hi = pack_bf16(v[j].z, v[j].w);
                    uint32_t d = acc_dst + j * 128;
                    asm volatile("st.shared.u16 [%0], %1;" ::"r"(d), "h"((uint16_t)(lo & 0xffff)) : "memory");
                    asm volatile("st.shared.u16 [%0], %1;" ::"r"(d + MEMS_LD * 2), "h"((uint16_t)(lo >> 16)) : "memory");
                    asm volatile("st.shared.u16 [%0], %1;" ::"r"(d + MEMS_LD * 4), "h"((uint16_t)(hi & 0xffff)) : "memory");
                    asm volatile("st.shared.u16 [%0], %1;" ::"r"(d + MEMS_LD * 6), "h"((uint16_t)(hi >> 16)) : "memory");
                }
            }
            bar_arrive(BAR_MEM, RT);
            PROF(2);
            bar_sync(BAR_RED, RT);
            PROF(3);
            {
                uint32_t pk0 = pack_bf16(pb_src[0] + pb_src[768], pb_src[8] + pb_src[768 + 8]);
                uint32_t pk1 = pack_bf16(pb_src[256] + pb_src[1024], pb_src[256 + 8] + pb_src[1024 + 8]);
                uint32_t pk2 = pack_bf16(pb_src[512] + pb_src[1280], pb_src[512 + 8] + pb_src[1280 + 8]);
                st_relaxed_v2(pb_dst, pk0, flag);
                st_relaxed_v2(pb_dst + 128, pk1, flag);
                st_relaxed_v2(pb_dst + 256, pk2, flag);
                *reinterpret_cast<uint32_t*>(pb_k + (size_t)s * (MEM_ * HD_)) = pk1;
                *reinterpret_cast<uint32_t*>(pb_v + (size_t)s * (MEM_ * HD_)) = pk2;
            }
            if (s == NSEG_ - 1) break;
            PROF(4);
            PROF(5);
            {
                uint4 v[8];
#pragma unroll
                for (int j = 0; j < 4; j++) v[j] = ld_relaxed_v4(hx_src + j * 256);
                if (hx_half == 0) {
#pragma unroll
                    for (int j = 0; j < 4; j++) v[4 + j] = ld_relaxed_v4(hx_src + j * 256 + 128);
                }
#pragma unroll
                for (int j = 0; j < 4; j++) {
                    if (v[j].y != flag || v[j].w != flag) v[j] = poll_ll(hx_src + j * 256, flag);
                    sts64(hx_dstA + j * 64 + (hx_half ? bo : 0), v[j].x, v[j].z);
                }
                if (hx_half == 0) {
#pragma unroll
                    for (int j = 0; j < 4; j++) {
                        if (v[4 + j].y != flag || v[4 + j].w != flag) v[4 + j] = poll_ll(hx_src + j * 256 + 128, flag);
                        sts64(hx_dstB + j * 64 + bo, v[4 + j].x, v[4 + j].z);
                    }
                }
            }
            cp_async_wait<0>();
            bar_sync(BAR_CTL, 128);
            PROF(6);
            {
                uint32_t bq[4][4];
#pragma unroll
                for (int kk = 0; kk < 4; kk++) ldsm_x4(bq[kk], qb + kk * 64);
                float sc[3][4];
#pragma unroll
                for (int m = 0; m < 3; m++) {
                    uint32_t a[8][4];
#pragma unroll
                    for (int kk = 0; kk < 8; kk++) ldsm_x4(a[kk], ka0 + bo + m * (16 * HL * 2) + kk * 32);
                    float s0[4] = {0.f, 0.f, 0.f, 0.f}, s1[4] = {0.f, 0.f, 0.f, 0.f};
#pragma unroll
                    for (int kk = 0; kk < 4; kk++) { mma16816(s0, a[2 * kk], bq[kk][0], bq[kk][1]); mma16816(s1, a[2 * kk + 1], bq[kk][2], bq[kk][3]); }
#pragma unroll
                    for (int e = 0; e < 4; e++) sc[m][e] = rbf(rbf(s0[e] + s1[e]) * 0.08838834764831845f);
                }
                uint32_t av[2][3][4];
#pragma unroll
                for (int kt = 0; kt < 3; kt++) { ldsm_x4_t(av[0][kt], va0 + bo + kt * 16 * HL * 2); ldsm_x4_t(av[1][kt], va0 + bo + kt * 16 * HL * 2 + 32); }
                float mx0 = fmaxf(fmaxf(fmaxf(sc[0][0], sc[0][2]), fmaxf(sc[1][0], sc[1][2])), sc[2][0]);
                float mx1 = fmaxf(fmaxf(fmaxf(sc[0][1], sc[0][3]), fmaxf(sc[1][1], sc[1][3])), sc[2][1]);
#pragma unroll
                for (int o = 4; o < 32; o <<= 1) { mx0 = fmaxf(mx0, __shfl_xor_sync(0xffffffffu, mx0, o)); mx1 = fmaxf(mx1, __shfl_xor_sync(0xffffffffu, mx1, o)); }
                float sum0 = 0.f, sum1 = 0.f;
#pragma unroll
                for (int m = 0; m < 3; m++) {
#pragma unroll
                    for (int e = 0; e < 4; e++) {
                        if (m == 2 && e >= 2) { sc[m][e] = 0.f; continue; }
                        float ev = __expf(sc[m][e] - ((e & 1) ? mx1 : mx0));
                        sc[m][e] = ev;
                        if (e & 1) sum1 += ev; else sum0 += ev;
                    }
                }
#pragma unroll
                for (int o = 4; o < 32; o <<= 1) { sum0 += __shfl_xor_sync(0xffffffffu, sum0, o); sum1 += __shfl_xor_sync(0xffffffffu, sum1, o); }
                float i0 = 1.0f / sum0, i1 = 1.0f / sum1;
                uint32_t pb[3][2];
#pragma unroll
                for (int m = 0; m < 3; m++) {
#pragma unroll
                    for (int hh = 0; hh < 2; hh++) {
                        uint32_t pk = pack_bf16(sc[m][2 * hh] * i0, sc[m][2 * hh + 1] * i1);
                        asm volatile("movmatrix.sync.aligned.m8n8.trans.b16 %0, %1;" : "=r"(pb[m][hh]) : "r"(pk));
                    }
                }
                PROF(7);
#pragma unroll
                for (int m = 0; m < 2; m++) {
                    float o[4] = {0.f, 0.f, 0.f, 0.f};
#pragma unroll
                    for (int kt = 0; kt < 3; kt++) mma16816(o, av[m][kt], pb[kt][0], pb[kt][1]);
                    int d0 = cw * 32 + m * 16 + g;
                    sm.om[2 * t][d0] = __float2bfloat16_rn(o[0]);
                    sm.om[2 * t + 1][d0] = __float2bfloat16_rn(o[1]);
                    sm.om[2 * t][d0 + 8] = __float2bfloat16_rn(o[2]);
                    sm.om[2 * t + 1][d0 + 8] = __float2bfloat16_rn(o[3]);
                }
            }
            bar_sync(BAR_CTL, 128);
            PROF(8);
            {
                float acc[5][4];
#pragma unroll
                for (int mi = 0; mi < 5; mi++) { acc[mi][0] = acc[mi][1] = acc[mi][2] = acc[mi][3] = 0.f; }
                uint32_t b[2][4];
                ldsm_x4(b[0], ob); ldsm_x4(b[1], ob + 64);
#pragma unroll
                for (int ki = 0; ki < 4; ki++)
#pragma unroll
                    for (int mi = 0; mi < 5; mi++) mma16816(acc[mi], wf[mi * 4 + ki], b[ki >> 1][(ki & 1) * 2], b[ki >> 1][(ki & 1) * 2 + 1]);
                if (kh == 1) {
#pragma unroll
                    for (int mi = 0; mi < 5; mi++)
                        *reinterpret_cast<float4*>(&sm.wred[mg][mi][lane * 4]) = make_float4(acc[mi][0], acc[mi][1], acc[mi][2], acc[mi][3]);
                }
                bar_sync(BAR_WO + mg, 64);
                if (kh == 0) {
                    float* dst = acc_dst_g + (size_t)s * (MEM_ * D_);
#pragma unroll
                    for (int mi = 0; mi < 5; mi++) {
                        float4 o2 = *reinterpret_cast<float4*>(&sm.wred[mg][mi][lane * 4]);
                        asm volatile("red.global.add.v2.f32 [%0], {%1,%2};" ::"l"(dst + mi * 128), "f"(acc[mi][0] + o2.x), "f"(acc[mi][1] + o2.y) : "memory");
                        asm volatile("red.global.add.v2.f32 [%0], {%1,%2};" ::"l"(dst + mi * 128 + 64), "f"(acc[mi][2] + o2.z), "f"(acc[mi][3] + o2.w) : "memory");
                    }
                    __threadfence();
                    __syncwarp();
                    if (lane == 0) atomicAdd(&g_cnt[s * 32], 1u);
                }
            }
            if (FUSE_X) bar_arrive(BAR_GO, RT);
            PROF(9);
            prefetch_kv(s + 1, buf ^ 1);
            PROF(10);
        }
    }
}

__global__ void __launch_bounds__(128)
attn_x_kernel() {
    __shared__ __align__(16) bf16 sq[32][HL], sk[48][HL], sv[48][HL];
    const int s = blockIdx.x >> 5, h = blockIdx.x & 31;
    const int tid = threadIdx.x, lane = tid & 31, w = tid >> 5, g = lane >> 2, t = lane & 3;
    for (int i = tid; i < (32 + 40 + 40) * 16; i += 128) {
        int r = i >> 4, ch = i & 15;
        const bf16* src; bf16* dst;
        if (r < 32) { src = g_qkv + (size_t)(s * SEG_ + r) * (3 * HD_) + h * DH_; dst = sq[r]; }
        else if (r < 72) { int rr = r - 32; dst = sk[rr];
            src = rr < 8 ? g_kmem + ((size_t)s * MEM_ + rr) * HD_ + h * DH_ : g_qkv + (size_t)(s * SEG_ + rr - 8) * (3 * HD_) + HD_ + h * DH_; }
        else { int rr = r - 72; dst = sv[rr];
            src = rr < 8 ? g_vmem + ((size_t)s * MEM_ + rr) * HD_ + h * DH_ : g_qkv + (size_t)(s * SEG_ + rr - 8) * (3 * HD_) + 2 * HD_ + h * DH_; }
        cp_async16(smem_u32(dst + ch * 8), src + ch * 8);
    }
    cp_async_commit();
    for (int i = tid; i < 8 * 16; i += 128) *reinterpret_cast<uint4*>(&sv[40 + (i >> 4)][(i & 15) * 8]) = make_uint4(0, 0, 0, 0);
    cp_async_wait<0>();
    __syncthreads();
    const int rh = w & 1, dhh = w >> 1;
    float sc[5][4];
#pragma unroll
    for (int n = 0; n < 5; n++) sc[n][0] = sc[n][1] = sc[n][2] = sc[n][3] = 0.f;
#pragma unroll
    for (int kk = 0; kk < 8; kk++) {
        uint32_t a[4];
        ldsm_x4(a, smem_u32(&sq[rh * 16 + (lane & 15)][kk * 16 + (lane >> 4) * 8]));
#pragma unroll
        for (int n = 0; n < 5; n++) {
            uint32_t b[2];
            asm volatile("ldmatrix.sync.aligned.m8n8.x2.shared.b16 {%0,%1}, [%2];" : "=r"(b[0]), "=r"(b[1])
                         : "r"(smem_u32(&sk[n * 8 + (lane & 7)][kk * 16 + ((lane >> 3) & 1) * 8])));
            mma16816(sc[n], a, b[0], b[1]);
        }
    }
    const float scale = 0.08838834764831845f;
    float mx[2] = {-INFINITY, -INFINITY};
#pragma unroll
    for (int n = 0; n < 5; n++)
#pragma unroll
        for (int e = 0; e < 4; e++) {
            int row = rh * 16 + g + (e >> 1) * 8, key = n * 8 + 2 * t + (e & 1);
            float v = rbf(rbf(sc[n][e]) * scale);
            if (key > row + MEM_) v = -INFINITY;
            sc[n][e] = v;
            mx[e >> 1] = fmaxf(mx[e >> 1], v);
        }
#pragma unroll
    for (int o = 1; o < 4; o <<= 1) { mx[0] = fmaxf(mx[0], __shfl_xor_sync(0xffffffffu, mx[0], o)); mx[1] = fmaxf(mx[1], __shfl_xor_sync(0xffffffffu, mx[1], o)); }
    float sum[2] = {0.f, 0.f};
#pragma unroll
    for (int n = 0; n < 5; n++)
#pragma unroll
        for (int e = 0; e < 4; e++) { float ev = __expf(sc[n][e] - mx[e >> 1]); sc[n][e] = ev; sum[e >> 1] += ev; }
#pragma unroll
    for (int o = 1; o < 4; o <<= 1) { sum[0] += __shfl_xor_sync(0xffffffffu, sum[0], o); sum[1] += __shfl_xor_sync(0xffffffffu, sum[1], o); }
    float inv[2] = {1.0f / sum[0], 1.0f / sum[1]};
    uint32_t pa[3][4];
#pragma unroll
    for (int kt = 0; kt < 3; kt++) {
        pa[kt][0] = pack_bf16(sc[2 * kt][0] * inv[0], sc[2 * kt][1] * inv[0]);
        pa[kt][1] = pack_bf16(sc[2 * kt][2] * inv[1], sc[2 * kt][3] * inv[1]);
        if (kt < 2) {
            pa[kt][2] = pack_bf16(sc[2 * kt + 1][0] * inv[0], sc[2 * kt + 1][1] * inv[0]);
            pa[kt][3] = pack_bf16(sc[2 * kt + 1][2] * inv[1], sc[2 * kt + 1][3] * inv[1]);
        } else { pa[kt][2] = 0u; pa[kt][3] = 0u; }
    }
#pragma unroll
    for (int n = 0; n < 8; n++) {
        float o[4] = {0.f, 0.f, 0.f, 0.f};
#pragma unroll
        for (int kt = 0; kt < 3; kt++) {
            uint32_t b[2];
            asm volatile("ldmatrix.sync.aligned.m8n8.x2.trans.shared.b16 {%0,%1}, [%2];" : "=r"(b[0]), "=r"(b[1])
                         : "r"(smem_u32(&sv[kt * 16 + (lane & 15)][dhh * 64 + n * 8])));
            mma16816(o, pa[kt], b[0], b[1]);
        }
        int row = s * SEG_ + rh * 16 + g;
        bf16* dst = g_o + (size_t)row * HD_ + h * DH_ + dhh * 64 + n * 8 + 2 * t;
        *reinterpret_cast<uint32_t*>(dst) = pack_bf16(o[0], o[1]);
        *reinterpret_cast<uint32_t*>(dst + 8 * HD_) = pack_bf16(o[2], o[3]);
    }
}

typedef CUresult (*PFN_encodeTiled)(CUtensorMap*, CUtensorMapDataType, cuuint32_t, void*, const cuuint64_t*,
                                    const cuuint64_t*, const cuuint32_t*, const cuuint32_t*, CUtensorMapInterleave,
                                    CUtensorMapSwizzle, CUtensorMapL2promotion, CUtensorMapFloatOOBfill);
static PFN_encodeTiled p_encode = nullptr;

static CUtensorMap make_map(const void* ptr, uint64_t rows, uint64_t cols, uint64_t ld, uint32_t box_rows) {
    CUtensorMap m;
    cuuint64_t dims[2] = {cols, rows};
    cuuint64_t strides[1] = {ld * 2};
    cuuint32_t box[2] = {64, box_rows};
    cuuint32_t es[2] = {1, 1};
    p_encode(&m, CU_TENSOR_MAP_DATA_TYPE_BFLOAT16, 2, const_cast<void*>(ptr), dims, strides, box, es,
             CU_TENSOR_MAP_INTERLEAVE_NONE, CU_TENSOR_MAP_SWIZZLE_128B, CU_TENSOR_MAP_L2_PROMOTION_L2_128B,
             CU_TENSOR_MAP_FLOAT_OOB_FILL_NONE);
    return m;
}

template <int BN, int EPI>
static void launch_gemm(const CUtensorMap& a, const CUtensorMap& b0, const CUtensorMap& b1, const CUtensorMap& b2,
                        int nPerB, int M, int N, int K, EpiParams ep, cudaStream_t st, int splitk = 1) {
    constexpr int STAGE = 16384 + (BN / 64) * 8192;
    constexpr int NST = (200 * 1024) / STAGE;
    constexpr int SMEM = NST * STAGE + 1024;
    cudaFuncSetAttribute(gemm_kernel<BN, EPI>, cudaFuncAttributeMaxDynamicSharedMemorySize, SMEM);
    dim3 grid((N + BN - 1) / BN, M / 128, splitk);
    gemm_kernel<BN, EPI><<<grid, 384, SMEM, st>>>(a, b0, b1, b2, nPerB, N, K, ep);
}

extern "C" void kernel_launch(void* const* d_in, const int* in_sizes, int n_in, void* d_out, int out_size) {
    const bf16* x    = (const bf16*)d_in[0];
    const bf16* mem0 = (const bf16*)d_in[1];
    const bf16* Wq   = (const bf16*)d_in[2];
    const bf16* Wk   = (const bf16*)d_in[3];
    const bf16* Wv   = (const bf16*)d_in[4];
    const bf16* Wo   = (const bf16*)d_in[5];
    const bf16* w_in  = (const bf16*)d_in[8];
    const bf16* w_sp  = (const bf16*)d_in[9];
    const bf16* b_sp  = (const bf16*)d_in[10];
    const bf16* w_out = (const bf16*)d_in[11];
    bf16* out = (bf16*)d_out;
    cudaStream_t st = cudaStreamPerThread;

    if (!p_encode) {
        cudaDriverEntryPointQueryResult qr;
        cudaGetDriverEntryPoint("cuTensorMapEncodeTiled", (void**)&p_encode, cudaEnableDefault, &qr);
    }
    void *p_xn, *p_qkv, *p_z, *p_zg, *p_gate, *p_o, *p_acc, *p_cnt, *p_hx;
    cudaGetSymbolAddress(&p_xn, g_xn); cudaGetSymbolAddress(&p_qkv, g_qkv); cudaGetSymbolAddress(&p_z, g_z);
    cudaGetSymbolAddress(&p_zg, g_zg); cudaGetSymbolAddress(&p_gate, g_gate); cudaGetSymbolAddress(&p_o, g_o);
    cudaGetSymbolAddress(&p_acc, g_acc); cudaGetSymbolAddress(&p_cnt, g_cnt); cudaGetSymbolAddress(&p_hx, g_hx);

    CUtensorMap mA_xn  = make_map(p_xn, S_, D_, D_, 128);
    CUtensorMap mA_wsp = make_map(w_sp, S_, S_, S_, 128);
    CUtensorMap mA_zg  = make_map(p_zg, S_, FH_, FH_, 128);
    CUtensorMap mA_o   = make_map(p_o, S_, HD_, HD_, 128);
    CUtensorMap mB_wq  = make_map(Wq, D_, HD_, HD_, 64);
    CUtensorMap mB_wk  = make_map(Wk, D_, HD_, HD_, 64);
    CUtensorMap mB_wv  = make_map(Wv, D_, HD_, HD_, 64);
    CUtensorMap mB_win = make_map(w_in, D_, F_, F_, 64);
    CUtensorMap mB_z2  = make_map((bf16*)p_z + FH_, S_, FH_, F_, 64);
    CUtensorMap mB_wout = make_map(w_out, FH_, D_, D_, 64);
    CUtensorMap mB_wo  = make_map(Wo, HD_, D_, D_, 64);

    cudaMemsetAsync(p_acc, 0, sizeof(float) * NSEG_ * MEM_ * D_, st);
    cudaMemsetAsync(p_cnt, 0, sizeof(unsigned) * NSEG_ * 32, st);
    void* p_xcnt; cudaGetSymbolAddress(&p_xcnt, g_xcnt);
    cudaMemsetAsync(p_xcnt, 0, sizeof(unsigned) * H_ * NSEG_, st);
    cudaMemsetAsync(p_hx, 0, sizeof(uint2) * H_ * 4 * 256 * 2, st);

    ln_kernel<<<S_ / 8, 256, 0, st>>>(x);
    if (!FUSE_X) { EpiParams ep{(bf16*)p_qkv, 3 * HD_, nullptr, nullptr}; launch_gemm<256, EPI_STORE>(mA_xn, mB_wq, mB_wk, mB_wv, HD_, S_, 3 * HD_, D_, ep, st); }
    { EpiParams ep{(bf16*)p_z, F_, nullptr, nullptr}; launch_gemm<128, EPI_GELU>(mA_xn, mB_win, mB_win, mB_win, 1 << 20, S_, F_, D_, ep, st); }
    ln2_kernel<<<S_ / 8, 256, 0, st>>>();
    { EpiParams ep{(bf16*)p_zg, FH_, (const bf16*)p_z, b_sp}; launch_gemm<128, EPI_SP>(mA_wsp, mB_z2, mB_z2, mB_z2, 1 << 20, S_, FH_, S_, ep, st); }
    { EpiParams ep{(bf16*)p_gate, D_, nullptr, nullptr}; launch_gemm<128, EPI_SILU>(mA_zg, mB_wout, mB_wout, mB_wout, 1 << 20, S_, D_, FH_, ep, st); }
    constexpr int RSM = (int)sizeof(RecurSmem) > 16 * 10240 ? (int)sizeof(RecurSmem) : 16 * 10240;
    cudaFuncSetAttribute(recur_kernel, cudaFuncAttributeMaxDynamicSharedMemorySize, RSM);
    recur_kernel<<<128, RT, RSM, st>>>(mem0, Wq, Wk, Wv, Wo);
    attn_x_kernel<<<NSEG_ * H_, 128, 0, st>>>();
    { EpiParams ep{out, D_, x, (const bf16*)p_gate}; launch_gemm<128, EPI_PART>(mA_o, mB_wo, mB_wo, mB_wo, 1 << 20, S_, D_, HD_, ep, st, 2); }
    final_combine_kernel<<<S_ * D_ / 4 / 256, 256, 0, st>>>(x, out);
}
```

```cpp
#include <cuda_runtime.h>
#include <cuda_bf16.h>
#include <cuda.h>
#include <stdint.h>
#define NO_PROBE_HX 1

typedef __nv_bfloat16 bf16;

constexpr int S_   = 2048;
constexpr int D_   = 640;
constexpr int H_   = 32;
constexpr int DH_  = 128;
constexpr int MEM_ = 8;
constexpr int SEG_ = 32;
constexpr int NSEG_ = S_ / SEG_;
constexpr int HD_  = H_ * DH_;
constexpr int F_   = 1728;
constexpr int FH_  = 864;

__device__ bf16 g_xn[S_ * D_];
__device__ bf16 g_qkv[(size_t)S_ * 3 * HD_];
__device__ bf16 g_z[S_ * F_];
__device__ bf16 g_zg[S_ * FH_];
__device__ bf16 g_gate[S_ * D_];
__device__ bf16 g_kmem[NSEG_ * MEM_ * HD_];
__device__ bf16 g_vmem[NSEG_ * MEM_ * HD_];
__device__ bf16 g_o[(size_t)S_ * HD_];
__device__ float g_acc[NSEG_ * MEM_ * D_];
__device__ unsigned g_cnt[NSEG_ * 32];
__device__ unsigned g_xcnt[H_ * NSEG_];
__device__ uint2 g_hx[H_ * 4 * 256 * 2];

__device__ __forceinline__ uint32_t smem_u32(const void* p) { return (uint32_t)__cvta_generic_to_shared(p); }
__device__ __forceinline__ float bf2f(bf16 v) { return __bfloat162float(v); }
__device__ __forceinline__ float rbf(float v) { return __bfloat162float(__float2bfloat16_rn(v)); }
__device__ __forceinline__ uint32_t pack_bf16(float lo, float hi) {
    __nv_bfloat162 t = __floats2bfloat162_rn(lo, hi);
    return *reinterpret_cast<uint32_t*>(&t);
}
__device__ __forceinline__ float lo_f(uint32_t u) { return __uint_as_float(u << 16); }
__device__ __forceinline__ float hi_f(uint32_t u) { return __uint_as_float(u & 0xffff0000u); }

__device__ __forceinline__ void mbar_init(uint32_t bar, uint32_t cnt) {
    asm volatile("mbarrier.init.shared.b64 [%0], %1;" ::"r"(bar), "r"(cnt));
}
__device__ __forceinline__ void mbar_expect_tx(uint32_t bar, uint32_t bytes) {
    asm volatile("mbarrier.arrive.expect_tx.shared.b64 _, [%0], %1;" ::"r"(bar), "r"(bytes) : "memory");
}
__device__ __forceinline__ void mbar_arrive(uint32_t bar) {
    asm volatile("mbarrier.arrive.shared.b64 _, [%0];" ::"r"(bar) : "memory");
}
__device__ __forceinline__ void mbar_wait(uint32_t bar, uint32_t parity) {
    asm volatile(
        "{\n .reg .pred p;\n"
        "WAIT_%=:\n"
        " mbarrier.try_wait.parity.shared.b64 p, [%0], %1;\n"
        " @p bra DONE_%=;\n"
        " bra WAIT_%=;\n"
        "DONE_%=:\n}\n" ::"r"(bar), "r"(parity) : "memory");
}
__device__ __forceinline__ void tma_load_2d(uint32_t dst, const CUtensorMap* tm, uint32_t bar, int c0, int c1) {
    asm volatile(
        "cp.async.bulk.tensor.2d.shared::cluster.global.mbarrier::complete_tx::bytes [%0], [%1, {%3, %4}], [%2];"
        ::"r"(dst), "l"(tm), "r"(bar), "r"(c0), "r"(c1) : "memory");
}
__device__ __forceinline__ void wgmma_fence() { asm volatile("wgmma.fence.sync.aligned;" ::: "memory"); }
__device__ __forceinline__ void wgmma_commit() { asm volatile("wgmma.commit_group.sync.aligned;" ::: "memory"); }
template <int N> __device__ __forceinline__ void wgmma_wait() { asm volatile("wgmma.wait_group.sync.aligned %0;" ::"n"(N) : "memory"); }

__device__ __forceinline__ uint64_t make_desc(uint32_t addr, uint32_t lbo, uint32_t sbo) {
    return (uint64_t)((addr & 0x3FFFF) >> 4) | ((uint64_t)(lbo >> 4) << 16) | ((uint64_t)(sbo >> 4) << 32) | (1ull << 62);
}

template <int N> struct Wgmma;
template <> struct Wgmma<128> {
    static __device__ __forceinline__ void mma(float* d, uint64_t da, uint64_t db, int sd) {
        asm volatile(
            "{\n.reg .pred p;\nsetp.ne.b32 p, %66, 0;\n"
            "wgmma.mma_async.sync.aligned.m64n128k16.f32.bf16.bf16 "
            "{%0,%1,%2,%3,%4,%5,%6,%7,%8,%9,%10,%11,%12,%13,%14,%15,"
            "%16,%17,%18,%19,%20,%21,%22,%23,%24,%25,%26,%27,%28,%29,%30,%31,"
            "%32,%33,%34,%35,%36,%37,%38,%39,%40,%41,%42,%43,%44,%45,%46,%47,"
            "%48,%49,%50,%51,%52,%53,%54,%55,%56,%57,%58,%59,%60,%61,%62,%63},"
            "%64,%65,p,1,1,0,1;\n}\n"
            : "+f"(d[0]), "+f"(d[1]), "+f"(d[2]), "+f"(d[3]), "+f"(d[4]), "+f"(d[5]), "+f"(d[6]), "+f"(d[7]),
              "+f"(d[8]), "+f"(d[9]), "+f"(d[10]), "+f"(d[11]), "+f"(d[12]), "+f"(d[13]), "+f"(d[14]), "+f"(d[15]),
              "+f"(d[16]), "+f"(d[17]), "+f"(d[18]), "+f"(d[19]), "+f"(d[20]), "+f"(d[21]), "+f"(d[22]), "+f"(d[23]),
              "+f"(d[24]), "+f"(d[25]), "+f"(d[26]), "+f"(d[27]), "+f"(d[28]), "+f"(d[29]), "+f"(d[30]), "+f"(d[31]),
              "+f"(d[32]), "+f"(d[33]), "+f"(d[34]), "+f"(d[35]), "+f"(d[36]), "+f"(d[37]), "+f"(d[38]), "+f"(d[39]),
              "+f"(d[40]), "+f"(d[41]), "+f"(d[42]), "+f"(d[43]), "+f"(d[44]), "+f"(d[45]), "+f"(d[46]), "+f"(d[47]),
              "+f"(d[48]), "+f"(d[49]), "+f"(d[50]), "+f"(d[51]), "+f"(d[52]), "+f"(d[53]), "+f"(d[54]), "+f"(d[55]),
              "+f"(d[56]), "+f"(d[57]), "+f"(d[58]), "+f"(d[59]), "+f"(d[60]), "+f"(d[61]), "+f"(d[62]), "+f"(d[63])
            : "l"(da), "l"(db), "r"(sd));
    }
};
template <> struct Wgmma<192> {
    static __device__ __forceinline__ void mma(float* d, uint64_t da, uint64_t db, int sd) {
        asm volatile(
            "{\n.reg .pred p;\nsetp.ne.b32 p, %98, 0;\n"
            "wgmma.mma_async.sync.aligned.m64n192k16.f32.bf16.bf16 "
            "{%0,%1,%2,%3,%4,%5,%6,%7,%8,%9,%10,%11,%12,%13,%14,%15,"
            "%16,%17,%18,%19,%20,%21,%22,%23,%24,%25,%26,%27,%28,%29,%30,%31,"
            "%32,%33,%34,%35,%36,%37,%38,%39,%40,%41,%42,%43,%44,%45,%46,%47,"
            "%48,%49,%50,%51,%52,%53,%54,%55,%56,%57,%58,%59,%60,%61,%62,%63,"
            "%64,%65,%66,%67,%68,%69,%70,%71,%72,%73,%74,%75,%76,%77,%78,%79,"
            "%80,%81,%82,%83,%84,%85,%86,%87,%88,%89,%90,%91,%92,%93,%94,%95},"
            "%96,%97,p,1,1,0,1;\n}\n"
            : "+f"(d[0]), "+f"(d[1]), "+f"(d[2]), "+f"(d[3]), "+f"(d[4]), "+f"(d[5]), "+f"(d[6]), "+f"(d[7]),
              "+f"(d[8]), "+f"(d[9]), "+f"(d[10]), "+f"(d[11]), "+f"(d[12]), "+f"(d[13]), "+f"(d[14]), "+f"(d[15]),
              "+f"(d[16]), "+f"(d[17]), "+f"(d[18]), "+f"(d[19]), "+f"(d[20]), "+f"(d[21]), "+f"(d[22]), "+f"(d[23]),
              "+f"(d[24]), "+f"(d[25]), "+f"(d[26]), "+f"(d[27]), "+f"(d[28]), "+f"(d[29]), "+f"(d[30]), "+f"(d[31]),
              "+f"(d[32]), "+f"(d[33]), "+f"(d[34]), "+f"(d[35]), "+f"(d[36]), "+f"(d[37]), "+f"(d[38]), "+f"(d[39]),
              "+f"(d[40]), "+f"(d[41]), "+f"(d[42]), "+f"(d[43]), "+f"(d[44]), "+f"(d[45]), "+f"(d[46]), "+f"(d[47]),
              "+f"(d[48]), "+f"(d[49]), "+f"(d[50]), "+f"(d[51]), "+f"(d[52]), "+f"(d[53]), "+f"(d[54]), "+f"(d[55]),
              "+f"(d[56]), "+f"(d[57]), "+f"(d[58]), "+f"(d[59]), "+f"(d[60]), "+f"(d[61]), "+f"(d[62]), "+f"(d[63]),
              "+f"(d[64]), "+f"(d[65]), "+f"(d[66]), "+f"(d[67]), "+f"(d[68]), "+f"(d[69]), "+f"(d[70]), "+f"(d[71]),
              "+f"(d[72]), "+f"(d[73]), "+f"(d[74]), "+f"(d[75]), "+f"(d[76]), "+f"(d[77]), "+f"(d[78]), "+f"(d[79]),
              "+f"(d[80]), "+f"(d[81]), "+f"(d[82]), "+f"(d[83]), "+f"(d[84]), "+f"(d[85]), "+f"(d[86]), "+f"(d[87]),
              "+f"(d[88]), "+f"(d[89]), "+f"(d[90]), "+f"(d[91]), "+f"(d[92]), "+f"(d[93]), "+f"(d[94]), "+f"(d[95])
            : "l"(da), "l"(db), "r"(sd));
    }
};

template <> struct Wgmma<256> {
    static __device__ __forceinline__ void mma(float* d, uint64_t da, uint64_t db, int sd) {
        asm volatile(
            "{\n.reg .pred p;\nsetp.ne.b32 p, %130, 0;\n"
            "wgmma.mma_async.sync.aligned.m64n256k16.f32.bf16.bf16 "
            "{%0,%1,%2,%3,%4,%5,%6,%7,%8,%9,%10,%11,%12,%13,%14,%15,%16,%17,%18,%19,%20,%21,%22,%23,%24,%25,%26,%27,%28,%29,%30,%31,%32,%33,%34,%35,%36,%37,%38,%39,%40,%41,%42,%43,%44,%45,%46,%47,%48,%49,%50,%51,%52,%53,%54,%55,%56,%57,%58,%59,%60,%61,%62,%63,%64,%65,%66,%67,%68,%69,%70,%71,%72,%73,%74,%75,%76,%77,%78,%79,%80,%81,%82,%83,%84,%85,%86,%87,%88,%89,%90,%91,%92,%93,%94,%95,%96,%97,%98,%99,%100,%101,%102,%103,%104,%105,%106,%107,%108,%109,%110,%111,%112,%113,%114,%115,%116,%117,%118,%119,%120,%121,%122,%123,%124,%125,%126,%127},"
            "%128,%129,p,1,1,0,1;\n}\n"
            : "+f"(d[0]), "+f"(d[1]), "+f"(d[2]), "+f"(d[3]), "+f"(d[4]), "+f"(d[5]), "+f"(d[6]), "+f"(d[7]), "+f"(d[8]), "+f"(d[9]), "+f"(d[10]), "+f"(d[11]), "+f"(d[12]), "+f"(d[13]), "+f"(d[14]), "+f"(d[15]), "+f"(d[16]), "+f"(d[17]), "+f"(d[18]), "+f"(d[19]), "+f"(d[20]), "+f"(d[21]), "+f"(d[22]), "+f"(d[23]), "+f"(d[24]), "+f"(d[25]), "+f"(d[26]), "+f"(d[27]), "+f"(d[28]), "+f"(d[29]), "+f"(d[30]), "+f"(d[31]), "+f"(d[32]), "+f"(d[33]), "+f"(d[34]), "+f"(d[35]), "+f"(d[36]), "+f"(d[37]), "+f"(d[38]), "+f"(d[39]), "+f"(d[40]), "+f"(d[41]), "+f"(d[42]), "+f"(d[43]), "+f"(d[44]), "+f"(d[45]), "+f"(d[46]), "+f"(d[47]), "+f"(d[48]), "+f"(d[49]), "+f"(d[50]), "+f"(d[51]), "+f"(d[52]), "+f"(d[53]), "+f"(d[54]), "+f"(d[55]), "+f"(d[56]), "+f"(d[57]), "+f"(d[58]), "+f"(d[59]), "+f"(d[60]), "+f"(d[61]), "+f"(d[62]), "+f"(d[63]), "+f"(d[64]), "+f"(d[65]), "+f"(d[66]), "+f"(d[67]), "+f"(d[68]), "+f"(d[69]), "+f"(d[70]), "+f"(d[71]), "+f"(d[72]), "+f"(d[73]), "+f"(d[74]), "+f"(d[75]), "+f"(d[76]), "+f"(d[77]), "+f"(d[78]), "+f"(d[79]), "+f"(d[80]), "+f"(d[81]), "+f"(d[82]), "+f"(d[83]), "+f"(d[84]), "+f"(d[85]), "+f"(d[86]), "+f"(d[87]), "+f"(d[88]), "+f"(d[89]), "+f"(d[90]), "+f"(d[91]), "+f"(d[92]), "+f"(d[93]), "+f"(d[94]), "+f"(d[95]), "+f"(d[96]), "+f"(d[97]), "+f"(d[98]), "+f"(d[99]), "+f"(d[100]), "+f"(d[101]), "+f"(d[102]), "+f"(d[103]), "+f"(d[104]), "+f"(d[105]), "+f"(d[106]), "+f"(d[107]), "+f"(d[108]), "+f"(d[109]), "+f"(d[110]), "+f"(d[111]), "+f"(d[112]), "+f"(d[113]), "+f"(d[114]), "+f"(d[115]), "+f"(d[116]), "+f"(d[117]), "+f"(d[118]), "+f"(d[119]), "+f"(d[120]), "+f"(d[121]), "+f"(d[122]), "+f"(d[123]), "+f"(d[124]), "+f"(d[125]), "+f"(d[126]), "+f"(d[127])
            : "l"(da), "l"(db), "r"(sd));
    }
};
template <int W>
__device__ __forceinline__ void ln_row(const bf16* __restrict__ src, bf16* __restrict__ dst, int lane) {
    constexpr int NP = W / 64;
    constexpr int REM = (W / 2) % 32;
    uint32_t v[NP + 1];
    const uint32_t* s32 = reinterpret_cast<const uint32_t*>(src);
    float sum = 0.f;
#pragma unroll
    for (int i = 0; i < NP; i++) { v[i] = s32[i * 32 + lane]; sum += lo_f(v[i]) + hi_f(v[i]); }
    if (REM) { v[NP] = (lane < REM) ? s32[NP * 32 + lane] : 0u; if (lane < REM) sum += lo_f(v[NP]) + hi_f(v[NP]); }
#pragma unroll
    for (int o = 16; o; o >>= 1) sum += __shfl_xor_sync(0xffffffffu, sum, o);
    float mean = sum * (1.0f / W);
    float vs = 0.f;
#pragma unroll
    for (int i = 0; i < NP; i++) { float a = lo_f(v[i]) - mean, b = hi_f(v[i]) - mean; vs += a * a + b * b; }
    if (REM && lane < REM) { float a = lo_f(v[NP]) - mean, b = hi_f(v[NP]) - mean; vs += a * a + b * b; }
#pragma unroll
    for (int o = 16; o; o >>= 1) vs += __shfl_xor_sync(0xffffffffu, vs, o);
    float var = rbf(vs * (1.0f / W));
    float mb = rbf(mean);
    float den = rbf(sqrtf(rbf(var + 1e-5f)));
    uint32_t* d32 = reinterpret_cast<uint32_t*>(dst);
#pragma unroll
    for (int i = 0; i < NP; i++) d32[i * 32 + lane] = pack_bf16(rbf(lo_f(v[i]) - mb) / den, rbf(hi_f(v[i]) - mb) / den);
    if (REM && lane < REM) d32[NP * 32 + lane] = pack_bf16(rbf(lo_f(v[NP]) - mb) / den, rbf(hi_f(v[NP]) - mb) / den);
}

__global__ void ln_kernel(const bf16* __restrict__ x) {
    int row = blockIdx.x * 8 + (threadIdx.x >> 5);
    ln_row<D_>(x + (size_t)row * D_, g_xn + (size_t)row * D_, threadIdx.x & 31);
}
__global__ void ln2_kernel() {
    int row = blockIdx.x * 8 + (threadIdx.x >> 5);
    bf16* p = g_z + (size_t)row * F_ + FH_;
    ln_row<FH_>(p, p, threadIdx.x & 31);
}

enum { EPI_STORE = 0, EPI_GELU = 1, EPI_SP = 2, EPI_SILU = 3, EPI_FINAL = 4, EPI_PART = 5 };
__device__ float g_part[2 * S_ * D_];
struct EpiParams {
    bf16* out; int ldo;
    const bf16* aux0;
    const bf16* aux1;
};

__device__ __forceinline__ float gelu_tanh_f(float x) {
    const float k0 = 0.7978845608028654f, k1 = 0.044715f;
    float inner = k0 * (x + k1 * x * x * x);
    return 0.5f * x * (1.0f + tanhf(inner));
}
__device__ __forceinline__ float silu_f(float x) { return x / (1.0f + expf(-x)); }

template <int BN, int EPI>
__global__ void __launch_bounds__(384, 1)
gemm_kernel(const __grid_constant__ CUtensorMap tmA, const __grid_constant__ CUtensorMap tmB0,
            const __grid_constant__ CUtensorMap tmB1, const __grid_constant__ CUtensorMap tmB2,
            int nPerB, int N, int K, EpiParams ep) {
    constexpr int BM = 128, BK = 64;
    constexpr int A_BYTES = BM * BK * 2;
    constexpr int B_BYTES = (BN / 64) * 8192;
    constexpr int STAGE = A_BYTES + B_BYTES;
    constexpr int NST = (200 * 1024) / STAGE;
    constexpr int OLD = BN + 8;
    extern __shared__ __align__(1024) uint8_t smem_raw[];
    uint8_t* smem = (uint8_t*)(((uintptr_t)smem_raw + 1023) & ~(uintptr_t)1023);
    __shared__ __align__(8) uint64_t full_bar[NST], empty_bar[NST];

    const int tid = threadIdx.x, wg = tid >> 7;
    const int m0 = blockIdx.y * BM, n0 = blockIdx.x * BN;
    const int nk = (K + BK - 1) / BK / gridDim.z;
    const int kbase = blockIdx.z * nk;

    if (tid == 0) {
        for (int i = 0; i < NST; i++) { mbar_init(smem_u32(&full_bar[i]), 1); mbar_init(smem_u32(&empty_bar[i]), 2); }
        asm volatile("fence.mbarrier_init.release.cluster;" ::: "memory");
    }
    __syncthreads();

    if (wg == 0) {
        if (tid == 0) {
            const int bsel = n0 / nPerB;
            const CUtensorMap* tmB = bsel == 0 ? &tmB0 : (bsel == 1 ? &tmB1 : &tmB2);
            const int nb = n0 - bsel * nPerB;
            for (int kt = 0; kt < nk; kt++) {
                int st = kt % NST; uint32_t ph = (kt / NST) & 1;
                mbar_wait(smem_u32(&empty_bar[st]), ph ^ 1);
                uint32_t fb = smem_u32(&full_bar[st]);
                mbar_expect_tx(fb, STAGE);
                uint32_t sa = smem_u32(smem + st * STAGE);
                tma_load_2d(sa, &tmA, fb, (kbase + kt) * BK, m0);
#pragma unroll
                for (int j = 0; j < BN / 64; j++) tma_load_2d(sa + A_BYTES + j * 8192, tmB, fb, nb + j * 64, (kbase + kt) * BK);
            }
        }
    } else {
        const int cw = wg - 1;
        float acc[BN / 2];
        for (int kt = 0; kt < nk; kt++) {
            int st = kt % NST; uint32_t ph = (kt / NST) & 1;
            mbar_wait(smem_u32(&full_bar[st]), ph);
            uint32_t sa = smem_u32(smem + st * STAGE) + cw * 64 * 128;
            uint32_t sb = smem_u32(smem + st * STAGE) + A_BYTES;
            wgmma_fence();
#pragma unroll
            for (int k = 0; k < BK / 16; k++) {
                uint64_t da = make_desc(sa + k * 32, 16, 1024);
                uint64_t db = make_desc(sb + k * 2048, 8192, 1024);
                Wgmma<BN>::mma(acc, da, db, (kt | k) != 0);
            }
            wgmma_commit();
            wgmma_wait<1>();
            if (kt > 0 && (tid & 127) == 0) mbar_arrive(smem_u32(&empty_bar[(kt - 1) % NST]));
        }
        wgmma_wait<0>();
        if (EPI == EPI_PART) {
            const int lane = tid & 31, wi = (tid >> 5) & 3, g = lane >> 2, t = lane & 3;
            float* dst = g_part + (size_t)blockIdx.z * (S_ * D_) + (size_t)(m0 + cw * 64 + wi * 16 + g) * D_ + n0 + 2 * t;
#pragma unroll
            for (int j = 0; j < BN / 8; j++) {
                *reinterpret_cast<float2*>(dst + j * 8) = make_float2(acc[4 * j], acc[4 * j + 1]);
                *reinterpret_cast<float2*>(dst + 8 * D_ + j * 8) = make_float2(acc[4 * j + 2], acc[4 * j + 3]);
            }
            return;
        }
        asm volatile("bar.sync 1, 256;" ::: "memory");
        const int lane = tid & 31, wi = (tid >> 5) & 3, g = lane >> 2, t = lane & 3;
        bf16* stg = reinterpret_cast<bf16*>(smem) + cw * 64 * OLD;
#pragma unroll
        for (int j = 0; j < BN / 8; j++) {
            *reinterpret_cast<uint32_t*>(&stg[(wi * 16 + g) * OLD + j * 8 + 2 * t]) = pack_bf16(acc[4 * j], acc[4 * j + 1]);
            *reinterpret_cast<uint32_t*>(&stg[(wi * 16 + g + 8) * OLD + j * 8 + 2 * t]) = pack_bf16(acc[4 * j + 2], acc[4 * j + 3]);
        }
        asm volatile("bar.sync %0, 128;" ::"r"(2 + cw) : "memory");
        constexpr int CPR = BN / 8;
        const int ltid = tid & 127;
#pragma unroll 4
        for (int i = ltid; i < 64 * CPR; i += 128) {
            int r = i / CPR, ch = i % CPR;
            int row = m0 + cw * 64 + r, col = n0 + ch * 8;
            if (col >= N) continue;
            uint4 v = *reinterpret_cast<const uint4*>(&stg[r * OLD + ch * 8]);
            uint32_t u[4] = {v.x, v.y, v.z, v.w}, o[4];
            if (EPI == EPI_STORE) {
#pragma unroll
                for (int q = 0; q < 4; q++) o[q] = u[q];
            } else if (EPI == EPI_GELU) {
#pragma unroll
                for (int q = 0; q < 4; q++) o[q] = pack_bf16(gelu_tanh_f(lo_f(u[q])), gelu_tanh_f(hi_f(u[q])));
            } else if (EPI == EPI_SP) {
                float bb = bf2f(ep.aux1[row]);
                uint4 z = *reinterpret_cast<const uint4*>(ep.aux0 + (size_t)row * F_ + col);
                uint32_t zz[4] = {z.x, z.y, z.z, z.w};
#pragma unroll
                for (int q = 0; q < 4; q++) o[q] = pack_bf16(lo_f(zz[q]) * rbf(lo_f(u[q]) + bb), hi_f(zz[q]) * rbf(hi_f(u[q]) + bb));
            } else if (EPI == EPI_SILU) {
#pragma unroll
                for (int q = 0; q < 4; q++) o[q] = pack_bf16(silu_f(lo_f(u[q])), silu_f(hi_f(u[q])));
            } else {
                uint4 xv = *reinterpret_cast<const uint4*>(ep.aux0 + (size_t)row * D_ + col);
                uint4 gv = *reinterpret_cast<const uint4*>(ep.aux1 + (size_t)row * D_ + col);
                uint32_t xx[4] = {xv.x, xv.y, xv.z, xv.w}, gg[4] = {gv.x, gv.y, gv.z, gv.w};
#pragma unroll
                for (int q = 0; q < 4; q++)
                    o[q] = pack_bf16(lo_f(xx[q]) + rbf(lo_f(u[q]) * lo_f(gg[q])), hi_f(xx[q]) + rbf(hi_f(u[q]) * hi_f(gg[q])));
            }
            *reinterpret_cast<uint4*>(ep.out + (size_t)row * ep.ldo + col) = make_uint4(o[0], o[1], o[2], o[3]);
        }
    }
}

__global__ void final_combine_kernel(const bf16* __restrict__ x, bf16* __restrict__ out) {
    int i = (blockIdx.x * blockDim.x + threadIdx.x) * 4;
    float4 a = *reinterpret_cast<const float4*>(g_part + i), b = *reinterpret_cast<const float4*>(g_part + S_ * D_ + i);
    uint2 xv = *reinterpret_cast<const uint2*>(x + i), gv = *reinterpret_cast<const uint2*>(g_gate + i);
    float s0 = rbf(a.x + b.x), s1 = rbf(a.y + b.y), s2 = rbf(a.z + b.z), s3 = rbf(a.w + b.w);
    uint2 o;
    o.x = pack_bf16(lo_f(xv.x) + rbf(s0 * lo_f(gv.x)), hi_f(xv.x) + rbf(s1 * hi_f(gv.x)));
    o.y = pack_bf16(lo_f(xv.y) + rbf(s2 * lo_f(gv.y)), hi_f(xv.y) + rbf(s3 * hi_f(gv.y)));
    *reinterpret_cast<uint2*>(out + i) = o;
}

__device__ __forceinline__ void mma16816(float* c, const uint32_t* a, uint32_t b0, uint32_t b1) {
    asm volatile(
        "mma.sync.aligned.m16n8k16.row.col.f32.bf16.bf16.f32 {%0,%1,%2,%3}, {%4,%5,%6,%7}, {%8,%9}, {%0,%1,%2,%3};"
        : "+f"(c[0]), "+f"(c[1]), "+f"(c[2]), "+f"(c[3])
        : "r"(a[0]), "r"(a[1]), "r"(a[2]), "r"(a[3]), "r"(b0), "r"(b1));
}
__device__ __forceinline__ void ldsm_x4(uint32_t* r, uint32_t addr) {
    asm volatile("ldmatrix.sync.aligned.m8n8.x4.shared.b16 {%0,%1,%2,%3}, [%4];"
                 : "=r"(r[0]), "=r"(r[1]), "=r"(r[2]), "=r"(r[3]) : "r"(addr));
}
__device__ __forceinline__ void ldsm_x4_t(uint32_t* r, uint32_t addr) {
    asm volatile("ldmatrix.sync.aligned.m8n8.x4.trans.shared.b16 {%0,%1,%2,%3}, [%4];"
                 : "=r"(r[0]), "=r"(r[1]), "=r"(r[2]), "=r"(r[3]) : "r"(addr));
}
__device__ __forceinline__ uint4 ld_relaxed_v4(const void* p) {
    uint4 v;
    asm volatile("ld.relaxed.gpu.global.v4.u32 {%0,%1,%2,%3}, [%4];" : "=r"(v.x), "=r"(v.y), "=r"(v.z), "=r"(v.w) : "l"(p) : "memory");
    return v;
}
__device__ __forceinline__ void st_relaxed_v4(void* p, uint32_t a, uint32_t b, uint32_t c, uint32_t d) {
    asm volatile("st.relaxed.gpu.global.v4.u32 [%0], {%1,%2,%3,%4};" ::"l"(p), "r"(a), "r"(b), "r"(c), "r"(d) : "memory");
}
__device__ __forceinline__ void st_relaxed_v2(void* p, uint32_t a, uint32_t b) {
    asm volatile("st.relaxed.gpu.global.v2.u32 [%0], {%1,%2};" ::"l"(p), "r"(a), "r"(b) : "memory");
}
__device__ __forceinline__ void cp_async16(uint32_t dst, const void* src) {
    asm volatile("cp.async.cg.shared.global [%0], [%1], 16;" ::"r"(dst), "l"(src) : "memory");
}
__device__ __forceinline__ void cp_async_commit() { asm volatile("cp.async.commit_group;" ::: "memory"); }
template <int N> __device__ __forceinline__ void cp_async_wait() { asm volatile("cp.async.wait_group %0;" ::"n"(N) : "memory"); }

#define PROF(i) do {} while (0)
constexpr int SPIN_LIMIT = 4000000;

__device__ __forceinline__ uint4 poll_ll(const void* p, uint32_t flag) {
    uint4 v = ld_relaxed_v4(p);
    int n = 0;
    while ((v.y != flag || v.w != flag) && ++n < SPIN_LIMIT) {
        v = ld_relaxed_v4(p);
    }
    return v;
}

constexpr int RT = 512;
constexpr bool FUSE_X = false;
constexpr int MEMS_LD = D_ + 8;
constexpr int HL = DH_ + 8;
struct RecurSmem {
    bf16 mem[MEM_][MEMS_LD];
    bf16 kall[2][48][HL];
    bf16 vall[2][48][HL];
    bf16 qm[16][HL];
    float sc[MEM_][40];
    bf16 p[MEM_][48 + 8];
    bf16 om[MEM_][HL];
    float red[12][16 * 8];
    float wred[2][5][16 * 8];
    bf16 xs[2][SEG_][MEMS_LD];
    float redx[6][4][16 * 8];
    bf16 xo[SEG_][96 + 8];
};

__device__ __forceinline__ void bar_sync(int id, int n) { asm volatile("bar.sync %0, %1;" ::"r"(id), "r"(n) : "memory"); }
__device__ __forceinline__ void bar_arrive(int id, int n) { asm volatile("bar.arrive %0, %1;" ::"r"(id), "r"(n) : "memory"); }
__device__ __forceinline__ void sts64(uint32_t a, uint32_t x, uint32_t y) { asm volatile("st.shared.v2.u32 [%0], {%1,%2};" ::"r"(a), "r"(x), "r"(y) : "memory"); }
__device__ __forceinline__ uint32_t ldg_u16x2(const bf16* p0, const bf16* p1) {
    return (uint32_t)*(const uint16_t*)p0 | ((uint32_t)*(const uint16_t*)p1 << 16);
}
enum { BAR_MEM = 1, BAR_RED = 2, BAR_CTL = 3, BAR_WO = 4, BAR_INIT = 6, BAR_X = 7, BAR_GO = 8 };

__global__ void __launch_bounds__(RT, 1)
recur_kernel(const bf16* __restrict__ mem0, const bf16* __restrict__ Wq, const bf16* __restrict__ Wk,
             const bf16* __restrict__ Wv, const bf16* __restrict__ Wo) {
    extern __shared__ __align__(16) uint8_t smem_raw[];
    RecurSmem& sm = *reinterpret_cast<RecurSmem*>(smem_raw);
    const int tid = threadIdx.x, lane = tid & 31, w = tid >> 5;
    const int g = lane >> 2, t = lane & 3;
    const int h = blockIdx.x >> 2, c = blockIdx.x & 3;

    if (w < 12) {
        asm volatile("setmaxnreg.dec.sync.aligned.u32 104;");
        uint32_t wf[20][4];
        const int mt = w % 6, kh = w / 6;
        {
            const bf16* W = (mt < 2) ? Wq : (mt < 4 ? Wk : Wv);
            int f0 = h * DH_ + c * 32 + (mt & 1) * 16;
            uint32_t stg = smem_u32(smem_raw) + w * 10240;
#pragma unroll 4
            for (int i = lane; i < 640; i += 32)
                cp_async16(stg + i * 16, W + (size_t)(kh * 320 + (i >> 1)) * HD_ + f0 + (i & 1) * 8);
            cp_async_commit(); cp_async_wait<0>(); __syncwarp();
            uint32_t la = stg + ((lane & 7) + ((lane >> 4) & 1) * 8) * 32 + ((lane >> 3) & 1) * 16;
#pragma unroll
            for (int i = 0; i < 20; i++) ldsm_x4_t(wf[i], la + i * 512);
        }
        bar_sync(BAR_INIT, RT);
        const uint32_t base = smem_u32(&sm.mem[lane & 7][kh * 320 + (lane >> 3) * 8]);
        const uint32_t rp = smem_u32(&sm.red[w][g * 8 + 2 * t]);
        const uint32_t xbase0 = smem_u32(&sm.xs[0][lane & 7][kh * 320 + (lane >> 3) * 8]);
        uint32_t xbase = xbase0;
        const uint32_t rxp = smem_u32(&sm.redx[mt][0][lane * 4]);
        auto load_x = [&](int seg) {
            for (int i = tid; i < SEG_ * (D_ / 8); i += 384) {
                int r = i / (D_ / 8), ch = i % (D_ / 8);
                cp_async16(smem_u32(&sm.xs[seg & 1][r][ch * 8]), g_xn + (size_t)(seg * SEG_ + r) * D_ + ch * 8);
            }
            cp_async_commit();
        };
        float acc[4][4];
        auto xhalf = [&](int n0) {
#pragma unroll
            for (int nt = 0; nt < 2; nt++) { acc[n0 + nt][0] = acc[n0 + nt][1] = acc[n0 + nt][2] = acc[n0 + nt][3] = 0.f; }
#pragma unroll
            for (int i = 0; i < 10; i++) {
#pragma unroll
                for (int nt = 0; nt < 2; nt++) {
                    uint32_t b[4];
                    ldsm_x4(b, xbase + (n0 + nt) * (8 * MEMS_LD * 2) + i * 64);
                    mma16816(acc[n0 + nt], wf[2 * i], b[0], b[1]);
                    mma16816(acc[n0 + nt], wf[2 * i + 1], b[2], b[3]);
                }
            }
        };
        auto xworkA = [&](int seg) {
            cp_async_wait<0>();
            bar_sync(BAR_X, 384);
            if (seg + 1 < NSEG_) load_x(seg + 1);
            xbase = xbase0 + (seg & 1) * (SEG_ * MEMS_LD * 2);
            xhalf(0);
        };
        auto xwork = [&](int seg) {
            xhalf(2);
            if (kh == 1) {
#pragma unroll
                for (int nt = 0; nt < 4; nt++)
                    asm volatile("st.shared.v4.f32 [%0], {%1,%2,%3,%4};" ::"r"(rxp + nt * 512), "f"(acc[nt][0]), "f"(acc[nt][1]), "f"(acc[nt][2]), "f"(acc[nt][3]) : "memory");
            }
            bar_sync(BAR_X, 384);
            if (kh == 0) {
#pragma unroll
                for (int nt = 0; nt < 4; nt++) {
                    float4 o;
                    asm volatile("ld.shared.v4.f32 {%0,%1,%2,%3}, [%4];" : "=f"(o.x), "=f"(o.y), "=f"(o.z), "=f"(o.w) : "r"(rxp + nt * 512) : "memory");
                    bf16* d = &sm.xo[nt * 8 + 2 * t][mt * 16 + g];
                    d[0] = __float2bfloat16_rn(acc[nt][0] + o.x);
                    d[104] = __float2bfloat16_rn(acc[nt][1] + o.y);
                    d[8] = __float2bfloat16_rn(acc[nt][2] + o.z);
                    d[104 + 8] = __float2bfloat16_rn(acc[nt][3] + o.w);
                }
            }
            bar_sync(BAR_X, 384);
            {
                int r = tid / 12, ch = tid % 12;
                uint4 v = *reinterpret_cast<const uint4*>(&sm.xo[r][ch * 8]);
                *reinterpret_cast<uint4*>(g_qkv + (size_t)(seg * SEG_ + r) * (3 * HD_) + (ch >> 2) * HD_ + h * DH_ + c * 32 + (ch & 3) * 8) = v;
            }
        };
        auto xsignal = [&](int seg) {
            __threadfence();
            __syncwarp();
            if (lane == 0) atomicAdd(&g_xcnt[h * NSEG_ + seg], 1u);
        };
        if (FUSE_X) {
            load_x(0);
            xworkA(0); xwork(0); xsignal(0);
            xworkA(1); xwork(1); xsignal(1);
        }
        for (int s = 0; s < NSEG_; s++) {
            bar_sync(BAR_MEM, RT);
            float a0[4] = {0.f, 0.f, 0.f, 0.f}, a1[4] = {0.f, 0.f, 0.f, 0.f};
#pragma unroll
            for (int i = 0; i < 10; i++) {
                uint32_t b[4];
                ldsm_x4(b, base + i * 64);
                mma16816(a0, wf[2 * i], b[0], b[1]);
                mma16816(a1, wf[2 * i + 1], b[2], b[3]);
            }
            sts64(rp, __float_as_uint(a0[0] + a1[0]), __float_as_uint(a0[1] + a1[1]));
            sts64(rp + 256, __float_as_uint(a0[2] + a1[2]), __float_as_uint(a0[3] + a1[3]));
            bar_arrive(BAR_RED, RT);
            if (FUSE_X) {
                if (s + 2 < NSEG_) xworkA(s + 2);
                if (s >= 1 && s + 1 < NSEG_) xsignal(s + 1);
                if (s + 1 < NSEG_) bar_sync(BAR_GO, RT);
                if (s + 2 < NSEG_) xwork(s + 2);
            }
        }
    } else {
        asm volatile("setmaxnreg.inc.sync.aligned.u32 200;");
        const int ct = tid - 384, cw = w - 12;
        const int mg = cw >> 1, kh = cw & 1;
        uint32_t wf[20][4];
        {
            uint32_t stg = smem_u32(smem_raw) + 12 * 10240 + cw * 10240;
#pragma unroll 4
            for (int i = lane; i < 640; i += 32) {
                int r = i / 10, ch = i % 10;
                cp_async16(stg + r * 160 + ch * 16, Wo + (size_t)(h * DH_ + kh * 64 + r) * D_ + c * 160 + mg * 80 + ch * 8);
            }
            cp_async_commit(); cp_async_wait<0>(); __syncwarp();
            uint32_t la = stg + ((lane & 7) + ((lane >> 4) & 1) * 8) * 160 + ((lane >> 3) & 1) * 16;
#pragma unroll
            for (int mi = 0; mi < 5; mi++)
#pragma unroll
                for (int ki = 0; ki < 4; ki++) ldsm_x4_t(wf[mi * 4 + ki], la + ki * 16 * 160 + mi * 32);
        }
        bar_sync(BAR_INIT, RT);
        for (int i = ct; i < 2 * 8 * HL; i += 128) {
            int b = i / (8 * HL), r = (i / HL) % 8, cc = i % HL;
            sm.kall[b][40 + r][cc] = __float2bfloat16(0.f);
            sm.vall[b][40 + r][cc] = __float2bfloat16(0.f);
        }
        for (int i = ct; i < 8 * HL; i += 128) sm.qm[8 + i / HL][i % HL] = __float2bfloat16(0.f);
        for (int i = ct; i < 8 * 56; i += 128) sm.p[i / 56][i % 56] = __float2bfloat16(0.f);
        bar_sync(BAR_CTL, 128);
        constexpr uint32_t KV_BUF = 48 * HL * 2;
        const bf16* kv_src = g_qkv + (size_t)(ct >> 4) * (3 * HD_) + HD_ + h * DH_ + (ct & 15) * 8;
        const uint32_t kv_dst0 = smem_u32(&sm.kall[0][MEM_ + (ct >> 4)][(ct & 15) * 8]);
        const uint32_t kv_dst1 = smem_u32(&sm.vall[0][MEM_ + (ct >> 4)][(ct & 15) * 8]);
        auto prefetch_kv = [&](int s, int buf) {
            if (FUSE_X) {
                if (ct == 0) {
                    const unsigned* cp = g_xcnt + h * NSEG_ + s;
                    unsigned v; int n = 0;
                    do { asm volatile("ld.acquire.gpu.global.u32 %0, [%1];" : "=r"(v) : "l"(cp) : "memory"); } while (v < 48u && ++n < SPIN_LIMIT);
                }
                bar_sync(BAR_CTL, 128);
            }
            const bf16* src = kv_src + (size_t)s * SEG_ * (3 * HD_);
#pragma unroll
            for (int j = 0; j < 4; j++) {
                cp_async16(kv_dst0 + buf * KV_BUF + j * (8 * HL * 2), src + (size_t)j * 8 * (3 * HD_));
                cp_async16(kv_dst1 + buf * KV_BUF + j * (8 * HL * 2), src + (size_t)j * 8 * (3 * HD_) + HD_);
            }
            cp_async_commit();
        };
        const float4* acc_src = reinterpret_cast<const float4*>(g_acc) + ct;
        const uint32_t acc_dst = smem_u32(&sm.mem[(ct & 1) * 4][ct >> 1]);
        const uint4* hx_base = reinterpret_cast<const uint4*>(g_hx) + h * 1024;
        const int hx_rq = ct & 63, hx_half = ct >> 6;
        const uint4* hx_src = hx_base + hx_half * 64 + hx_rq;
        const uint32_t hx_col = (hx_rq & 7) * 8, hx_r = hx_rq >> 3;
        const uint32_t hx_dstA = (hx_half == 0 ? smem_u32(&sm.qm[hx_r][0]) : smem_u32(&sm.kall[0][hx_r][0])) + hx_col;
        const uint32_t hx_dstB = smem_u32(&sm.vall[0][hx_r][0]) + hx_col;
        const uint4* hx_probe = hx_base + (lane >> 3) * 256 + ((lane & 7) % 3) * 64 + (lane & 7) * 8 + 3;
        const int pb_r = ct >> 4, pb_pr = ct & 15;
        uint2* pb_dst = g_hx + (h * 1024 + c * 256 + pb_r * 8) * 2 + pb_pr;
        const float* pb_src = &sm.red[pb_pr >> 3][(pb_pr & 7) * 16 + pb_r];
        bf16* pb_k = g_kmem + (size_t)pb_r * HD_ + h * DH_ + c * 32 + pb_pr * 2;
        bf16* pb_v = g_vmem + (size_t)pb_r * HD_ + h * DH_ + c * 32 + pb_pr * 2;
        const uint32_t qb = smem_u32(&sm.qm[lane & 7][(lane >> 3) * 8]);
        const uint32_t ka0 = smem_u32(&sm.kall[0][lane & 15][(lane >> 4) * 8]);
        const uint32_t va0 = smem_u32(&sm.vall[0][(lane & 7) + ((lane >> 4) & 1) * 8][cw * 32 + ((lane >> 3) & 1) * 8]);
        const uint32_t ob = smem_u32(&sm.om[lane & 7][kh * 64 + (lane >> 3) * 8]);
        float* acc_dst_g = g_acc + (c * 160 + mg * 80 + g) * 8 + 2 * t;

        prefetch_kv(0, 0);
        for (int s = 0; s < NSEG_; s++) {
            const int buf = s & 1;
            const uint32_t flag = s + 1;
            const uint32_t bo = buf * KV_BUF;
            PROF(0);
            if (s == 0) {
                for (int i = ct; i < MEM_ * D_ / 8; i += 128) {
                    int r = i / (D_ / 8), cc = (i % (D_ / 8)) * 8;
                    *reinterpret_cast<uint4*>(&sm.mem[r][cc]) = *reinterpret_cast<const uint4*>(mem0 + r * D_ + cc);
                }
            } else {
                {
                    const unsigned* cp = g_cnt + (s - 1) * 32;
                    unsigned v; int n = 0;
                    do { asm volatile("ld.acquire.gpu.global.u32 %0, [%1];" : "=r"(v) : "l"(cp) : "memory"); } while (v < 512u && ++n < SPIN_LIMIT);
                }
                PROF(1);
                const float4* src = acc_src + (size_t)(s - 1) * (MEM_ * D_ / 4);
                float4 v[10];
#pragma unroll
                for (int j = 0; j < 10; j++)
                    asm volatile("ld.relaxed.gpu.global.v4.f32 {%0,%1,%2,%3}, [%4];" : "=f"(v[j].x), "=f"(v[j].y), "=f"(v[j].z), "=f"(v[j].w) : "l"(src + 128 * j) : "memory");
#pragma unroll
                for (int j = 0; j < 10; j++) {
                    uint32_t lo = pack_bf16(v[j].x, v[j].y), hi = pack_bf16(v[j].z, v[j].w);
                    uint32_t d = acc_dst + j * 128;
                    asm volatile("st.shared.u16 [%0], %1;" ::"r"(d), "h"((uint16_t)(lo & 0xffff)) : "memory");
                    asm volatile("st.shared.u16 [%0], %1;" ::"r"(d + MEMS_LD * 2), "h"((uint16_t)(lo >> 16)) : "memory");
                    asm volatile("st.shared.u16 [%0], %1;" ::"r"(d + MEMS_LD * 4), "h"((uint16_t)(hi & 0xffff)) : "memory");
                    asm volatile("st.shared.u16 [%0], %1;" ::"r"(d + MEMS_LD * 6), "h"((uint16_t)(hi >> 16)) : "memory");
                }
            }
            bar_arrive(BAR_MEM, RT);
            PROF(2);
            bar_sync(BAR_RED, RT);
            PROF(3);
            {
                uint32_t pk0 = pack_bf16(pb_src[0] + pb_src[768], pb_src[8] + pb_src[768 + 8]);
                uint32_t pk1 = pack_bf16(pb_src[256] + pb_src[1024], pb_src[256 + 8] + pb_src[1024 + 8]);
                uint32_t pk2 = pack_bf16(pb_src[512] + pb_src[1280], pb_src[512 + 8] + pb_src[1280 + 8]);
                st_relaxed_v2(pb_dst, pk0, flag);
                st_relaxed_v2(pb_dst + 128, pk1, flag);
                st_relaxed_v2(pb_dst + 256, pk2, flag);
                *reinterpret_cast<uint32_t*>(pb_k + (size_t)s * (MEM_ * HD_)) = pk1;
                *reinterpret_cast<uint32_t*>(pb_v + (size_t)s * (MEM_ * HD_)) = pk2;
            }
            if (s == NSEG_ - 1) break;
            PROF(4);
            PROF(5);
            {
                uint4 v[8];
#pragma unroll
                for (int j = 0; j < 4; j++) v[j] = ld_relaxed_v4(hx_src + j * 256);
                if (hx_half == 0) {
#pragma unroll
                    for (int j = 0; j < 4; j++) v[4 + j] = ld_relaxed_v4(hx_src + j * 256 + 128);
                }
#pragma unroll
                for (int j = 0; j < 4; j++) {
                    if (v[j].y != flag || v[j].w != flag) v[j] = poll_ll(hx_src + j * 256, flag);
                    sts64(hx_dstA + j * 64 + (hx_half ? bo : 0), v[j].x, v[j].z);
                }
                if (hx_half == 0) {
#pragma unroll
                    for (int j = 0; j < 4; j++) {
                        if (v[4 + j].y != flag || v[4 + j].w != flag) v[4 + j] = poll_ll(hx_src + j * 256 + 128, flag);
                        sts64(hx_dstB + j * 64 + bo, v[4 + j].x, v[4 + j].z);
                    }
                }
            }
            cp_async_wait<0>();
            bar_sync(BAR_CTL, 128);
            PROF(6);
            {
                uint32_t bq[4][4];
#pragma unroll
                for (int kk = 0; kk < 4; kk++) ldsm_x4(bq[kk], qb + kk * 64);
                float sc[3][4];
#pragma unroll
                for (int m = 0; m < 3; m++) {
                    uint32_t a[8][4];
#pragma unroll
                    for (int kk = 0; kk < 8; kk++) ldsm_x4(a[kk], ka0 + bo + m * (16 * HL * 2) + kk * 32);
                    float s0[4] = {0.f, 0.f, 0.f, 0.f}, s1[4] = {0.f, 0.f, 0.f, 0.f};
#pragma unroll
                    for (int kk = 0; kk < 4; kk++) { mma16816(s0, a[2 * kk], bq[kk][0], bq[kk][1]); mma16816(s1, a[2 * kk + 1], bq[kk][2], bq[kk][3]); }
#pragma unroll
                    for (int e = 0; e < 4; e++) sc[m][e] = rbf(rbf(s0[e] + s1[e]) * 0.08838834764831845f);
                }
                uint32_t av[2][3][4];
#pragma unroll
                for (int kt = 0; kt < 3; kt++) { ldsm_x4_t(av[0][kt], va0 + bo + kt * 16 * HL * 2); ldsm_x4_t(av[1][kt], va0 + bo + kt * 16 * HL * 2 + 32); }
                float mx0 = fmaxf(fmaxf(fmaxf(sc[0][0], sc[0][2]), fmaxf(sc[1][0], sc[1][2])), sc[2][0]);
                float mx1 = fmaxf(fmaxf(fmaxf(sc[0][1], sc[0][3]), fmaxf(sc[1][1], sc[1][3])), sc[2][1]);
#pragma unroll
                for (int o = 4; o < 32; o <<= 1) { mx0 = fmaxf(mx0, __shfl_xor_sync(0xffffffffu, mx0, o)); mx1 = fmaxf(mx1, __shfl_xor_sync(0xffffffffu, mx1, o)); }
                float sum0 = 0.f, sum1 = 0.f;
#pragma unroll
                for (int m = 0; m < 3; m++) {
#pragma unroll
                    for (int e = 0; e < 4; e++) {
                        if (m == 2 && e >= 2) { sc[m][e] = 0.f; continue; }
                        float ev = __expf(sc[m][e] - ((e & 1) ? mx1 : mx0));
                        sc[m][e] = ev;
                        if (e & 1) sum1 += ev; else sum0 += ev;
                    }
                }
#pragma unroll
                for (int o = 4; o < 32; o <<= 1) { sum0 += __shfl_xor_sync(0xffffffffu, sum0, o); sum1 += __shfl_xor_sync(0xffffffffu, sum1, o); }
                float i0 = 1.0f / sum0, i1 = 1.0f / sum1;
                uint32_t pb[3][2];
#pragma unroll
                for (int m = 0; m < 3; m++) {
#pragma unroll
                    for (int hh = 0; hh < 2; hh++) {
                        uint32_t pk = pack_bf16(sc[m][2 * hh] * i0, sc[m][2 * hh + 1] * i1);
                        asm volatile("movmatrix.sync.aligned.m8n8.trans.b16 %0, %1;" : "=r"(pb[m][hh]) : "r"(pk));
                    }
                }
                PROF(7);
#pragma unroll
                for (int m = 0; m < 2; m++) {
                    float o[4] = {0.f, 0.f, 0.f, 0.f};
#pragma unroll
                    for (int kt = 0; kt < 3; kt++) mma16816(o, av[m][kt], pb[kt][0], pb[kt][1]);
                    int d0 = cw * 32 + m * 16 + g;
                    sm.om[2 * t][d0] = __float2bfloat16_rn(o[0]);
                    sm.om[2 * t + 1][d0] = __float2bfloat16_rn(o[1]);
                    sm.om[2 * t][d0 + 8] = __float2bfloat16_rn(o[2]);
                    sm.om[2 * t + 1][d0 + 8] = __float2bfloat16_rn(o[3]);
                }
            }
            bar_sync(BAR_CTL, 128);
            PROF(8);
            {
                float acc[5][4];
#pragma unroll
                for (int mi = 0; mi < 5; mi++) { acc[mi][0] = acc[mi][1] = acc[mi][2] = acc[mi][3] = 0.f; }
                uint32_t b[2][4];
                ldsm_x4(b[0], ob); ldsm_x4(b[1], ob + 64);
#pragma unroll
                for (int ki = 0; ki < 4; ki++)
#pragma unroll
                    for (int mi = 0; mi < 5; mi++) mma16816(acc[mi], wf[mi * 4 + ki], b[ki >> 1][(ki & 1) * 2], b[ki >> 1][(ki & 1) * 2 + 1]);
                {
                    float* dst = acc_dst_g + (size_t)s * (MEM_ * D_);
#pragma unroll
                    for (int mi = 0; mi < 5; mi++) {
                        asm volatile("red.global.add.v2.f32 [%0], {%1,%2};" ::"l"(dst + mi * 128), "f"(acc[mi][0]), "f"(acc[mi][1]) : "memory");
                        asm volatile("red.global.add.v2.f32 [%0], {%1,%2};" ::"l"(dst + mi * 128 + 64), "f"(acc[mi][2]), "f"(acc[mi][3]) : "memory");
                    }
                    __threadfence();
                    __syncwarp();
                    if (lane == 0) atomicAdd(&g_cnt[s * 32], 1u);
                }
            }
            if (FUSE_X) bar_arrive(BAR_GO, RT);
            PROF(9);
            prefetch_kv(s + 1, buf ^ 1);
            PROF(10);
        }
    }
}

__global__ void __launch_bounds__(128)
attn_x_kernel() {
    __shared__ __align__(16) bf16 sq[32][HL], sk[48][HL], sv[48][HL];
    const int s = blockIdx.x >> 5, h = blockIdx.x & 31;
    const int tid = threadIdx.x, lane = tid & 31, w = tid >> 5, g = lane >> 2, t = lane & 3;
    for (int i = tid; i < (32 + 40 + 40) * 16; i += 128) {
        int r = i >> 4, ch = i & 15;
        const bf16* src; bf16* dst;
        if (r < 32) { src = g_qkv + (size_t)(s * SEG_ + r) * (3 * HD_) + h * DH_; dst = sq[r]; }
        else if (r < 72) { int rr = r - 32; dst = sk[rr];
            src = rr < 8 ? g_kmem + ((size_t)s * MEM_ + rr) * HD_ + h * DH_ : g_qkv + (size_t)(s * SEG_ + rr - 8) * (3 * HD_) + HD_ + h * DH_; }
        else { int rr = r - 72; dst = sv[rr];
            src = rr < 8 ? g_vmem + ((size_t)s * MEM_ + rr) * HD_ + h * DH_ : g_qkv + (size_t)(s * SEG_ + rr - 8) * (3 * HD_) + 2 * HD_ + h * DH_; }
        cp_async16(smem_u32(dst + ch * 8), src + ch * 8);
    }
    cp_async_commit();
    for (int i = tid; i < 8 * 16; i += 128) *reinterpret_cast<uint4*>(&sv[40 + (i >> 4)][(i & 15) * 8]) = make_uint4(0, 0, 0, 0);
    cp_async_wait<0>();
    __syncthreads();
    const int rh = w & 1, dhh = w >> 1;
    float sc[5][4];
#pragma unroll
    for (int n = 0; n < 5; n++) sc[n][0] = sc[n][1] = sc[n][2] = sc[n][3] = 0.f;
#pragma unroll
    for (int kk = 0; kk < 8; kk++) {
        uint32_t a[4];
        ldsm_x4(a, smem_u32(&sq[rh * 16 + (lane & 15)][kk * 16 + (lane >> 4) * 8]));
#pragma unroll
        for (int n = 0; n < 5; n++) {
            uint32_t b[2];
            asm volatile("ldmatrix.sync.aligned.m8n8.x2.shared.b16 {%0,%1}, [%2];" : "=r"(b[0]), "=r"(b[1])
                         : "r"(smem_u32(&sk[n * 8 + (lane & 7)][kk * 16 + ((lane >> 3) & 1) * 8])));
            mma16816(sc[n], a, b[0], b[1]);
        }
    }
    const float scale = 0.08838834764831845f;
    float mx[2] = {-INFINITY, -INFINITY};
#pragma unroll
    for (int n = 0; n < 5; n++)
#pragma unroll
        for (int e = 0; e < 4; e++) {
            int row = rh * 16 + g + (e >> 1) * 8, key = n * 8 + 2 * t + (e & 1);
            float v = rbf(rbf(sc[n][e]) * scale);
            if (key > row + MEM_) v = -INFINITY;
            sc[n][e] = v;
            mx[e >> 1] = fmaxf(mx[e >> 1], v);
        }
#pragma unroll
    for (int o = 1; o < 4; o <<= 1) { mx[0] = fmaxf(mx[0], __shfl_xor_sync(0xffffffffu, mx[0], o)); mx[1] = fmaxf(mx[1], __shfl_xor_sync(0xffffffffu, mx[1], o)); }
    float sum[2] = {0.f, 0.f};
#pragma unroll
    for (int n = 0; n < 5; n++)
#pragma unroll
        for (int e = 0; e < 4; e++) { float ev = __expf(sc[n][e] - mx[e >> 1]); sc[n][e] = ev; sum[e >> 1] += ev; }
#pragma unroll
    for (int o = 1; o < 4; o <<= 1) { sum[0] += __shfl_xor_sync(0xffffffffu, sum[0], o); sum[1] += __shfl_xor_sync(0xffffffffu, sum[1], o); }
    float inv[2] = {1.0f / sum[0], 1.0f / sum[1]};
    uint32_t pa[3][4];
#pragma unroll
    for (int kt = 0; kt < 3; kt++) {
        pa[kt][0] = pack_bf16(sc[2 * kt][0] * inv[0], sc[2 * kt][1] * inv[0]);
        pa[kt][1] = pack_bf16(sc[2 * kt][2] * inv[1], sc[2 * kt][3] * inv[1]);
        if (kt < 2) {
            pa[kt][2] = pack_bf16(sc[2 * kt + 1][0] * inv[0], sc[2 * kt + 1][1] * inv[0]);
            pa[kt][3] = pack_bf16(sc[2 * kt + 1][2] * inv[1], sc[2 * kt + 1][3] * inv[1]);
        } else { pa[kt][2] = 0u; pa[kt][3] = 0u; }
    }
#pragma unroll
    for (int n = 0; n < 8; n++) {
        float o[4] = {0.f, 0.f, 0.f, 0.f};
#pragma unroll
        for (int kt = 0; kt < 3; kt++) {
            uint32_t b[2];
            asm volatile("ldmatrix.sync.aligned.m8n8.x2.trans.shared.b16 {%0,%1}, [%2];" : "=r"(b[0]), "=r"(b[1])
                         : "r"(smem_u32(&sv[kt * 16 + (lane & 15)][dhh * 64 + n * 8])));
            mma16816(o, pa[kt], b[0], b[1]);
        }
        int row = s * SEG_ + rh * 16 + g;
        bf16* dst = g_o + (size_t)row * HD_ + h * DH_ + dhh * 64 + n * 8 + 2 * t;
        *reinterpret_cast<uint32_t*>(dst) = pack_bf16(o[0], o[1]);
        *reinterpret_cast<uint32_t*>(dst + 8 * HD_) = pack_bf16(o[2], o[3]);
    }
}

typedef CUresult (*PFN_encodeTiled)(CUtensorMap*, CUtensorMapDataType, cuuint32_t, void*, const cuuint64_t*,
                                    const cuuint64_t*, const cuuint32_t*, const cuuint32_t*, CUtensorMapInterleave,
                                    CUtensorMapSwizzle, CUtensorMapL2promotion, CUtensorMapFloatOOBfill);
static PFN_encodeTiled p_encode = nullptr;

static CUtensorMap make_map(const void* ptr, uint64_t rows, uint64_t cols, uint64_t ld, uint32_t box_rows) {
    CUtensorMap m;
    cuuint64_t dims[2] = {cols, rows};
    cuuint64_t strides[1] = {ld * 2};
    cuuint32_t box[2] = {64, box_rows};
    cuuint32_t es[2] = {1, 1};
    p_encode(&m, CU_TENSOR_MAP_DATA_TYPE_BFLOAT16, 2, const_cast<void*>(ptr), dims, strides, box, es,
             CU_TENSOR_MAP_INTERLEAVE_NONE, CU_TENSOR_MAP_SWIZZLE_128B, CU_TENSOR_MAP_L2_PROMOTION_L2_128B,
             CU_TENSOR_MAP_FLOAT_OOB_FILL_NONE);
    return m;
}

template <int BN, int EPI>
static void launch_gemm(const CUtensorMap& a, const CUtensorMap& b0, const CUtensorMap& b1, const CUtensorMap& b2,
                        int nPerB, int M, int N, int K, EpiParams ep, cudaStream_t st, int splitk = 1) {
    constexpr int STAGE = 16384 + (BN / 64) * 8192;
    constexpr int NST = (200 * 1024) / STAGE;
    constexpr int SMEM = NST * STAGE + 1024;
    cudaFuncSetAttribute(gemm_kernel<BN, EPI>, cudaFuncAttributeMaxDynamicSharedMemorySize, SMEM);
    dim3 grid((N + BN - 1) / BN, M / 128, splitk);
    gemm_kernel<BN, EPI><<<grid, 384, SMEM, st>>>(a, b0, b1, b2, nPerB, N, K, ep);
}

extern "C" void kernel_launch(void* const* d_in, const int* in_sizes, int n_in, void* d_out, int out_size) {
    const bf16* x    = (const bf16*)d_in[0];
    const bf16* mem0 = (const bf16*)d_in[1];
    const bf16* Wq   = (const bf16*)d_in[2];
    const bf16* Wk   = (const bf16*)d_in[3];
    const bf16* Wv   = (const bf16*)d_in[4];
    const bf16* Wo   = (const bf16*)d_in[5];
    const bf16* w_in  = (const bf16*)d_in[8];
    const bf16* w_sp  = (const bf16*)d_in[9];
    const bf16* b_sp  = (const bf16*)d_in[10];
    const bf16* w_out = (const bf16*)d_in[11];
    bf16* out = (bf16*)d_out;
    cudaStream_t st = cudaStreamPerThread;

    if (!p_encode) {
        cudaDriverEntryPointQueryResult qr;
        cudaGetDriverEntryPoint("cuTensorMapEncodeTiled", (void**)&p_encode, cudaEnableDefault, &qr);
    }
    void *p_xn, *p_qkv, *p_z, *p_zg, *p_gate, *p_o, *p_acc, *p_cnt, *p_hx;
    cudaGetSymbolAddress(&p_xn, g_xn); cudaGetSymbolAddress(&p_qkv, g_qkv); cudaGetSymbolAddress(&p_z, g_z);
    cudaGetSymbolAddress(&p_zg, g_zg); cudaGetSymbolAddress(&p_gate, g_gate); cudaGetSymbolAddress(&p_o, g_o);
    cudaGetSymbolAddress(&p_acc, g_acc); cudaGetSymbolAddress(&p_cnt, g_cnt); cudaGetSymbolAddress(&p_hx, g_hx);

    CUtensorMap mA_xn  = make_map(p_xn, S_, D_, D_, 128);
    CUtensorMap mA_wsp = make_map(w_sp, S_, S_, S_, 128);
    CUtensorMap mA_zg  = make_map(p_zg, S_, FH_, FH_, 128);
    CUtensorMap mA_o   = make_map(p_o, S_, HD_, HD_, 128);
    CUtensorMap mB_wq  = make_map(Wq, D_, HD_, HD_, 64);
    CUtensorMap mB_wk  = make_map(Wk, D_, HD_, HD_, 64);
    CUtensorMap mB_wv  = make_map(Wv, D_, HD_, HD_, 64);
    CUtensorMap mB_win = make_map(w_in, D_, F_, F_, 64);
    CUtensorMap mB_z2  = make_map((bf16*)p_z + FH_, S_, FH_, F_, 64);
    CUtensorMap mB_wout = make_map(w_out, FH_, D_, D_, 64);
    CUtensorMap mB_wo  = make_map(Wo, HD_, D_, D_, 64);

    cudaMemsetAsync(p_acc, 0, sizeof(float) * NSEG_ * MEM_ * D_, st);
    cudaMemsetAsync(p_cnt, 0, sizeof(unsigned) * NSEG_ * 32, st);
    void* p_xcnt; cudaGetSymbolAddress(&p_xcnt, g_xcnt);
    cudaMemsetAsync(p_xcnt, 0, sizeof(unsigned) * H_ * NSEG_, st);
    cudaMemsetAsync(p_hx, 0, sizeof(uint2) * H_ * 4 * 256 * 2, st);

    static cudaStream_t st2 = nullptr;
    static cudaEvent_t ev_fork = nullptr, ev_join = nullptr;
    if (!st2) {
        cudaStreamCreateWithFlags(&st2, cudaStreamNonBlocking);
        cudaEventCreateWithFlags(&ev_fork, cudaEventDisableTiming);
        cudaEventCreateWithFlags(&ev_join, cudaEventDisableTiming);
    }
    ln_kernel<<<S_ / 8, 256, 0, st>>>(x);
    cudaEventRecord(ev_fork, st);
    cudaStreamWaitEvent(st2, ev_fork, 0);
    { EpiParams ep{(bf16*)p_z, F_, nullptr, nullptr}; launch_gemm<128, EPI_GELU>(mA_xn, mB_win, mB_win, mB_win, 1 << 20, S_, F_, D_, ep, st2); }
    ln2_kernel<<<S_ / 8, 256, 0, st2>>>();
    { EpiParams ep{(bf16*)p_zg, FH_, (const bf16*)p_z, b_sp}; launch_gemm<128, EPI_SP>(mA_wsp, mB_z2, mB_z2, mB_z2, 1 << 20, S_, FH_, S_, ep, st2); }
    { EpiParams ep{(bf16*)p_gate, D_, nullptr, nullptr}; launch_gemm<128, EPI_SILU>(mA_zg, mB_wout, mB_wout, mB_wout, 1 << 20, S_, D_, FH_, ep, st2); }
    cudaEventRecord(ev_join, st2);
    if (!FUSE_X) { EpiParams ep{(bf16*)p_qkv, 3 * HD_, nullptr, nullptr}; launch_gemm<256, EPI_STORE>(mA_xn, mB_wq, mB_wk, mB_wv, HD_, S_, 3 * HD_, D_, ep, st); }
    constexpr int RSM = (int)sizeof(RecurSmem) > 16 * 10240 ? (int)sizeof(RecurSmem) : 16 * 10240;
    cudaFuncSetAttribute(recur_kernel, cudaFuncAttributeMaxDynamicSharedMemorySize, RSM);
    recur_kernel<<<128, RT, RSM, st>>>(mem0, Wq, Wk, Wv, Wo);
    attn_x_kernel<<<NSEG_ * H_, 128, 0, st>>>();
    cudaStreamWaitEvent(st, ev_join, 0);
    { EpiParams ep{out, D_, x, (const bf16*)p_gate}; launch_gemm<128, EPI_FINAL>(mA_o, mB_wo, mB_wo, mB_wo, 1 << 20, S_, D_, HD_, ep, st); }
}
```

```cpp
#include <cuda_runtime.h>
#include <cuda_bf16.h>
#include <cuda.h>
#include <stdint.h>
#define NO_PROBE_HX 1

typedef __nv_bfloat16 bf16;

constexpr int S_   = 2048;
constexpr int D_   = 640;
constexpr int H_   = 32;
constexpr int DH_  = 128;
constexpr int MEM_ = 8;
constexpr int SEG_ = 32;
constexpr int NSEG_ = S_ / SEG_;
constexpr int HD_  = H_ * DH_;
constexpr int F_   = 1728;
constexpr int FH_  = 864;

__device__ bf16 g_xn[S_ * D_];
__device__ bf16 g_qkv[(size_t)S_ * 3 * HD_];
__device__ bf16 g_z[S_ * F_];
__device__ bf16 g_zg[S_ * FH_];
__device__ bf16 g_gate[S_ * D_];
__device__ bf16 g_kmem[NSEG_ * MEM_ * HD_];
__device__ bf16 g_vmem[NSEG_ * MEM_ * HD_];
__device__ bf16 g_o[(size_t)S_ * HD_];
__device__ float g_acc[NSEG_ * MEM_ * D_];
__device__ unsigned g_cnt[NSEG_ * 32];
__device__ unsigned g_xcnt[H_ * NSEG_];
__device__ uint2 g_hx[H_ * 4 * 256 * 2];

__device__ __forceinline__ uint32_t smem_u32(const void* p) { return (uint32_t)__cvta_generic_to_shared(p); }
__device__ __forceinline__ float bf2f(bf16 v) { return __bfloat162float(v); }
__device__ __forceinline__ float rbf(float v) { return __bfloat162float(__float2bfloat16_rn(v)); }
__device__ __forceinline__ uint32_t pack_bf16(float lo, float hi) {
    __nv_bfloat162 t = __floats2bfloat162_rn(lo, hi);
    return *reinterpret_cast<uint32_t*>(&t);
}
__device__ __forceinline__ float lo_f(uint32_t u) { return __uint_as_float(u << 16); }
__device__ __forceinline__ float hi_f(uint32_t u) { return __uint_as_float(u & 0xffff0000u); }

__device__ __forceinline__ void mbar_init(uint32_t bar, uint32_t cnt) {
    asm volatile("mbarrier.init.shared.b64 [%0], %1;" ::"r"(bar), "r"(cnt));
}
__device__ __forceinline__ void mbar_expect_tx(uint32_t bar, uint32_t bytes) {
    asm volatile("mbarrier.arrive.expect_tx.shared.b64 _, [%0], %1;" ::"r"(bar), "r"(bytes) : "memory");
}
__device__ __forceinline__ void mbar_arrive(uint32_t bar) {
    asm volatile("mbarrier.arrive.shared.b64 _, [%0];" ::"r"(bar) : "memory");
}
__device__ __forceinline__ void mbar_wait(uint32_t bar, uint32_t parity) {
    asm volatile(
        "{\n .reg .pred p;\n"
        "WAIT_%=:\n"
        " mbarrier.try_wait.parity.shared.b64 p, [%0], %1;\n"
        " @p bra DONE_%=;\n"
        " bra WAIT_%=;\n"
        "DONE_%=:\n}\n" ::"r"(bar), "r"(parity) : "memory");
}
__device__ __forceinline__ void tma_load_2d(uint32_t dst, const CUtensorMap* tm, uint32_t bar, int c0, int c1) {
    asm volatile(
        "cp.async.bulk.tensor.2d.shared::cluster.global.mbarrier::complete_tx::bytes [%0], [%1, {%3, %4}], [%2];"
        ::"r"(dst), "l"(tm), "r"(bar), "r"(c0), "r"(c1) : "memory");
}
__device__ __forceinline__ void wgmma_fence() { asm volatile("wgmma.fence.sync.aligned;" ::: "memory"); }
__device__ __forceinline__ void wgmma_commit() { asm volatile("wgmma.commit_group.sync.aligned;" ::: "memory"); }
template <int N> __device__ __forceinline__ void wgmma_wait() { asm volatile("wgmma.wait_group.sync.aligned %0;" ::"n"(N) : "memory"); }

__device__ __forceinline__ uint64_t make_desc(uint32_t addr, uint32_t lbo, uint32_t sbo) {
    return (uint64_t)((addr & 0x3FFFF) >> 4) | ((uint64_t)(lbo >> 4) << 16) | ((uint64_t)(sbo >> 4) << 32) | (1ull << 62);
}

template <int N> struct Wgmma;
template <> struct Wgmma<128> {
    static __device__ __forceinline__ void mma(float* d, uint64_t da, uint64_t db, int sd) {
        asm volatile(
            "{\n.reg .pred p;\nsetp.ne.b32 p, %66, 0;\n"
            "wgmma.mma_async.sync.aligned.m64n128k16.f32.bf16.bf16 "
            "{%0,%1,%2,%3,%4,%5,%6,%7,%8,%9,%10,%11,%12,%13,%14,%15,"
            "%16,%17,%18,%19,%20,%21,%22,%23,%24,%25,%26,%27,%28,%29,%30,%31,"
            "%32,%33,%34,%35,%36,%37,%38,%39,%40,%41,%42,%43,%44,%45,%46,%47,"
            "%48,%49,%50,%51,%52,%53,%54,%55,%56,%57,%58,%59,%60,%61,%62,%63},"
            "%64,%65,p,1,1,0,1;\n}\n"
            : "+f"(d[0]), "+f"(d[1]), "+f"(d[2]), "+f"(d[3]), "+f"(d[4]), "+f"(d[5]), "+f"(d[6]), "+f"(d[7]),
              "+f"(d[8]), "+f"(d[9]), "+f"(d[10]), "+f"(d[11]), "+f"(d[12]), "+f"(d[13]), "+f"(d[14]), "+f"(d[15]),
              "+f"(d[16]), "+f"(d[17]), "+f"(d[18]), "+f"(d[19]), "+f"(d[20]), "+f"(d[21]), "+f"(d[22]), "+f"(d[23]),
              "+f"(d[24]), "+f"(d[25]), "+f"(d[26]), "+f"(d[27]), "+f"(d[28]), "+f"(d[29]), "+f"(d[30]), "+f"(d[31]),
              "+f"(d[32]), "+f"(d[33]), "+f"(d[34]), "+f"(d[35]), "+f"(d[36]), "+f"(d[37]), "+f"(d[38]), "+f"(d[39]),
              "+f"(d[40]), "+f"(d[41]), "+f"(d[42]), "+f"(d[43]), "+f"(d[44]), "+f"(d[45]), "+f"(d[46]), "+f"(d[47]),
              "+f"(d[48]), "+f"(d[49]), "+f"(d[50]), "+f"(d[51]), "+f"(d[52]), "+f"(d[53]), "+f"(d[54]), "+f"(d[55]),
              "+f"(d[56]), "+f"(d[57]), "+f"(d[58]), "+f"(d[59]), "+f"(d[60]), "+f"(d[61]), "+f"(d[62]), "+f"(d[63])
            : "l"(da), "l"(db), "r"(sd));
    }
};
template <> struct Wgmma<192> {
    static __device__ __forceinline__ void mma(float* d, uint64_t da, uint64_t db, int sd) {
        asm volatile(
            "{\n.reg .pred p;\nsetp.ne.b32 p, %98, 0;\n"
            "wgmma.mma_async.sync.aligned.m64n192k16.f32.bf16.bf16 "
            "{%0,%1,%2,%3,%4,%5,%6,%7,%8,%9,%10,%11,%12,%13,%14,%15,"
            "%16,%17,%18,%19,%20,%21,%22,%23,%24,%25,%26,%27,%28,%29,%30,%31,"
            "%32,%33,%34,%35,%36,%37,%38,%39,%40,%41,%42,%43,%44,%45,%46,%47,"
            "%48,%49,%50,%51,%52,%53,%54,%55,%56,%57,%58,%59,%60,%61,%62,%63,"
            "%64,%65,%66,%67,%68,%69,%70,%71,%72,%73,%74,%75,%76,%77,%78,%79,"
            "%80,%81,%82,%83,%84,%85,%86,%87,%88,%89,%90,%91,%92,%93,%94,%95},"
            "%96,%97,p,1,1,0,1;\n}\n"
            : "+f"(d[0]), "+f"(d[1]), "+f"(d[2]), "+f"(d[3]), "+f"(d[4]), "+f"(d[5]), "+f"(d[6]), "+f"(d[7]),
              "+f"(d[8]), "+f"(d[9]), "+f"(d[10]), "+f"(d[11]), "+f"(d[12]), "+f"(d[13]), "+f"(d[14]), "+f"(d[15]),
              "+f"(d[16]), "+f"(d[17]), "+f"(d[18]), "+f"(d[19]), "+f"(d[20]), "+f"(d[21]), "+f"(d[22]), "+f"(d[23]),
              "+f"(d[24]), "+f"(d[25]), "+f"(d[26]), "+f"(d[27]), "+f"(d[28]), "+f"(d[29]), "+f"(d[30]), "+f"(d[31]),
              "+f"(d[32]), "+f"(d[33]), "+f"(d[34]), "+f"(d[35]), "+f"(d[36]), "+f"(d[37]), "+f"(d[38]), "+f"(d[39]),
              "+f"(d[40]), "+f"(d[41]), "+f"(d[42]), "+f"(d[43]), "+f"(d[44]), "+f"(d[45]), "+f"(d[46]), "+f"(d[47]),
              "+f"(d[48]), "+f"(d[49]), "+f"(d[50]), "+f"(d[51]), "+f"(d[52]), "+f"(d[53]), "+f"(d[54]), "+f"(d[55]),
              "+f"(d[56]), "+f"(d[57]), "+f"(d[58]), "+f"(d[59]), "+f"(d[60]), "+f"(d[61]), "+f"(d[62]), "+f"(d[63]),
              "+f"(d[64]), "+f"(d[65]), "+f"(d[66]), "+f"(d[67]), "+f"(d[68]), "+f"(d[69]), "+f"(d[70]), "+f"(d[71]),
              "+f"(d[72]), "+f"(d[73]), "+f"(d[74]), "+f"(d[75]), "+f"(d[76]), "+f"(d[77]), "+f"(d[78]), "+f"(d[79]),
              "+f"(d[80]), "+f"(d[81]), "+f"(d[82]), "+f"(d[83]), "+f"(d[84]), "+f"(d[85]), "+f"(d[86]), "+f"(d[87]),
              "+f"(d[88]), "+f"(d[89]), "+f"(d[90]), "+f"(d[91]), "+f"(d[92]), "+f"(d[93]), "+f"(d[94]), "+f"(d[95])
            : "l"(da), "l"(db), "r"(sd));
    }
};

template <> struct Wgmma<256> {
    static __device__ __forceinline__ void mma(float* d, uint64_t da, uint64_t db, int sd) {
        asm volatile(
            "{\n.reg .pred p;\nsetp.ne.b32 p, %130, 0;\n"
            "wgmma.mma_async.sync.aligned.m64n256k16.f32.bf16.bf16 "
            "{%0,%1,%2,%3,%4,%5,%6,%7,%8,%9,%10,%11,%12,%13,%14,%15,%16,%17,%18,%19,%20,%21,%22,%23,%24,%25,%26,%27,%28,%29,%30,%31,%32,%33,%34,%35,%36,%37,%38,%39,%40,%41,%42,%43,%44,%45,%46,%47,%48,%49,%50,%51,%52,%53,%54,%55,%56,%57,%58,%59,%60,%61,%62,%63,%64,%65,%66,%67,%68,%69,%70,%71,%72,%73,%74,%75,%76,%77,%78,%79,%80,%81,%82,%83,%84,%85,%86,%87,%88,%89,%90,%91,%92,%93,%94,%95,%96,%97,%98,%99,%100,%101,%102,%103,%104,%105,%106,%107,%108,%109,%110,%111,%112,%113,%114,%115,%116,%117,%118,%119,%120,%121,%122,%123,%124,%125,%126,%127},"
            "%128,%129,p,1,1,0,1;\n}\n"
            : "+f"(d[0]), "+f"(d[1]), "+f"(d[2]), "+f"(d[3]), "+f"(d[4]), "+f"(d[5]), "+f"(d[6]), "+f"(d[7]), "+f"(d[8]), "+f"(d[9]), "+f"(d[10]), "+f"(d[11]), "+f"(d[12]), "+f"(d[13]), "+f"(d[14]), "+f"(d[15]), "+f"(d[16]), "+f"(d[17]), "+f"(d[18]), "+f"(d[19]), "+f"(d[20]), "+f"(d[21]), "+f"(d[22]), "+f"(d[23]), "+f"(d[24]), "+f"(d[25]), "+f"(d[26]), "+f"(d[27]), "+f"(d[28]), "+f"(d[29]), "+f"(d[30]), "+f"(d[31]), "+f"(d[32]), "+f"(d[33]), "+f"(d[34]), "+f"(d[35]), "+f"(d[36]), "+f"(d[37]), "+f"(d[38]), "+f"(d[39]), "+f"(d[40]), "+f"(d[41]), "+f"(d[42]), "+f"(d[43]), "+f"(d[44]), "+f"(d[45]), "+f"(d[46]), "+f"(d[47]), "+f"(d[48]), "+f"(d[49]), "+f"(d[50]), "+f"(d[51]), "+f"(d[52]), "+f"(d[53]), "+f"(d[54]), "+f"(d[55]), "+f"(d[56]), "+f"(d[57]), "+f"(d[58]), "+f"(d[59]), "+f"(d[60]), "+f"(d[61]), "+f"(d[62]), "+f"(d[63]), "+f"(d[64]), "+f"(d[65]), "+f"(d[66]), "+f"(d[67]), "+f"(d[68]), "+f"(d[69]), "+f"(d[70]), "+f"(d[71]), "+f"(d[72]), "+f"(d[73]), "+f"(d[74]), "+f"(d[75]), "+f"(d[76]), "+f"(d[77]), "+f"(d[78]), "+f"(d[79]), "+f"(d[80]), "+f"(d[81]), "+f"(d[82]), "+f"(d[83]), "+f"(d[84]), "+f"(d[85]), "+f"(d[86]), "+f"(d[87]), "+f"(d[88]), "+f"(d[89]), "+f"(d[90]), "+f"(d[91]), "+f"(d[92]), "+f"(d[93]), "+f"(d[94]), "+f"(d[95]), "+f"(d[96]), "+f"(d[97]), "+f"(d[98]), "+f"(d[99]), "+f"(d[100]), "+f"(d[101]), "+f"(d[102]), "+f"(d[103]), "+f"(d[104]), "+f"(d[105]), "+f"(d[106]), "+f"(d[107]), "+f"(d[108]), "+f"(d[109]), "+f"(d[110]), "+f"(d[111]), "+f"(d[112]), "+f"(d[113]), "+f"(d[114]), "+f"(d[115]), "+f"(d[116]), "+f"(d[117]), "+f"(d[118]), "+f"(d[119]), "+f"(d[120]), "+f"(d[121]), "+f"(d[122]), "+f"(d[123]), "+f"(d[124]), "+f"(d[125]), "+f"(d[126]), "+f"(d[127])
            : "l"(da), "l"(db), "r"(sd));
    }
};
template <int W>
__device__ __forceinline__ void ln_row(const bf16* __restrict__ src, bf16* __restrict__ dst, int lane) {
    constexpr int NP = W / 64;
    constexpr int REM = (W / 2) % 32;
    uint32_t v[NP + 1];
    const uint32_t* s32 = reinterpret_cast<const uint32_t*>(src);
    float sum = 0.f;
#pragma unroll
    for (int i = 0; i < NP; i++) { v[i] = s32[i * 32 + lane]; sum += lo_f(v[i]) + hi_f(v[i]); }
    if (REM) { v[NP] = (lane < REM) ? s32[NP * 32 + lane] : 0u; if (lane < REM) sum += lo_f(v[NP]) + hi_f(v[NP]); }
#pragma unroll
    for (int o = 16; o; o >>= 1) sum += __shfl_xor_sync(0xffffffffu, sum, o);
    float mean = sum * (1.0f / W);
    float vs = 0.f;
#pragma unroll
    for (int i = 0; i < NP; i++) { float a = lo_f(v[i]) - mean, b = hi_f(v[i]) - mean; vs += a * a + b * b; }
    if (REM && lane < REM) { float a = lo_f(v[NP]) - mean, b = hi_f(v[NP]) - mean; vs += a * a + b * b; }
#pragma unroll
    for (int o = 16; o; o >>= 1) vs += __shfl_xor_sync(0xffffffffu, vs, o);
    float var = rbf(vs * (1.0f / W));
    float mb = rbf(mean);
    float den = rbf(sqrtf(rbf(var + 1e-5f)));
    uint32_t* d32 = reinterpret_cast<uint32_t*>(dst);
#pragma unroll
    for (int i = 0; i < NP; i++) d32[i * 32 + lane] = pack_bf16(rbf(lo_f(v[i]) - mb) / den, rbf(hi_f(v[i]) - mb) / den);
    if (REM && lane < REM) d32[NP * 32 + lane] = pack_bf16(rbf(lo_f(v[NP]) - mb) / den, rbf(hi_f(v[NP]) - mb) / den);
}

__global__ void ln_kernel(const bf16* __restrict__ x) {
    int row = blockIdx.x * 8 + (threadIdx.x >> 5);
    ln_row<D_>(x + (size_t)row * D_, g_xn + (size_t)row * D_, threadIdx.x & 31);
}
__global__ void ln2_kernel() {
    int row = blockIdx.x * 8 + (threadIdx.x >> 5);
    bf16* p = g_z + (size_t)row * F_ + FH_;
    ln_row<FH_>(p, p, threadIdx.x & 31);
}

enum { EPI_STORE = 0, EPI_GELU = 1, EPI_SP = 2, EPI_SILU = 3, EPI_FINAL = 4, EPI_PART = 5 };
__device__ float g_part[2 * S_ * D_];
struct EpiParams {
    bf16* out; int ldo;
    const bf16* aux0;
    const bf16* aux1;
};

__device__ __forceinline__ float gelu_tanh_f(float x) {
    const float k0 = 0.7978845608028654f, k1 = 0.044715f;
    float inner = k0 * (x + k1 * x * x * x);
    return 0.5f * x * (1.0f + tanhf(inner));
}
__device__ __forceinline__ float silu_f(float x) { return x / (1.0f + expf(-x)); }

template <int BN, int EPI>
__global__ void __launch_bounds__(384, 1)
gemm_kernel(const __grid_constant__ CUtensorMap tmA, const __grid_constant__ CUtensorMap tmB0,
            const __grid_constant__ CUtensorMap tmB1, const __grid_constant__ CUtensorMap tmB2,
            int nPerB, int N, int K, EpiParams ep) {
    constexpr int BM = 128, BK = 64;
    constexpr int A_BYTES = BM * BK * 2;
    constexpr int B_BYTES = (BN / 64) * 8192;
    constexpr int STAGE = A_BYTES + B_BYTES;
    constexpr int NST = (200 * 1024) / STAGE;
    constexpr int OLD = BN + 8;
    extern __shared__ __align__(1024) uint8_t smem_raw[];
    uint8_t* smem = (uint8_t*)(((uintptr_t)smem_raw + 1023) & ~(uintptr_t)1023);
    __shared__ __align__(8) uint64_t full_bar[NST], empty_bar[NST];

    const int tid = threadIdx.x, wg = tid >> 7;
    const int m0 = blockIdx.y * BM, n0 = blockIdx.x * BN;
    const int nk = (K + BK - 1) / BK / gridDim.z;
    const int kbase = blockIdx.z * nk;

    if (tid == 0) {
        for (int i = 0; i < NST; i++) { mbar_init(smem_u32(&full_bar[i]), 1); mbar_init(smem_u32(&empty_bar[i]), 2); }
        asm volatile("fence.mbarrier_init.release.cluster;" ::: "memory");
    }
    __syncthreads();

    if (wg == 0) {
        if (tid == 0) {
            const int bsel = n0 / nPerB;
            const CUtensorMap* tmB = bsel == 0 ? &tmB0 : (bsel == 1 ? &tmB1 : &tmB2);
            const int nb = n0 - bsel * nPerB;
            for (int kt = 0; kt < nk; kt++) {
                int st = kt % NST; uint32_t ph = (kt / NST) & 1;
                mbar_wait(smem_u32(&empty_bar[st]), ph ^ 1);
                uint32_t fb = smem_u32(&full_bar[st]);
                mbar_expect_tx(fb, STAGE);
                uint32_t sa = smem_u32(smem + st * STAGE);
                tma_load_2d(sa, &tmA, fb, (kbase + kt) * BK, m0);
#pragma unroll
                for (int j = 0; j < BN / 64; j++) tma_load_2d(sa + A_BYTES + j * 8192, tmB, fb, nb + j * 64, (kbase + kt) * BK);
            }
        }
    } else {
        const int cw = wg - 1;
        float acc[BN / 2];
        for (int kt = 0; kt < nk; kt++) {
            int st = kt % NST; uint32_t ph = (kt / NST) & 1;
            mbar_wait(smem_u32(&full_bar[st]), ph);
            uint32_t sa = smem_u32(smem + st * STAGE) + cw * 64 * 128;
            uint32_t sb = smem_u32(smem + st * STAGE) + A_BYTES;
            wgmma_fence();
#pragma unroll
            for (int k = 0; k < BK / 16; k++) {
                uint64_t da = make_desc(sa + k * 32, 16, 1024);
                uint64_t db = make_desc(sb + k * 2048, 8192, 1024);
                Wgmma<BN>::mma(acc, da, db, (kt | k) != 0);
            }
            wgmma_commit();
            wgmma_wait<1>();
            if (kt > 0 && (tid & 127) == 0) mbar_arrive(smem_u32(&empty_bar[(kt - 1) % NST]));
        }
        wgmma_wait<0>();
        if (EPI == EPI_PART) {
            const int lane = tid & 31, wi = (tid >> 5) & 3, g = lane >> 2, t = lane & 3;
            float* dst = g_part + (size_t)blockIdx.z * (S_ * D_) + (size_t)(m0 + cw * 64 + wi * 16 + g) * D_ + n0 + 2 * t;
#pragma unroll
            for (int j = 0; j < BN / 8; j++) {
                *reinterpret_cast<float2*>(dst + j * 8) = make_float2(acc[4 * j], acc[4 * j + 1]);
                *reinterpret_cast<float2*>(dst + 8 * D_ + j * 8) = make_float2(acc[4 * j + 2], acc[4 * j + 3]);
            }
            return;
        }
        asm volatile("bar.sync 1, 256;" ::: "memory");
        const int lane = tid & 31, wi = (tid >> 5) & 3, g = lane >> 2, t = lane & 3;
        bf16* stg = reinterpret_cast<bf16*>(smem) + cw * 64 * OLD;
#pragma unroll
        for (int j = 0; j < BN / 8; j++) {
            *reinterpret_cast<uint32_t*>(&stg[(wi * 16 + g) * OLD + j * 8 + 2 * t]) = pack_bf16(acc[4 * j], acc[4 * j + 1]);
            *reinterpret_cast<uint32_t*>(&stg[(wi * 16 + g + 8) * OLD + j * 8 + 2 * t]) = pack_bf16(acc[4 * j + 2], acc[4 * j + 3]);
        }
        asm volatile("bar.sync %0, 128;" ::"r"(2 + cw) : "memory");
        constexpr int CPR = BN / 8;
        const int ltid = tid & 127;
#pragma unroll 4
        for (int i = ltid; i < 64 * CPR; i += 128) {
            int r = i / CPR, ch = i % CPR;
            int row = m0 + cw * 64 + r, col = n0 + ch * 8;
            if (col >= N) continue;
            uint4 v = *reinterpret_cast<const uint4*>(&stg[r * OLD + ch * 8]);
            uint32_t u[4] = {v.x, v.y, v.z, v.w}, o[4];
            if (EPI == EPI_STORE) {
#pragma unroll
                for (int q = 0; q < 4; q++) o[q] = u[q];
            } else if (EPI == EPI_GELU) {
#pragma unroll
                for (int q = 0; q < 4; q++) o[q] = pack_bf16(gelu_tanh_f(lo_f(u[q])), gelu_tanh_f(hi_f(u[q])));
            } else if (EPI == EPI_SP) {
                float bb = bf2f(ep.aux1[row]);
                uint4 z = *reinterpret_cast<const uint4*>(ep.aux0 + (size_t)row * F_ + col);
                uint32_t zz[4] = {z.x, z.y, z.z, z.w};
#pragma unroll
                for (int q = 0; q < 4; q++) o[q] = pack_bf16(lo_f(zz[q]) * rbf(lo_f(u[q]) + bb), hi_f(zz[q]) * rbf(hi_f(u[q]) + bb));
            } else if (EPI == EPI_SILU) {
#pragma unroll
                for (int q = 0; q < 4; q++) o[q] = pack_bf16(silu_f(lo_f(u[q])), silu_f(hi_f(u[q])));
            } else {
                uint4 xv = *reinterpret_cast<const uint4*>(ep.aux0 + (size_t)row * D_ + col);
                uint4 gv = *reinterpret_cast<const uint4*>(ep.aux1 + (size_t)row * D_ + col);
                uint32_t xx[4] = {xv.x, xv.y, xv.z, xv.w}, gg[4] = {gv.x, gv.y, gv.z, gv.w};
#pragma unroll
                for (int q = 0; q < 4; q++)
                    o[q] = pack_bf16(lo_f(xx[q]) + rbf(lo_f(u[q]) * lo_f(gg[q])), hi_f(xx[q]) + rbf(hi_f(u[q]) * hi_f(gg[q])));
            }
            *reinterpret_cast<uint4*>(ep.out + (size_t)row * ep.ldo + col) = make_uint4(o[0], o[1], o[2], o[3]);
        }
    }
}

__global__ void final_combine_kernel(const bf16* __restrict__ x, bf16* __restrict__ out) {
    int i = (blockIdx.x * blockDim.x + threadIdx.x) * 4;
    float4 a = *reinterpret_cast<const float4*>(g_part + i), b = *reinterpret_cast<const float4*>(g_part + S_ * D_ + i);
    uint2 xv = *reinterpret_cast<const uint2*>(x + i), gv = *reinterpret_cast<const uint2*>(g_gate + i);
    float s0 = rbf(a.x + b.x), s1 = rbf(a.y + b.y), s2 = rbf(a.z + b.z), s3 = rbf(a.w + b.w);
    uint2 o;
    o.x = pack_bf16(lo_f(xv.x) + rbf(s0 * lo_f(gv.x)), hi_f(xv.x) + rbf(s1 * hi_f(gv.x)));
    o.y = pack_bf16(lo_f(xv.y) + rbf(s2 * lo_f(gv.y)), hi_f(xv.y) + rbf(s3 * hi_f(gv.y)));
    *reinterpret_cast<uint2*>(out + i) = o;
}

__device__ __forceinline__ void mma16816(float* c, const uint32_t* a, uint32_t b0, uint32_t b1) {
    asm volatile(
        "mma.sync.aligned.m16n8k16.row.col.f32.bf16.bf16.f32 {%0,%1,%2,%3}, {%4,%5,%6,%7}, {%8,%9}, {%0,%1,%2,%3};"
        : "+f"(c[0]), "+f"(c[1]), "+f"(c[2]), "+f"(c[3])
        : "r"(a[0]), "r"(a[1]), "r"(a[2]), "r"(a[3]), "r"(b0), "r"(b1));
}
__device__ __forceinline__ void ldsm_x4(uint32_t* r, uint32_t addr) {
    asm volatile("ldmatrix.sync.aligned.m8n8.x4.shared.b16 {%0,%1,%2,%3}, [%4];"
                 : "=r"(r[0]), "=r"(r[1]), "=r"(r[2]), "=r"(r[3]) : "r"(addr));
}
__device__ __forceinline__ void ldsm_x4_t(uint32_t* r, uint32_t addr) {
    asm volatile("ldmatrix.sync.aligned.m8n8.x4.trans.shared.b16 {%0,%1,%2,%3}, [%4];"
                 : "=r"(r[0]), "=r"(r[1]), "=r"(r[2]), "=r"(r[3]) : "r"(addr));
}
__device__ __forceinline__ uint4 ld_relaxed_v4(const void* p) {
    uint4 v;
    asm volatile("ld.relaxed.gpu.global.v4.u32 {%0,%1,%2,%3}, [%4];" : "=r"(v.x), "=r"(v.y), "=r"(v.z), "=r"(v.w) : "l"(p) : "memory");
    return v;
}
__device__ __forceinline__ void st_relaxed_v4(void* p, uint32_t a, uint32_t b, uint32_t c, uint32_t d) {
    asm volatile("st.relaxed.gpu.global.v4.u32 [%0], {%1,%2,%3,%4};" ::"l"(p), "r"(a), "r"(b), "r"(c), "r"(d) : "memory");
}
__device__ __forceinline__ void st_relaxed_v2(void* p, uint32_t a, uint32_t b) {
    asm volatile("st.relaxed.gpu.global.v2.u32 [%0], {%1,%2};" ::"l"(p), "r"(a), "r"(b) : "memory");
}
__device__ __forceinline__ void cp_async16(uint32_t dst, const void* src) {
    asm volatile("cp.async.cg.shared.global [%0], [%1], 16;" ::"r"(dst), "l"(src) : "memory");
}
__device__ __forceinline__ void cp_async_commit() { asm volatile("cp.async.commit_group;" ::: "memory"); }
template <int N> __device__ __forceinline__ void cp_async_wait() { asm volatile("cp.async.wait_group %0;" ::"n"(N) : "memory"); }

#define PROF(i) do {} while (0)
constexpr int SPIN_LIMIT = 4000000;

__device__ __forceinline__ uint4 poll_ll(const void* p, uint32_t flag) {
    uint4 v = ld_relaxed_v4(p);
    int n = 0;
    while ((v.y != flag || v.w != flag) && ++n < SPIN_LIMIT) {
        v = ld_relaxed_v4(p);
    }
    return v;
}

constexpr int RT = 512;
constexpr bool FUSE_X = false;
constexpr int MEMS_LD = D_ + 8;
constexpr int HL = DH_ + 8;
struct RecurSmem {
    bf16 mem[MEM_][MEMS_LD];
    bf16 kall[2][48][HL];
    bf16 vall[2][48][HL];
    bf16 qm[16][HL];
    float sc[MEM_][40];
    bf16 p[MEM_][48 + 8];
    bf16 om[MEM_][HL];
    float red[12][16 * 8];
    float wred[2][5][16 * 8];
    bf16 xs[2][SEG_][MEMS_LD];
    float redx[6][4][16 * 8];
    bf16 xo[SEG_][96 + 8];
};

__device__ __forceinline__ void bar_sync(int id, int n) { asm volatile("bar.sync %0, %1;" ::"r"(id), "r"(n) : "memory"); }
__device__ __forceinline__ void bar_arrive(int id, int n) { asm volatile("bar.arrive %0, %1;" ::"r"(id), "r"(n) : "memory"); }
__device__ __forceinline__ void sts64(uint32_t a, uint32_t x, uint32_t y) { asm volatile("st.shared.v2.u32 [%0], {%1,%2};" ::"r"(a), "r"(x), "r"(y) : "memory"); }
__device__ __forceinline__ uint32_t ldg_u16x2(const bf16* p0, const bf16* p1) {
    return (uint32_t)*(const uint16_t*)p0 | ((uint32_t)*(const uint16_t*)p1 << 16);
}
enum { BAR_MEM = 1, BAR_RED = 2, BAR_CTL = 3, BAR_WO = 4, BAR_INIT = 6, BAR_X = 7, BAR_GO = 8 };

__global__ void __launch_bounds__(RT, 1)
recur_kernel(const bf16* __restrict__ mem0, const bf16* __restrict__ Wq, const bf16* __restrict__ Wk,
             const bf16* __restrict__ Wv, const bf16* __restrict__ Wo) {
    extern __shared__ __align__(16) uint8_t smem_raw[];
    RecurSmem& sm = *reinterpret_cast<RecurSmem*>(smem_raw);
    const int tid = threadIdx.x, lane = tid & 31, w = tid >> 5;
    const int g = lane >> 2, t = lane & 3;
    const int h = blockIdx.x >> 2, c = blockIdx.x & 3;

    if (w < 12) {
        asm volatile("setmaxnreg.dec.sync.aligned.u32 104;");
        uint32_t wf[20][4];
        const int mt = w % 6, kh = w / 6;
        {
            const bf16* W = (mt < 2) ? Wq : (mt < 4 ? Wk : Wv);
            int f0 = h * DH_ + c * 32 + (mt & 1) * 16;
            uint32_t stg = smem_u32(smem_raw) + w * 10240;
#pragma unroll 4
            for (int i = lane; i < 640; i += 32)
                cp_async16(stg + i * 16, W + (size_t)(kh * 320 + (i >> 1)) * HD_ + f0 + (i & 1) * 8);
            cp_async_commit(); cp_async_wait<0>(); __syncwarp();
            uint32_t la = stg + ((lane & 7) + ((lane >> 4) & 1) * 8) * 32 + ((lane >> 3) & 1) * 16;
#pragma unroll
            for (int i = 0; i < 20; i++) ldsm_x4_t(wf[i], la + i * 512);
        }
        bar_sync(BAR_INIT, RT);
        const uint32_t base = smem_u32(&sm.mem[lane & 7][kh * 320 + (lane >> 3) * 8]);
        const uint32_t rp = smem_u32(&sm.red[w][g * 8 + 2 * t]);
        const uint32_t xbase0 = smem_u32(&sm.xs[0][lane & 7][kh * 320 + (lane >> 3) * 8]);
        uint32_t xbase = xbase0;
        const uint32_t rxp = smem_u32(&sm.redx[mt][0][lane * 4]);
        auto load_x = [&](int seg) {
            for (int i = tid; i < SEG_ * (D_ / 8); i += 384) {
                int r = i / (D_ / 8), ch = i % (D_ / 8);
                cp_async16(smem_u32(&sm.xs[seg & 1][r][ch * 8]), g_xn + (size_t)(seg * SEG_ + r) * D_ + ch * 8);
            }
            cp_async_commit();
        };
        float acc[4][4];
        auto xhalf = [&](int n0) {
#pragma unroll
            for (int nt = 0; nt < 2; nt++) { acc[n0 + nt][0] = acc[n0 + nt][1] = acc[n0 + nt][2] = acc[n0 + nt][3] = 0.f; }
#pragma unroll
            for (int i = 0; i < 10; i++) {
#pragma unroll
                for (int nt = 0; nt < 2; nt++) {
                    uint32_t b[4];
                    ldsm_x4(b, xbase + (n0 + nt) * (8 * MEMS_LD * 2) + i * 64);
                    mma16816(acc[n0 + nt], wf[2 * i], b[0], b[1]);
                    mma16816(acc[n0 + nt], wf[2 * i + 1], b[2], b[3]);
                }
            }
        };
        auto xworkA = [&](int seg) {
            cp_async_wait<0>();
            bar_sync(BAR_X, 384);
            if (seg + 1 < NSEG_) load_x(seg + 1);
            xbase = xbase0 + (seg & 1) * (SEG_ * MEMS_LD * 2);
            xhalf(0);
        };
        auto xwork = [&](int seg) {
            xhalf(2);
            if (kh == 1) {
#pragma unroll
                for (int nt = 0; nt < 4; nt++)
                    asm volatile("st.shared.v4.f32 [%0], {%1,%2,%3,%4};" ::"r"(rxp + nt * 512), "f"(acc[nt][0]), "f"(acc[nt][1]), "f"(acc[nt][2]), "f"(acc[nt][3]) : "memory");
            }
            bar_sync(BAR_X, 384);
            if (kh == 0) {
#pragma unroll
                for (int nt = 0; nt < 4; nt++) {
                    float4 o;
                    asm volatile("ld.shared.v4.f32 {%0,%1,%2,%3}, [%4];" : "=f"(o.x), "=f"(o.y), "=f"(o.z), "=f"(o.w) : "r"(rxp + nt * 512) : "memory");
                    bf16* d = &sm.xo[nt * 8 + 2 * t][mt * 16 + g];
                    d[0] = __float2bfloat16_rn(acc[nt][0] + o.x);
                    d[104] = __float2bfloat16_rn(acc[nt][1] + o.y);
                    d[8] = __float2bfloat16_rn(acc[nt][2] + o.z);
                    d[104 + 8] = __float2bfloat16_rn(acc[nt][3] + o.w);
                }
            }
            bar_sync(BAR_X, 384);
            {
                int r = tid / 12, ch = tid % 12;
                uint4 v = *reinterpret_cast<const uint4*>(&sm.xo[r][ch * 8]);
                *reinterpret_cast<uint4*>(g_qkv + (size_t)(seg * SEG_ + r) * (3 * HD_) + (ch >> 2) * HD_ + h * DH_ + c * 32 + (ch & 3) * 8) = v;
            }
        };
        auto xsignal = [&](int seg) {
            __threadfence();
            __syncwarp();
            if (lane == 0) atomicAdd(&g_xcnt[h * NSEG_ + seg], 1u);
        };
        if (FUSE_X) {
            load_x(0);
            xworkA(0); xwork(0); xsignal(0);
            xworkA(1); xwork(1); xsignal(1);
        }
        for (int s = 0; s < NSEG_; s++) {
            bar_sync(BAR_MEM, RT);
            float a0[4] = {0.f, 0.f, 0.f, 0.f}, a1[4] = {0.f, 0.f, 0.f, 0.f};
#pragma unroll
            for (int i = 0; i < 10; i++) {
                uint32_t b[4];
                ldsm_x4(b, base + i * 64);
                mma16816(a0, wf[2 * i], b[0], b[1]);
                mma16816(a1, wf[2 * i + 1], b[2], b[3]);
            }
            sts64(rp, __float_as_uint(a0[0] + a1[0]), __float_as_uint(a0[1] + a1[1]));
            sts64(rp + 256, __float_as_uint(a0[2] + a1[2]), __float_as_uint(a0[3] + a1[3]));
            bar_arrive(BAR_RED, RT);
            if (FUSE_X) {
                if (s + 2 < NSEG_) xworkA(s + 2);
                if (s >= 1 && s + 1 < NSEG_) xsignal(s + 1);
                if (s + 1 < NSEG_) bar_sync(BAR_GO, RT);
                if (s + 2 < NSEG_) xwork(s + 2);
            }
        }
    } else {
        asm volatile("setmaxnreg.inc.sync.aligned.u32 200;");
        const int ct = tid - 384, cw = w - 12;
        const int mg = cw >> 1, kh = cw & 1;
        uint32_t wf[20][4];
        {
            uint32_t stg = smem_u32(smem_raw) + 12 * 10240 + cw * 10240;
#pragma unroll 4
            for (int i = lane; i < 640; i += 32) {
                int r = i / 10, ch = i % 10;
                cp_async16(stg + r * 160 + ch * 16, Wo + (size_t)(h * DH_ + kh * 64 + r) * D_ + c * 160 + mg * 80 + ch * 8);
            }
            cp_async_commit(); cp_async_wait<0>(); __syncwarp();
            uint32_t la = stg + ((lane & 7) + ((lane >> 4) & 1) * 8) * 160 + ((lane >> 3) & 1) * 16;
#pragma unroll
            for (int mi = 0; mi < 5; mi++)
#pragma unroll
                for (int ki = 0; ki < 4; ki++) ldsm_x4_t(wf[mi * 4 + ki], la + ki * 16 * 160 + mi * 32);
        }
        bar_sync(BAR_INIT, RT);
        for (int i = ct; i < 2 * 8 * HL; i += 128) {
            int b = i / (8 * HL), r = (i / HL) % 8, cc = i % HL;
            sm.kall[b][40 + r][cc] = __float2bfloat16(0.f);
            sm.vall[b][40 + r][cc] = __float2bfloat16(0.f);
        }
        for (int i = ct; i < 8 * HL; i += 128) sm.qm[8 + i / HL][i % HL] = __float2bfloat16(0.f);
        for (int i = ct; i < 8 * 56; i += 128) sm.p[i / 56][i % 56] = __float2bfloat16(0.f);
        bar_sync(BAR_CTL, 128);
        constexpr uint32_t KV_BUF = 48 * HL * 2;
        const bf16* kv_src = g_qkv + (size_t)(ct >> 4) * (3 * HD_) + HD_ + h * DH_ + (ct & 15) * 8;
        const uint32_t kv_dst0 = smem_u32(&sm.kall[0][MEM_ + (ct >> 4)][(ct & 15) * 8]);
        const uint32_t kv_dst1 = smem_u32(&sm.vall[0][MEM_ + (ct >> 4)][(ct & 15) * 8]);
        auto prefetch_kv = [&](int s, int buf) {
            if (FUSE_X) {
                if (ct == 0) {
                    const unsigned* cp = g_xcnt + h * NSEG_ + s;
                    unsigned v; int n = 0;
                    do { asm volatile("ld.acquire.gpu.global.u32 %0, [%1];" : "=r"(v) : "l"(cp) : "memory"); } while (v < 48u && ++n < SPIN_LIMIT);
                }
                bar_sync(BAR_CTL, 128);
            }
            const bf16* src = kv_src + (size_t)s * SEG_ * (3 * HD_);
#pragma unroll
            for (int j = 0; j < 4; j++) {
                cp_async16(kv_dst0 + buf * KV_BUF + j * (8 * HL * 2), src + (size_t)j * 8 * (3 * HD_));
                cp_async16(kv_dst1 + buf * KV_BUF + j * (8 * HL * 2), src + (size_t)j * 8 * (3 * HD_) + HD_);
            }
            cp_async_commit();
        };
        const float4* acc_src = reinterpret_cast<const float4*>(g_acc) + ct;
        const uint32_t acc_dst = smem_u32(&sm.mem[(ct & 1) * 4][ct >> 1]);
        const uint4* hx_base = reinterpret_cast<const uint4*>(g_hx) + h * 1024;
        const int hx_rq = ct & 63, hx_half = ct >> 6;
        const uint4* hx_src = hx_base + hx_half * 64 + hx_rq;
        const uint32_t hx_col = (hx_rq & 7) * 8, hx_r = hx_rq >> 3;
        const uint32_t hx_dstA = (hx_half == 0 ? smem_u32(&sm.qm[hx_r][0]) : smem_u32(&sm.kall[0][hx_r][0])) + hx_col;
        const uint32_t hx_dstB = smem_u32(&sm.vall[0][hx_r][0]) + hx_col;
        const uint4* hx_probe = hx_base + (lane >> 3) * 256 + ((lane & 7) % 3) * 64 + (lane & 7) * 8 + 3;
        const int pb_r = ct >> 4, pb_pr = ct & 15;
        uint2* pb_dst = g_hx + (h * 1024 + c * 256 + pb_r * 8) * 2 + pb_pr;
        const float* pb_src = &sm.red[pb_pr >> 3][(pb_pr & 7) * 16 + pb_r];
        bf16* pb_k = g_kmem + (size_t)pb_r * HD_ + h * DH_ + c * 32 + pb_pr * 2;
        bf16* pb_v = g_vmem + (size_t)pb_r * HD_ + h * DH_ + c * 32 + pb_pr * 2;
        const uint32_t qb = smem_u32(&sm.qm[lane & 7][(lane >> 3) * 8]);
        const uint32_t ka0 = smem_u32(&sm.kall[0][lane & 15][(lane >> 4) * 8]);
        const uint32_t va0 = smem_u32(&sm.vall[0][(lane & 7) + ((lane >> 4) & 1) * 8][cw * 32 + ((lane >> 3) & 1) * 8]);
        const uint32_t ob = smem_u32(&sm.om[lane & 7][kh * 64 + (lane >> 3) * 8]);
        float* acc_dst_g = g_acc + (c * 160 + mg * 80 + g) * 8 + 2 * t;

        prefetch_kv(0, 0);
        for (int s = 0; s < NSEG_; s++) {
            const int buf = s & 1;
            const uint32_t flag = s + 1;
            const uint32_t bo = buf * KV_BUF;
            PROF(0);
            if (s == 0) {
                for (int i = ct; i < MEM_ * D_ / 8; i += 128) {
                    int r = i / (D_ / 8), cc = (i % (D_ / 8)) * 8;
                    *reinterpret_cast<uint4*>(&sm.mem[r][cc]) = *reinterpret_cast<const uint4*>(mem0 + r * D_ + cc);
                }
            } else {
                if (ct == 0) {
                    const unsigned* cp = g_cnt + (s - 1) * 32;
                    unsigned v; int n = 0;
                    do { asm volatile("ld.acquire.gpu.global.u32 %0, [%1];" : "=r"(v) : "l"(cp) : "memory"); } while (v < 256u && ++n < SPIN_LIMIT);
                }
                bar_sync(BAR_CTL, 128);
                PROF(1);
                const float4* src = acc_src + (size_t)(s - 1) * (MEM_ * D_ / 4);
                float4 v[10];
#pragma unroll
                for (int j = 0; j < 10; j++)
                    asm volatile("ld.relaxed.gpu.global.v4.f32 {%0,%1,%2,%3}, [%4];" : "=f"(v[j].x), "=f"(v[j].y), "=f"(v[j].z), "=f"(v[j].w) : "l"(src + 128 * j) : "memory");
#pragma unroll
                for (int j = 0; j < 10; j++) {
                    uint32_t lo = pack_bf16(v[j].x, v[j].y), hi = pack_bf16(v[j].z, v[j].w);
                    uint32_t d = acc_dst + j * 128;
                    asm volatile("st.shared.u16 [%0], %1;" ::"r"(d), "h"((uint16_t)(lo & 0xffff)) : "memory");
                    asm volatile("st.shared.u16 [%0], %1;" ::"r"(d + MEMS_LD * 2), "h"((uint16_t)(lo >> 16)) : "memory");
                    asm volatile("st.shared.u16 [%0], %1;" ::"r"(d + MEMS_LD * 4), "h"((uint16_t)(hi & 0xffff)) : "memory");
                    asm volatile("st.shared.u16 [%0], %1;" ::"r"(d + MEMS_LD * 6), "h"((uint16_t)(hi >> 16)) : "memory");
                }
            }
            bar_arrive(BAR_MEM, RT);
            PROF(2);
            bar_sync(BAR_RED, RT);
            PROF(3);
            {
                uint32_t pk0 = pack_bf16(pb_src[0] + pb_src[768], pb_src[8] + pb_src[768 + 8]);
                uint32_t pk1 = pack_bf16(pb_src[256] + pb_src[1024], pb_src[256 + 8] + pb_src[1024 + 8]);
                uint32_t pk2 = pack_bf16(pb_src[512] + pb_src[1280], pb_src[512 + 8] + pb_src[1280 + 8]);
                st_relaxed_v2(pb_dst, pk0, flag);
                st_relaxed_v2(pb_dst + 128, pk1, flag);
                st_relaxed_v2(pb_dst + 256, pk2, flag);
                *reinterpret_cast<uint32_t*>(pb_k + (size_t)s * (MEM_ * HD_)) = pk1;
                *reinterpret_cast<uint32_t*>(pb_v + (size_t)s * (MEM_ * HD_)) = pk2;
            }
            if (s == NSEG_ - 1) break;
            PROF(4);
            PROF(5);
            {
                uint4 v[8];
#pragma unroll
                for (int j = 0; j < 4; j++) v[j] = ld_relaxed_v4(hx_src + j * 256);
                if (hx_half == 0) {
#pragma unroll
                    for (int j = 0; j < 4; j++) v[4 + j] = ld_relaxed_v4(hx_src + j * 256 + 128);
                }
#pragma unroll
                for (int j = 0; j < 4; j++) {
                    if (v[j].y != flag || v[j].w != flag) v[j] = poll_ll(hx_src + j * 256, flag);
                    sts64(hx_dstA + j * 64 + (hx_half ? bo : 0), v[j].x, v[j].z);
                }
                if (hx_half == 0) {
#pragma unroll
                    for (int j = 0; j < 4; j++) {
                        if (v[4 + j].y != flag || v[4 + j].w != flag) v[4 + j] = poll_ll(hx_src + j * 256 + 128, flag);
                        sts64(hx_dstB + j * 64 + bo, v[4 + j].x, v[4 + j].z);
                    }
                }
            }
            cp_async_wait<0>();
            bar_sync(BAR_CTL, 128);
            PROF(6);
            {
                uint32_t bq[4][4];
#pragma unroll
                for (int kk = 0; kk < 4; kk++) ldsm_x4(bq[kk], qb + kk * 64);
                float sc[3][4];
#pragma unroll
                for (int m = 0; m < 3; m++) {
                    uint32_t a[8][4];
#pragma unroll
                    for (int kk = 0; kk < 8; kk++) ldsm_x4(a[kk], ka0 + bo + m * (16 * HL * 2) + kk * 32);
                    float s0[4] = {0.f, 0.f, 0.f, 0.f}, s1[4] = {0.f, 0.f, 0.f, 0.f};
#pragma unroll
                    for (int kk = 0; kk < 4; kk++) { mma16816(s0, a[2 * kk], bq[kk][0], bq[kk][1]); mma16816(s1, a[2 * kk + 1], bq[kk][2], bq[kk][3]); }
#pragma unroll
                    for (int e = 0; e < 4; e++) sc[m][e] = rbf(rbf(s0[e] + s1[e]) * 0.08838834764831845f);
                }
                uint32_t av[2][3][4];
#pragma unroll
                for (int kt = 0; kt < 3; kt++) { ldsm_x4_t(av[0][kt], va0 + bo + kt * 16 * HL * 2); ldsm_x4_t(av[1][kt], va0 + bo + kt * 16 * HL * 2 + 32); }
                float mx0 = fmaxf(fmaxf(fmaxf(sc[0][0], sc[0][2]), fmaxf(sc[1][0], sc[1][2])), sc[2][0]);
                float mx1 = fmaxf(fmaxf(fmaxf(sc[0][1], sc[0][3]), fmaxf(sc[1][1], sc[1][3])), sc[2][1]);
#pragma unroll
                for (int o = 4; o < 32; o <<= 1) { mx0 = fmaxf(mx0, __shfl_xor_sync(0xffffffffu, mx0, o)); mx1 = fmaxf(mx1, __shfl_xor_sync(0xffffffffu, mx1, o)); }
                float sum0 = 0.f, sum1 = 0.f;
#pragma unroll
                for (int m = 0; m < 3; m++) {
#pragma unroll
                    for (int e = 0; e < 4; e++) {
                        if (m == 2 && e >= 2) { sc[m][e] = 0.f; continue; }
                        float ev = __expf(sc[m][e] - ((e & 1) ? mx1 : mx0));
                        sc[m][e] = ev;
                        if (e & 1) sum1 += ev; else sum0 += ev;
                    }
                }
#pragma unroll
                for (int o = 4; o < 32; o <<= 1) { sum0 += __shfl_xor_sync(0xffffffffu, sum0, o); sum1 += __shfl_xor_sync(0xffffffffu, sum1, o); }
                float i0 = 1.0f / sum0, i1 = 1.0f / sum1;
                uint32_t pb[3][2];
#pragma unroll
                for (int m = 0; m < 3; m++) {
#pragma unroll
                    for (int hh = 0; hh < 2; hh++) {
                        uint32_t pk = pack_bf16(sc[m][2 * hh] * i0, sc[m][2 * hh + 1] * i1);
                        asm volatile("movmatrix.sync.aligned.m8n8.trans.b16 %0, %1;" : "=r"(pb[m][hh]) : "r"(pk));
                    }
                }
                PROF(7);
#pragma unroll
                for (int m = 0; m < 2; m++) {
                    float o[4] = {0.f, 0.f, 0.f, 0.f};
#pragma unroll
                    for (int kt = 0; kt < 3; kt++) mma16816(o, av[m][kt], pb[kt][0], pb[kt][1]);
                    int d0 = cw * 32 + m * 16 + g;
                    sm.om[2 * t][d0] = __float2bfloat16_rn(o[0]);
                    sm.om[2 * t + 1][d0] = __float2bfloat16_rn(o[1]);
                    sm.om[2 * t][d0 + 8] = __float2bfloat16_rn(o[2]);
                    sm.om[2 * t + 1][d0 + 8] = __float2bfloat16_rn(o[3]);
                }
            }
            bar_sync(BAR_CTL, 128);
            PROF(8);
            {
                float acc[5][4];
#pragma unroll
                for (int mi = 0; mi < 5; mi++) { acc[mi][0] = acc[mi][1] = acc[mi][2] = acc[mi][3] = 0.f; }
                uint32_t b[2][4];
                ldsm_x4(b[0], ob); ldsm_x4(b[1], ob + 64);
#pragma unroll
                for (int ki = 0; ki < 4; ki++)
#pragma unroll
                    for (int mi = 0; mi < 5; mi++) mma16816(acc[mi], wf[mi * 4 + ki], b[ki >> 1][(ki & 1) * 2], b[ki >> 1][(ki & 1) * 2 + 1]);
                if (kh == 1) {
#pragma unroll
                    for (int mi = 0; mi < 5; mi++)
                        *reinterpret_cast<float4*>(&sm.wred[mg][mi][lane * 4]) = make_float4(acc[mi][0], acc[mi][1], acc[mi][2], acc[mi][3]);
                }
                bar_sync(BAR_WO + mg, 64);
                if (kh == 0) {
                    float* dst = acc_dst_g + (size_t)s * (MEM_ * D_);
#pragma unroll
                    for (int mi = 0; mi < 5; mi++) {
                        float4 o2 = *reinterpret_cast<float4*>(&sm.wred[mg][mi][lane * 4]);
                        asm volatile("red.global.add.v2.f32 [%0], {%1,%2};" ::"l"(dst + mi * 128), "f"(acc[mi][0] + o2.x), "f"(acc[mi][1] + o2.y) : "memory");
                        asm volatile("red.global.add.v2.f32 [%0], {%1,%2};" ::"l"(dst + mi * 128 + 64), "f"(acc[mi][2] + o2.z), "f"(acc[mi][3] + o2.w) : "memory");
                    }
                    __threadfence();
                    __syncwarp();
                    if (lane == 0) atomicAdd(&g_cnt[s * 32], 1u);
                }
            }
            if (FUSE_X) bar_arrive(BAR_GO, RT);
            PROF(9);
            prefetch_kv(s + 1, buf ^ 1);
            PROF(10);
        }
    }
}

__global__ void __launch_bounds__(128)
attn_x_kernel() {
    __shared__ __align__(16) bf16 sq[32][HL], sk[48][HL], sv[48][HL];
    const int s = blockIdx.x >> 5, h = blockIdx.x & 31;
    const int tid = threadIdx.x, lane = tid & 31, w = tid >> 5, g = lane >> 2, t = lane & 3;
    for (int i = tid; i < (32 + 40 + 40) * 16; i += 128) {
        int r = i >> 4, ch = i & 15;
        const bf16* src; bf16* dst;
        if (r < 32) { src = g_qkv + (size_t)(s * SEG_ + r) * (3 * HD_) + h * DH_; dst = sq[r]; }
        else if (r < 72) { int rr = r - 32; dst = sk[rr];
            src = rr < 8 ? g_kmem + ((size_t)s * MEM_ + rr) * HD_ + h * DH_ : g_qkv + (size_t)(s * SEG_ + rr - 8) * (3 * HD_) + HD_ + h * DH_; }
        else { int rr = r - 72; dst = sv[rr];
            src = rr < 8 ? g_vmem + ((size_t)s * MEM_ + rr) * HD_ + h * DH_ : g_qkv + (size_t)(s * SEG_ + rr - 8) * (3 * HD_) + 2 * HD_ + h * DH_; }
        cp_async16(smem_u32(dst + ch * 8), src + ch * 8);
    }
    cp_async_commit();
    for (int i = tid; i < 8 * 16; i += 128) *reinterpret_cast<uint4*>(&sv[40 + (i >> 4)][(i & 15) * 8]) = make_uint4(0, 0, 0, 0);
    cp_async_wait<0>();
    __syncthreads();
    const int rh = w & 1, dhh = w >> 1;
    float sc[5][4];
#pragma unroll
    for (int n = 0; n < 5; n++) sc[n][0] = sc[n][1] = sc[n][2] = sc[n][3] = 0.f;
#pragma unroll
    for (int kk = 0; kk < 8; kk++) {
        uint32_t a[4];
        ldsm_x4(a, smem_u32(&sq[rh * 16 + (lane & 15)][kk * 16 + (lane >> 4) * 8]));
#pragma unroll
        for (int n = 0; n < 5; n++) {
            uint32_t b[2];
            asm volatile("ldmatrix.sync.aligned.m8n8.x2.shared.b16 {%0,%1}, [%2];" : "=r"(b[0]), "=r"(b[1])
                         : "r"(smem_u32(&sk[n * 8 + (lane & 7)][kk * 16 + ((lane >> 3) & 1) * 8])));
            mma16816(sc[n], a, b[0], b[1]);
        }
    }
    const float scale = 0.08838834764831845f;
    float mx[2] = {-INFINITY, -INFINITY};
#pragma unroll
    for (int n = 0; n < 5; n++)
#pragma unroll
        for (int e = 0; e < 4; e++) {
            int row = rh * 16 + g + (e >> 1) * 8, key = n * 8 + 2 * t + (e & 1);
            float v = rbf(rbf(sc[n][e]) * scale);
            if (key > row + MEM_) v = -INFINITY;
            sc[n][e] = v;
            mx[e >> 1] = fmaxf(mx[e >> 1], v);
        }
#pragma unroll
    for (int o = 1; o < 4; o <<= 1) { mx[0] = fmaxf(mx[0], __shfl_xor_sync(0xffffffffu, mx[0], o)); mx[1] = fmaxf(mx[1], __shfl_xor_sync(0xffffffffu, mx[1], o)); }
    float sum[2] = {0.f, 0.f};
#pragma unroll
    for (int n = 0; n < 5; n++)
#pragma unroll
        for (int e = 0; e < 4; e++) { float ev = __expf(sc[n][e] - mx[e >> 1]); sc[n][e] = ev; sum[e >> 1] += ev; }
#pragma unroll
    for (int o = 1; o < 4; o <<= 1) { sum[0] += __shfl_xor_sync(0xffffffffu, sum[0], o); sum[1] += __shfl_xor_sync(0xffffffffu, sum[1], o); }
    float inv[2] = {1.0f / sum[0], 1.0f / sum[1]};
    uint32_t pa[3][4];
#pragma unroll
    for (int kt = 0; kt < 3; kt++) {
        pa[kt][0] = pack_bf16(sc[2 * kt][0] * inv[0], sc[2 * kt][1] * inv[0]);
        pa[kt][1] = pack_bf16(sc[2 * kt][2] * inv[1], sc[2 * kt][3] * inv[1]);
        if (kt < 2) {
            pa[kt][2] = pack_bf16(sc[2 * kt + 1][0] * inv[0], sc[2 * kt + 1][1] * inv[0]);
            pa[kt][3] = pack_bf16(sc[2 * kt + 1][2] * inv[1], sc[2 * kt + 1][3] * inv[1]);
        } else { pa[kt][2] = 0u; pa[kt][3] = 0u; }
    }
#pragma unroll
    for (int n = 0; n < 8; n++) {
        float o[4] = {0.f, 0.f, 0.f, 0.f};
#pragma unroll
        for (int kt = 0; kt < 3; kt++) {
            uint32_t b[2];
            asm volatile("ldmatrix.sync.aligned.m8n8.x2.trans.shared.b16 {%0,%1}, [%2];" : "=r"(b[0]), "=r"(b[1])
                         : "r"(smem_u32(&sv[kt * 16 + (lane & 15)][dhh * 64 + n * 8])));
            mma16816(o, pa[kt], b[0], b[1]);
        }
        int row = s * SEG_ + rh * 16 + g;
        bf16* dst = g_o + (size_t)row * HD_ + h * DH_ + dhh * 64 + n * 8 + 2 * t;
        *reinterpret_cast<uint32_t*>(dst) = pack_bf16(o[0], o[1]);
        *reinterpret_cast<uint32_t*>(dst + 8 * HD_) = pack_bf16(o[2], o[3]);
    }
}

typedef CUresult (*PFN_encodeTiled)(CUtensorMap*, CUtensorMapDataType, cuuint32_t, void*, const cuuint64_t*,
                                    const cuuint64_t*, const cuuint32_t*, const cuuint32_t*, CUtensorMapInterleave,
                                    CUtensorMapSwizzle, CUtensorMapL2promotion, CUtensorMapFloatOOBfill);
static PFN_encodeTiled p_encode = nullptr;

static CUtensorMap make_map(const void* ptr, uint64_t rows, uint64_t cols, uint64_t ld, uint32_t box_rows) {
    CUtensorMap m;
    cuuint64_t dims[2] = {cols, rows};
    cuuint64_t strides[1] = {ld * 2};
    cuuint32_t box[2] = {64, box_rows};
    cuuint32_t es[2] = {1, 1};
    p_encode(&m, CU_TENSOR_MAP_DATA_TYPE_BFLOAT16, 2, const_cast<void*>(ptr), dims, strides, box, es,
             CU_TENSOR_MAP_INTERLEAVE_NONE, CU_TENSOR_MAP_SWIZZLE_128B, CU_TENSOR_MAP_L2_PROMOTION_L2_128B,
             CU_TENSOR_MAP_FLOAT_OOB_FILL_NONE);
    return m;
}

template <int BN, int EPI>
static void launch_gemm(const CUtensorMap& a, const CUtensorMap& b0, const CUtensorMap& b1, const CUtensorMap& b2,
                        int nPerB, int M, int N, int K, EpiParams ep, cudaStream_t st, int splitk = 1) {
    constexpr int STAGE = 16384 + (BN / 64) * 8192;
    constexpr int NST = (200 * 1024) / STAGE;
    constexpr int SMEM = NST * STAGE + 1024;
    cudaFuncSetAttribute(gemm_kernel<BN, EPI>, cudaFuncAttributeMaxDynamicSharedMemorySize, SMEM);
    dim3 grid((N + BN - 1) / BN, M / 128, splitk);
    gemm_kernel<BN, EPI><<<grid, 384, SMEM, st>>>(a, b0, b1, b2, nPerB, N, K, ep);
}

extern "C" void kernel_launch(void* const* d_in, const int* in_sizes, int n_in, void* d_out, int out_size) {
    const bf16* x    = (const bf16*)d_in[0];
    const bf16* mem0 = (const bf16*)d_in[1];
    const bf16* Wq   = (const bf16*)d_in[2];
    const bf16* Wk   = (const bf16*)d_in[3];
    const bf16* Wv   = (const bf16*)d_in[4];
    const bf16* Wo   = (const bf16*)d_in[5];
    const bf16* w_in  = (const bf16*)d_in[8];
    const bf16* w_sp  = (const bf16*)d_in[9];
    const bf16* b_sp  = (const bf16*)d_in[10];
    const bf16* w_out = (const bf16*)d_in[11];
    bf16* out = (bf16*)d_out;
    cudaStream_t st = cudaStreamPerThread;

    if (!p_encode) {
        cudaDriverEntryPointQueryResult qr;
        cudaGetDriverEntryPoint("cuTensorMapEncodeTiled", (void**)&p_encode, cudaEnableDefault, &qr);
    }
    void *p_xn, *p_qkv, *p_z, *p_zg, *p_gate, *p_o, *p_acc, *p_cnt, *p_hx;
    cudaGetSymbolAddress(&p_xn, g_xn); cudaGetSymbolAddress(&p_qkv, g_qkv); cudaGetSymbolAddress(&p_z, g_z);
    cudaGetSymbolAddress(&p_zg, g_zg); cudaGetSymbolAddress(&p_gate, g_gate); cudaGetSymbolAddress(&p_o, g_o);
    cudaGetSymbolAddress(&p_acc, g_acc); cudaGetSymbolAddress(&p_cnt, g_cnt); cudaGetSymbolAddress(&p_hx, g_hx);

    CUtensorMap mA_xn  = make_map(p_xn, S_, D_, D_, 128);
    CUtensorMap mA_wsp = make_map(w_sp, S_, S_, S_, 128);
    CUtensorMap mA_zg  = make_map(p_zg, S_, FH_, FH_, 128);
    CUtensorMap mA_o   = make_map(p_o, S_, HD_, HD_, 128);
    CUtensorMap mB_wq  = make_map(Wq, D_, HD_, HD_, 64);
    CUtensorMap mB_wk  = make_map(Wk, D_, HD_, HD_, 64);
    CUtensorMap mB_wv  = make_map(Wv, D_, HD_, HD_, 64);
    CUtensorMap mB_win = make_map(w_in, D_, F_, F_, 64);
    CUtensorMap mB_z2  = make_map((bf16*)p_z + FH_, S_, FH_, F_, 64);
    CUtensorMap mB_wout = make_map(w_out, FH_, D_, D_, 64);
    CUtensorMap mB_wo  = make_map(Wo, HD_, D_, D_, 64);

    cudaMemsetAsync(p_acc, 0, sizeof(float) * NSEG_ * MEM_ * D_, st);
    cudaMemsetAsync(p_cnt, 0, sizeof(unsigned) * NSEG_ * 32, st);
    void* p_xcnt; cudaGetSymbolAddress(&p_xcnt, g_xcnt);
    cudaMemsetAsync(p_xcnt, 0, sizeof(unsigned) * H_ * NSEG_, st);
    cudaMemsetAsync(p_hx, 0, sizeof(uint2) * H_ * 4 * 256 * 2, st);

    static cudaStream_t st2 = nullptr;
    static cudaEvent_t ev_fork = nullptr, ev_join = nullptr;
    if (!st2) {
        cudaStreamCreateWithFlags(&st2, cudaStreamNonBlocking);
        cudaEventCreateWithFlags(&ev_fork, cudaEventDisableTiming);
        cudaEventCreateWithFlags(&ev_join, cudaEventDisableTiming);
    }
    ln_kernel<<<S_ / 8, 256, 0, st>>>(x);
    cudaEventRecord(ev_fork, st);
    cudaStreamWaitEvent(st2, ev_fork, 0);
    { EpiParams ep{(bf16*)p_z, F_, nullptr, nullptr}; launch_gemm<128, EPI_GELU>(mA_xn, mB_win, mB_win, mB_win, 1 << 20, S_, F_, D_, ep, st2); }
    ln2_kernel<<<S_ / 8, 256, 0, st2>>>();
    { EpiParams ep{(bf16*)p_zg, FH_, (const bf16*)p_z, b_sp}; launch_gemm<128, EPI_SP>(mA_wsp, mB_z2, mB_z2, mB_z2, 1 << 20, S_, FH_, S_, ep, st2); }
    { EpiParams ep{(bf16*)p_gate, D_, nullptr, nullptr}; launch_gemm<128, EPI_SILU>(mA_zg, mB_wout, mB_wout, mB_wout, 1 << 20, S_, D_, FH_, ep, st2); }
    cudaEventRecord(ev_join, st2);
    if (!FUSE_X) { EpiParams ep{(bf16*)p_qkv, 3 * HD_, nullptr, nullptr}; launch_gemm<256, EPI_STORE>(mA_xn, mB_wq, mB_wk, mB_wv, HD_, S_, 3 * HD_, D_, ep, st); }
    constexpr int RSM = (int)sizeof(RecurSmem) > 16 * 10240 ? (int)sizeof(RecurSmem) : 16 * 10240;
    cudaFuncSetAttribute(recur_kernel, cudaFuncAttributeMaxDynamicSharedMemorySize, RSM);
    recur_kernel<<<128, RT, RSM, st>>>(mem0, Wq, Wk, Wv, Wo);
    attn_x_kernel<<<NSEG_ * H_, 128, 0, st>>>();
    cudaStreamWaitEvent(st, ev_join, 0);
    { EpiParams ep{out, D_, x, (const bf16*)p_gate}; launch_gemm<128, EPI_FINAL>(mA_o, mB_wo, mB_wo, mB_wo, 1 << 20, S_, D_, HD_, ep, st); }
}
```
